```python
import torch

def _softmax(x, axis=-1):
    return torch.softmax(x, dim=axis)
def _gelu(x):
    return torch.nn.functional.gelu(x, approximate="tanh")
def _silu(x):
    return torch.nn.functional.silu(x)
def _sigmoid(x):
    return torch.sigmoid(x)
def _layernorm(x, axis=-1, eps=1e-5):
    m = x.mean(dim=axis, keepdim=True)
    v = x.var(dim=axis, keepdim=True, unbiased=False)
    return (x - m) / torch.sqrt(v + eps)
def _scatter_add(tgt, idx, src, axis=0):
    return tgt.clone().index_add_(axis, idx, src)
def _segment_sum(src, seg, n):
    out = torch.zeros((n,) + src.shape[1:], dtype=src.dtype)
    return out.index_add_(0, seg, src)
def _pad(x, pw):
    flat = tuple(v for pair in reversed(pw) for v in pair)
    return torch.nn.functional.pad(x, flat)

kernel_name = 'gated_mix__linear_attn_block__glu_gated_reglu__prompt'

def setup_inputs():

    _w = (lambda a: (lambda t: t.to(torch.bfloat16) if t.is_floating_point() else t)(torch.as_tensor(a)))
    def _A_setup():
        B, S, D = 1, 2048, 448
        return {
            "x": _w((lambda *s: torch.randn(*s, dtype=torch.bfloat16) * 0.05)(B, S, D)),
            "wqkv": _w((lambda *s: torch.randn(*s, dtype=torch.bfloat16) * 0.8)(D, 3 * D)),
            "wo": _w((lambda *s: torch.randn(*s, dtype=torch.bfloat16) * 0.05)(D, D)),
        }
    _A_in = _A_setup()

    def _B_setup():
        B, S, D, F = 1, 2048, 448, 1792
        return {
            "x": _w((lambda *s: torch.randn(*s, dtype=torch.bfloat16) * 0.05)(B, S, D)),
            "W_gate": _w((lambda *s: torch.randn(*s, dtype=torch.bfloat16) * 1.6)(D, F) * (2.0 / D) ** 0.5),
            "W_up": _w((lambda *s: torch.randn(*s, dtype=torch.bfloat16) * 1.6)(D, F) * (2.0 / D) ** 0.5),
            "W_down": _w((lambda *s: torch.randn(*s, dtype=torch.bfloat16) * 1.6)(F, D) * (1.0 / F) ** 0.5),
        }
    _B_in = _B_setup()

    return {
        "A_x": _A_in["x"],
        "A_wqkv": _A_in["wqkv"],
        "A_wo": _A_in["wo"],
        "B_x": _B_in["x"],
        "B_W_gate": _B_in["W_gate"],
        "B_W_up": _B_in["W_up"],
        "B_W_down": _B_in["W_down"],
        "gate_w": _w((lambda *s: torch.randn(*s, dtype=torch.bfloat16) * 0.05)(448) * 16.0),
    }

def reference(A_x, A_wqkv, A_wo, B_x, B_W_gate, B_W_up, B_W_down, gate_w):
    def _A_ref(x, wqkv, wo):
        B, S, D = x.shape
        H = 16; Dh = D // H
        qkv = (lambda x, *d: x.permute(*d))((x @ wqkv).reshape(B, S, 3, H, Dh), 2, 0, 3, 1, 4)
        q, k, v = qkv[0], qkv[1], qkv[2]
        phi = lambda t: torch.where(t > 0, t + 1, torch.exp(t)) + 1e-6
        pq, pk = phi(q), phi(k)
        kv = torch.einsum("bhsd,bhse->bhde", pk, v)
        z = torch.einsum("bhsd->bhd", pk)
        num = torch.einsum("bhqd,bhde->bhqe", pq, kv)
        den = torch.einsum("bhqd,bhd->bhq", pq, z)[..., None] + 1e-6
        o = num / den
        return (lambda x, *d: x.permute(*d))(o, 0, 2, 1, 3).reshape(B, S, D) @ wo

    def _B_ref(x, W_gate, W_up, W_down):
        gate = torch.einsum("bsd,df->bsf", x, W_gate)
        up = torch.einsum("bsd,df->bsf", x, W_up)
        gate = gate * (lambda x, dt: x.to(dt))(gate > 0, gate.dtype)
        h = gate * up
        return torch.einsum("bsf,fd->bsd", h, W_down)

    x = A_x
    g = _sigmoid((x * gate_w).sum(-1, keepdims=True))
    a = _A_ref(x, A_wqkv, A_wo)
    b = _B_ref(x, B_W_gate, B_W_up, B_W_down)
    return g * a + (1 - g) * b
```

```cpp
#include <cuda_runtime.h>
#include <cuda_bf16.h>
#include <cuda.h>
#include <stdint.h>

namespace {

constexpr int kS = 2048, kD = 448, kF = 1792;
constexpr int NTHREADS = 384;
constexpr int NCTA = 128;
constexpr uint32_t OFF_X = 0;
constexpr uint32_t OFF_RING = 114688;
constexpr uint32_t SLOT_BYTES = 14336;
constexpr int NSLOT = 7;
constexpr uint32_t OFF_STG = 215040;
constexpr uint32_t OFF_MISC = 231424;
constexpr uint32_t SMEM_BYTES = 232448;
constexpr uint32_t BAR_FULL = OFF_MISC, BAR_EMPTY = OFF_MISC + 56, BAR_XFULL = OFF_MISC + 112;
constexpr uint32_t BAR_STGFREE = OFF_MISC + 168, BAR_KVDONE = OFF_MISC + 176, BAR_AUX = OFF_MISC + 184;
constexpr uint32_t OFF_G = OFF_MISC + 256;
constexpr int P1_LAG = 3;

__device__ float g_kvacc[2][8][4096];
__device__ unsigned int g_counter;

#define TS(role, idx)
#define TSG(role, idx)

__device__ __forceinline__ void mbar_init(uint32_t bar, uint32_t cnt) {
    asm volatile("mbarrier.init.shared::cta.b64 [%0], %1;" :: "r"(bar), "r"(cnt) : "memory");
}
__device__ __forceinline__ void mbar_expect_tx(uint32_t bar, uint32_t bytes) {
    asm volatile("mbarrier.arrive.expect_tx.shared::cta.b64 _, [%0], %1;" :: "r"(bar), "r"(bytes) : "memory");
}
__device__ __forceinline__ void mbar_arrive(uint32_t bar) {
    asm volatile("mbarrier.arrive.shared::cta.b64 _, [%0];" :: "r"(bar) : "memory");
}
__device__ __forceinline__ void mbar_arrive_cluster(uint32_t bar) {
    asm volatile("mbarrier.arrive.shared::cluster.b64 _, [%0];" :: "r"(bar) : "memory");
}
__device__ __forceinline__ void mbar_wait(uint32_t bar, uint32_t parity) {
    asm volatile("{\n"
                 ".reg .pred p;\n"
                 ".reg .u32 c;\n"
                 "mbarrier.try_wait.parity.shared::cta.b64 p, [%0], %1;\n"
                 "@p bra DONE;\n"
                 "mov.u32 c, 0;\n"
                 "AGAIN:\n"
                 "mbarrier.try_wait.parity.shared::cta.b64 p, [%0], %1;\n"
                 "@p bra DONE;\n"
                 "add.u32 c, c, 1;\n"
                 "setp.lt.u32 p, c, 4194304;\n"
                 "@p bra AGAIN;\n"
                 "trap;\n"
                 "DONE:\n"
                 "}" :: "r"(bar), "r"(parity) : "memory");
}
__device__ __forceinline__ uint32_t mapa(uint32_t addr, uint32_t cta) {
    uint32_t r; asm("mapa.shared::cluster.u32 %0, %1, %2;" : "=r"(r) : "r"(addr), "r"(cta)); return r;
}
__device__ __forceinline__ bool elect_one() {
    uint32_t p;
    asm volatile("{ .reg .pred P; elect.sync _|P, 0xffffffff; selp.u32 %0, 1, 0, P; }" : "=r"(p));
    return p;
}
__device__ __forceinline__ void tma2d(uint32_t dst, const CUtensorMap* m, int c0, int c1, uint32_t bar) {
    asm volatile("cp.async.bulk.tensor.2d.shared::cluster.global.mbarrier::complete_tx::bytes [%0], [%1, {%3, %4}], [%2];"
                 :: "r"(dst), "l"(m), "r"(bar), "r"(c0), "r"(c1) : "memory");
}
__device__ __forceinline__ void tma2d_mc(uint32_t dst, const CUtensorMap* m, int c0, int c1, uint32_t bar) {
    asm volatile("cp.async.bulk.tensor.2d.shared::cluster.global.mbarrier::complete_tx::bytes.multicast::cluster [%0], [%1, {%3, %4}], [%2], %5;"
                 :: "r"(dst), "l"(m), "r"(bar), "r"(c0), "r"(c1), "h"((uint16_t)3) : "memory");
}
__device__ __forceinline__ void tma3d_mc(uint32_t dst, const CUtensorMap* m, int c0, int c1, int c2, uint32_t bar) {
    asm volatile("cp.async.bulk.tensor.3d.shared::cluster.global.mbarrier::complete_tx::bytes.multicast::cluster [%0], [%1, {%3, %4, %5}], [%2], %6;"
                 :: "r"(dst), "l"(m), "r"(bar), "r"(c0), "r"(c1), "r"(c2), "h"((uint16_t)3) : "memory");
}
__device__ __forceinline__ void tma_reduce2d(const CUtensorMap* m, uint32_t src, int c0, int c1) {
    asm volatile("cp.reduce.async.bulk.tensor.2d.global.shared::cta.add.bulk_group [%0, {%2, %3}], [%1];"
                 :: "l"(m), "r"(src), "r"(c0), "r"(c1) : "memory");
}
__device__ __forceinline__ void prefetch_map(const CUtensorMap* m) {
    asm volatile("prefetch.tensormap [%0];" :: "l"(m) : "memory");
}
__device__ __forceinline__ void wg_fence() { asm volatile("wgmma.fence.sync.aligned;" ::: "memory"); }
__device__ __forceinline__ void wg_commit() { asm volatile("wgmma.commit_group.sync.aligned;" ::: "memory"); }
template <int N> __device__ __forceinline__ void wg_wait() { asm volatile("wgmma.wait_group.sync.aligned %0;" :: "n"(N) : "memory"); }
template <int N> __device__ __forceinline__ void reg_fence(float (&d)[N]) {
#pragma unroll
    for (int i = 0; i < N; i++) asm volatile("" : "+f"(d[i]) :: "memory");
}
template <int N> __device__ __forceinline__ void reg_fence(uint32_t (&d)[N]) {
#pragma unroll
    for (int i = 0; i < N; i++) asm volatile("" : "+r"(d[i]) :: "memory");
}
__device__ __forceinline__ void fence_async_smem() { asm volatile("fence.proxy.async.shared::cta;" ::: "memory"); }
template <int ID, int N> __device__ __forceinline__ void bar_sync() { asm volatile("bar.sync %0, %1;" :: "n"(ID), "n"(N) : "memory"); }
template <int ID, int N> __device__ __forceinline__ void bar_arrive() { asm volatile("bar.arrive %0, %1;" :: "n"(ID), "n"(N) : "memory"); }
__device__ __forceinline__ void ldsm4(uint32_t* r, uint32_t addr) {
    asm volatile("ldmatrix.sync.aligned.m8n8.x4.shared.b16 {%0, %1, %2, %3}, [%4];"
                 : "=r"(r[0]), "=r"(r[1]), "=r"(r[2]), "=r"(r[3]) : "r"(addr) : "memory");
}
__device__ __forceinline__ void stsm4(uint32_t addr, uint32_t r0, uint32_t r1, uint32_t r2, uint32_t r3) {
    asm volatile("stmatrix.sync.aligned.m8n8.x4.shared.b16 [%0], {%1, %2, %3, %4};"
                 :: "r"(addr), "r"(r0), "r"(r1), "r"(r2), "r"(r3) : "memory");
}
__device__ __forceinline__ uint32_t pack_bf16(float lo, float hi) {
    uint32_t r; asm("cvt.rn.bf16x2.f32 %0, %1, %2;" : "=r"(r) : "f"(hi), "f"(lo)); return r;
}
__device__ __forceinline__ uint32_t pack_relu_bf16(float lo, float hi) {
    uint32_t r; asm("cvt.rn.relu.bf16x2.f32 %0, %1, %2;" : "=r"(r) : "f"(hi), "f"(lo)); return r;
}
__device__ __forceinline__ uint32_t mul_bf16x2(uint32_t a, uint32_t b) {
    uint32_t r; asm("mul.rn.bf16x2 %0, %1, %2;" : "=r"(r) : "r"(a), "r"(b)); return r;
}
__device__ __forceinline__ float phi(float t) {
    float e; asm("ex2.approx.ftz.f32 %0, %1;" : "=f"(e) : "f"(fminf(t, 0.f) * 1.4426950408889634f));
    return e + (fmaxf(t, 0.f) + 1e-6f);
}
__device__ __forceinline__ uint64_t mkdesc(uint32_t addr, uint32_t lbo, uint32_t sbo, uint32_t sw) {
    uint32_t lo = ((addr & 0x3FFFF) >> 4) | ((lbo >> 4) << 16);
    uint32_t hi = (sbo >> 4) | (sw << 30);
    return ((uint64_t)hi << 32) | lo;
}

__device__ __forceinline__ void wgmma_rs56(float (&d)[28], uint32_t a0, uint32_t a1, uint32_t a2, uint32_t a3, uint64_t db, int sd) {
    asm volatile("{ .reg .pred p; setp.ne.b32 p, %33, 0;\n"
        "wgmma.mma_async.sync.aligned.m64n56k16.f32.bf16.bf16 {"
        "%0, %1, %2, %3, %4, %5, %6, %7, %8, %9, %10, %11, %12, %13, %14, %15, "
        "%16, %17, %18, %19, %20, %21, %22, %23, %24, %25, %26, %27"
        "}, {%28, %29, %30, %31}, %32, p, 1, 1, 1; }"
        : "+f"(d[0]), "+f"(d[1]), "+f"(d[2]), "+f"(d[3]), "+f"(d[4]), "+f"(d[5]), "+f"(d[6]), "+f"(d[7]),
          "+f"(d[8]), "+f"(d[9]), "+f"(d[10]), "+f"(d[11]), "+f"(d[12]), "+f"(d[13]), "+f"(d[14]), "+f"(d[15]),
          "+f"(d[16]), "+f"(d[17]), "+f"(d[18]), "+f"(d[19]), "+f"(d[20]), "+f"(d[21]), "+f"(d[22]), "+f"(d[23]),
          "+f"(d[24]), "+f"(d[25]), "+f"(d[26]), "+f"(d[27])
        : "r"(a0), "r"(a1), "r"(a2), "r"(a3), "l"(db), "r"(sd));
}
__device__ __forceinline__ void wgmma_rs64(float (&d)[32], uint32_t a0, uint32_t a1, uint32_t a2, uint32_t a3, uint64_t db, int sd) {
    asm volatile("{ .reg .pred p; setp.ne.b32 p, %37, 0;\n"
        "wgmma.mma_async.sync.aligned.m64n64k16.f32.bf16.bf16 {"
        "%0, %1, %2, %3, %4, %5, %6, %7, %8, %9, %10, %11, %12, %13, %14, %15, "
        "%16, %17, %18, %19, %20, %21, %22, %23, %24, %25, %26, %27, %28, %29, %30, %31"
        "}, {%32, %33, %34, %35}, %36, p, 1, 1, 1; }"
        : "+f"(d[0]), "+f"(d[1]), "+f"(d[2]), "+f"(d[3]), "+f"(d[4]), "+f"(d[5]), "+f"(d[6]), "+f"(d[7]),
          "+f"(d[8]), "+f"(d[9]), "+f"(d[10]), "+f"(d[11]), "+f"(d[12]), "+f"(d[13]), "+f"(d[14]), "+f"(d[15]),
          "+f"(d[16]), "+f"(d[17]), "+f"(d[18]), "+f"(d[19]), "+f"(d[20]), "+f"(d[21]), "+f"(d[22]), "+f"(d[23]),
          "+f"(d[24]), "+f"(d[25]), "+f"(d[26]), "+f"(d[27]), "+f"(d[28]), "+f"(d[29]), "+f"(d[30]), "+f"(d[31])
        : "r"(a0), "r"(a1), "r"(a2), "r"(a3), "l"(db), "r"(sd));
}
__device__ __forceinline__ void wgmma_rs224(float (&d)[112], uint32_t a0, uint32_t a1, uint32_t a2, uint32_t a3, uint64_t db, int sd) {
    asm volatile("{ .reg .pred p; setp.ne.b32 p, %117, 0;\n"
        "wgmma.mma_async.sync.aligned.m64n224k16.f32.bf16.bf16 {"
        "%0, %1, %2, %3, %4, %5, %6, %7, %8, %9, %10, %11, %12, %13, %14, %15, "
        "%16, %17, %18, %19, %20, %21, %22, %23, %24, %25, %26, %27, %28, %29, %30, %31, "
        "%32, %33, %34, %35, %36, %37, %38, %39, %40, %41, %42, %43, %44, %45, %46, %47, "
        "%48, %49, %50, %51, %52, %53, %54, %55, %56, %57, %58, %59, %60, %61, %62, %63, "
        "%64, %65, %66, %67, %68, %69, %70, %71, %72, %73, %74, %75, %76, %77, %78, %79, "
        "%80, %81, %82, %83, %84, %85, %86, %87, %88, %89, %90, %91, %92, %93, %94, %95, "
        "%96, %97, %98, %99, %100, %101, %102, %103, %104, %105, %106, %107, %108, %109, %110, %111"
        "}, {%112, %113, %114, %115}, %116, p, 1, 1, 1; }"
        : "+f"(d[0]), "+f"(d[1]), "+f"(d[2]), "+f"(d[3]), "+f"(d[4]), "+f"(d[5]), "+f"(d[6]), "+f"(d[7]),
          "+f"(d[8]), "+f"(d[9]), "+f"(d[10]), "+f"(d[11]), "+f"(d[12]), "+f"(d[13]), "+f"(d[14]), "+f"(d[15]),
          "+f"(d[16]), "+f"(d[17]), "+f"(d[18]), "+f"(d[19]), "+f"(d[20]), "+f"(d[21]), "+f"(d[22]), "+f"(d[23]),
          "+f"(d[24]), "+f"(d[25]), "+f"(d[26]), "+f"(d[27]), "+f"(d[28]), "+f"(d[29]), "+f"(d[30]), "+f"(d[31]),
          "+f"(d[32]), "+f"(d[33]), "+f"(d[34]), "+f"(d[35]), "+f"(d[36]), "+f"(d[37]), "+f"(d[38]), "+f"(d[39]),
          "+f"(d[40]), "+f"(d[41]), "+f"(d[42]), "+f"(d[43]), "+f"(d[44]), "+f"(d[45]), "+f"(d[46]), "+f"(d[47]),
          "+f"(d[48]), "+f"(d[49]), "+f"(d[50]), "+f"(d[51]), "+f"(d[52]), "+f"(d[53]), "+f"(d[54]), "+f"(d[55]),
          "+f"(d[56]), "+f"(d[57]), "+f"(d[58]), "+f"(d[59]), "+f"(d[60]), "+f"(d[61]), "+f"(d[62]), "+f"(d[63]),
          "+f"(d[64]), "+f"(d[65]), "+f"(d[66]), "+f"(d[67]), "+f"(d[68]), "+f"(d[69]), "+f"(d[70]), "+f"(d[71]),
          "+f"(d[72]), "+f"(d[73]), "+f"(d[74]), "+f"(d[75]), "+f"(d[76]), "+f"(d[77]), "+f"(d[78]), "+f"(d[79]),
          "+f"(d[80]), "+f"(d[81]), "+f"(d[82]), "+f"(d[83]), "+f"(d[84]), "+f"(d[85]), "+f"(d[86]), "+f"(d[87]),
          "+f"(d[88]), "+f"(d[89]), "+f"(d[90]), "+f"(d[91]), "+f"(d[92]), "+f"(d[93]), "+f"(d[94]), "+f"(d[95]),
          "+f"(d[96]), "+f"(d[97]), "+f"(d[98]), "+f"(d[99]), "+f"(d[100]), "+f"(d[101]), "+f"(d[102]), "+f"(d[103]),
          "+f"(d[104]), "+f"(d[105]), "+f"(d[106]), "+f"(d[107]), "+f"(d[108]), "+f"(d[109]), "+f"(d[110]), "+f"(d[111])
        : "r"(a0), "r"(a1), "r"(a2), "r"(a3), "l"(db), "r"(sd));
}
__device__ __forceinline__ void wgmma_ss64_tt(float (&d)[32], uint64_t da, uint64_t db, int sd) {
    asm volatile("{ .reg .pred p; setp.ne.b32 p, %34, 0;\n"
        "wgmma.mma_async.sync.aligned.m64n64k16.f32.bf16.bf16 {"
        "%0, %1, %2, %3, %4, %5, %6, %7, %8, %9, %10, %11, %12, %13, %14, %15, "
        "%16, %17, %18, %19, %20, %21, %22, %23, %24, %25, %26, %27, %28, %29, %30, %31"
        "}, %32, %33, p, 1, 1, 1, 1; }"
        : "+f"(d[0]), "+f"(d[1]), "+f"(d[2]), "+f"(d[3]), "+f"(d[4]), "+f"(d[5]), "+f"(d[6]), "+f"(d[7]),
          "+f"(d[8]), "+f"(d[9]), "+f"(d[10]), "+f"(d[11]), "+f"(d[12]), "+f"(d[13]), "+f"(d[14]), "+f"(d[15]),
          "+f"(d[16]), "+f"(d[17]), "+f"(d[18]), "+f"(d[19]), "+f"(d[20]), "+f"(d[21]), "+f"(d[22]), "+f"(d[23]),
          "+f"(d[24]), "+f"(d[25]), "+f"(d[26]), "+f"(d[27]), "+f"(d[28]), "+f"(d[29]), "+f"(d[30]), "+f"(d[31])
        : "l"(da), "l"(db), "r"(sd));
}

struct Ring {
    uint32_t slot, phase;
    __device__ __forceinline__ void advance() { if (++slot == NSLOT) { slot = 0; phase ^= 1; } }
};

__global__ void __cluster_dims__(2, 1, 1) __launch_bounds__(NTHREADS, 1)
fused_kernel(const __grid_constant__ CUtensorMap mX, const __grid_constant__ CUtensorMap mQKV,
             const __grid_constant__ CUtensorMap mG, const __grid_constant__ CUtensorMap mU,
             const __grid_constant__ CUtensorMap mD, const __grid_constant__ CUtensorMap mO,
             const __grid_constant__ CUtensorMap mOut,
             const __nv_bfloat16* __restrict__ gate_w, __nv_bfloat16* __restrict__ out)
{
    extern __shared__ __align__(1024) unsigned char smem[];
    const uint32_t sb = (uint32_t)__cvta_generic_to_shared(smem);
    const int tid = threadIdx.x, warp = tid >> 5, lane = tid & 31;
    const int rank = blockIdx.x & 1, j = (blockIdx.x >> 1) & 7;
    const int row0 = ((blockIdx.x >> 4) * 2 + rank) * 128;

    TSG(2, 0); TS(2, 1);
    if (warp == 8) {
        if (elect_one()) {
            if (sb & 1023) asm volatile("trap;");
            prefetch_map(&mX); prefetch_map(&mQKV);
            for (int s = 0; s < NSLOT; s++) {
                mbar_init(sb + BAR_FULL + 8 * s, 1);
                mbar_init(sb + BAR_EMPTY + 8 * s, 4);
                mbar_init(sb + BAR_XFULL + 8 * s, 1);
            }
            mbar_init(sb + BAR_STGFREE, 4);
            mbar_init(sb + BAR_KVDONE, 8);
            mbar_init(sb + BAR_AUX, 3);
            asm volatile("fence.mbarrier_init.release.cluster;" ::: "memory");
            mbar_expect_tx(sb + BAR_XFULL, 16384);
            tma2d(sb + OFF_X, &mX, 0, row0, sb + BAR_XFULL);
        }
        __syncwarp();
    }
    asm volatile("barrier.cluster.arrive.relaxed.aligned;" ::: "memory");
    asm volatile("barrier.cluster.wait.aligned;" ::: "memory");

    if (warp >= 8) {
        asm volatile("setmaxnreg.dec.sync.aligned.u32 40;");
        if (warp == 8) {
            if (elect_one()) {
                Ring r{0, 1};
                auto acquire = [&](uint32_t bytes) -> uint32_t {
                    mbar_wait(sb + BAR_EMPTY + 8 * r.slot, r.phase);
                    mbar_expect_tx(sb + BAR_FULL + 8 * r.slot, bytes);
                    return sb + OFF_RING + r.slot * SLOT_BYTES;
                };
                #pragma unroll 1
                for (int s = 0; s < 14; s++) {
                    uint32_t dst = acquire(12288);
                    tma3d_mc(dst + rank * 6144, &mQKV, 56 * j, 32 * s + 16 * rank, 0, sb + BAR_FULL + 8 * r.slot);
                    r.advance();
                    if (s < 6) {
                        mbar_expect_tx(sb + BAR_XFULL + 8 * (s + 1), 16384);
                        tma2d(sb + OFF_X + (s + 1) * 16384, &mX, 64 * (s + 1), row0, sb + BAR_XFULL + 8 * (s + 1));
                    }
                    if (s == 6) { prefetch_map(&mG); prefetch_map(&mU); prefetch_map(&mD); prefetch_map(&mO); prefetch_map(&mOut); }
                }
                #pragma unroll 1
                for (int s = 0; s < 28; s++) {
                    uint32_t dst = acquire(14336);
                    const int ks = s < 14 ? s : s - 14;
                    tma3d_mc(dst + rank * 7168, s < 14 ? &mG : &mU, 0, 32 * ks + 16 * rank, 7 * j, sb + BAR_FULL + 8 * r.slot);
                    r.advance();
                }
                int c = j == 7 ? 0 : j;
                #pragma unroll 1
                for (int c0 = 0; c0 < 7; c0++) {
                    uint32_t dst = acquire(14336);
                    tma2d_mc(dst + rank * 7168, &mD, 64 * c, 224 * j + 56 * rank, sb + BAR_FULL + 8 * r.slot);
                    r.advance();
                    dst = acquire(14336);
                    tma2d_mc(dst + rank * 7168, &mD, 64 * c, 224 * j + 112 + 56 * rank, sb + BAR_FULL + 8 * r.slot);
                    r.advance();
                    dst = acquire(8192);
                    tma2d_mc(dst + rank * 4096, &mO, 64 * c, 56 * j + 32 * rank, sb + BAR_FULL + 8 * r.slot);
                    r.advance();
                    if (++c == 7) c = 0;
                }
            }
        } else {
            const int ht = tid - 288, hw = warp - 9;
            unsigned int cnt0;
            asm volatile("ld.relaxed.gpu.global.u32 %0, [%1];" : "=r"(cnt0) : "l"(&g_counter) : "memory");
            {
                uint4* o = reinterpret_cast<uint4*>(out) + blockIdx.x * 896;
                for (int q = ht; q < 896; q += 96) o[q] = make_uint4(0, 0, 0, 0);
            }
            const unsigned int epoch = cnt0 >> 7;
            if (ht < 64)
                reinterpret_cast<float4*>(&g_kvacc[(epoch + 1) & 1][0][0])[blockIdx.x * 64 + ht] = make_float4(0.f, 0.f, 0.f, 0.f);
            const int r4 = lane >> 3, c8 = lane & 7;
            #pragma unroll 1
            for (int half = 0; half < 2; half++) {
                float acc[6] = {0.f, 0.f, 0.f, 0.f, 0.f, 0.f};
                #pragma unroll 1
                for (int kc = 0; kc < 7; kc++) {
                    const uint4 w = __ldg(reinterpret_cast<const uint4*>(gate_w + kc * 64 + c8 * 8));
                    if (half == 0) mbar_wait(sb + BAR_XFULL + 8 * kc, 0);
                    const uint32_t wv[4] = {w.x, w.y, w.z, w.w};
                    #pragma unroll
                    for (int p = 0; p < 6; p++) {
                        const int row = min(((half * 6 + p) * 3 + hw) * 4 + r4, 127);
                        uint32_t x0, x1, x2, x3;
                        asm volatile("ld.shared.v4.u32 {%0, %1, %2, %3}, [%4];" : "=r"(x0), "=r"(x1), "=r"(x2), "=r"(x3)
                                     : "r"(sb + OFF_X + kc * 16384 + row * 128 + ((c8 ^ (row & 7)) << 4)));
                        const uint32_t xv[4] = {x0, x1, x2, x3};
                        #pragma unroll
                        for (int e = 0; e < 4; e++) {
                            acc[p] = fmaf(__uint_as_float(xv[e] << 16), __uint_as_float(wv[e] << 16), acc[p]);
                            acc[p] = fmaf(__uint_as_float(xv[e] & 0xffff0000u), __uint_as_float(wv[e] & 0xffff0000u), acc[p]);
                        }
                    }
                }
                #pragma unroll
                for (int p = 0; p < 6; p++) {
                    float v = acc[p];
                    v += __shfl_xor_sync(0xffffffffu, v, 1);
                    v += __shfl_xor_sync(0xffffffffu, v, 2);
                    v += __shfl_xor_sync(0xffffffffu, v, 4);
                    const int row = ((half * 6 + p) * 3 + hw) * 4 + r4;
                    if (c8 == 0 && row < 128)
                        *reinterpret_cast<float*>(smem + OFF_G + row * 4) = 1.f / (1.f + __expf(-v));
                }
            }
            TS(2, 2);
            bar_sync<3, 96>();
            if (ht == 0) {
                mbar_wait(sb + BAR_KVDONE, 0);
                TS(2, 3);
                asm volatile("fence.acq_rel.gpu;" ::: "memory");
                asm volatile("red.relaxed.gpu.global.add.u32 [%0], 1;" :: "l"(&g_counter) : "memory");
                TS(2, 4);
                const unsigned int target = (epoch + 1) << 7;
                unsigned int v; int it = 0;
                do {
                    asm volatile("ld.acquire.gpu.global.u32 %0, [%1];" : "=r"(v) : "l"(&g_counter) : "memory");
                    if (++it > (1 << 22)) asm volatile("trap;");
                } while ((int)(v - target) < 0);
                asm volatile("fence.proxy.async;" ::: "memory");
                TS(2, 5);
            }
            bar_sync<3, 96>();
            const float4* src = reinterpret_cast<const float4*>(&g_kvacc[epoch & 1][j][0]);
            #pragma unroll 2
            for (int q = ht; q < 512; q += 96) {
                const float4 a = __ldcg(src + 2 * q), b = __ldcg(src + 2 * q + 1);
                const int d = q >> 3, c = q & 7;
                asm volatile("st.shared.v4.u32 [%0], {%1, %2, %3, %4};"
                             :: "r"(sb + OFF_STG + d * 128 + ((c ^ (d & 7)) << 4)), "r"(pack_bf16(a.x, a.y)), "r"(pack_bf16(a.z, a.w)),
                                "r"(pack_bf16(b.x, b.y)), "r"(pack_bf16(b.z, b.w)) : "memory");
            }
            fence_async_smem();
            __syncwarp();
            if (lane == 0) mbar_arrive(sb + BAR_AUX);
            TS(2, 6);
        }
    } else {
        asm volatile("setmaxnreg.inc.sync.aligned.u32 232;");
        const int wg = warp >> 2, w4 = warp & 3;
        const int q4 = lane & 3, g8 = lane >> 2;
        unsigned int cnt0;
        asm volatile("ld.relaxed.gpu.global.u32 %0, [%1];" : "=r"(cnt0) : "l"(&g_counter) : "memory");
        const int lrow = w4 * 16 + (lane & 15);
        const uint32_t ltile = lrow * 128, lx = ((lane >> 4) ^ (lrow & 7)) << 4;
        const uint32_t xa = sb + OFF_X + wg * 8192 + ltile;
        const uint32_t empty_dst = mapa(sb + BAR_EMPTY, w4 & 1);
        const bool signaller = lane == 0 && w4 < 2;
        Ring r{0, 0};
        uint32_t prev = 0;
        auto release = [&](uint32_t slot) { if (signaller) mbar_arrive_cluster(empty_dst + 8 * slot); };
        uint32_t a0[8], a1[8];
        TS(wg, 0);

        float aq[28], ak[28], av[28];
        mbar_wait(sb + BAR_XFULL, 0);
        TS(wg, 1);
        ldsm4(a0, xa + lx); ldsm4(a0 + 4, xa + (lx ^ 32));
        #pragma unroll 1
        for (int it = 0; it < 7; it++) {
            if (wg == 1 && 2 * it == 14 - P1_LAG) bar_sync<4, 256>();
            mbar_wait(sb + BAR_FULL + 8 * r.slot, r.phase);
            if (it == 0) TS(wg, 2);
            {
                const uint32_t b = sb + OFF_RING + r.slot * SLOT_BYTES;
                wg_fence();
                wgmma_rs56(aq, a0[0], a0[1], a0[2], a0[3], mkdesc(b, 16, 1024, 1), it);
                wgmma_rs56(ak, a0[0], a0[1], a0[2], a0[3], mkdesc(b + 2048, 16, 1024, 1), it);
                wgmma_rs56(av, a0[0], a0[1], a0[2], a0[3], mkdesc(b + 4096, 16, 1024, 1), it);
                wgmma_rs56(aq, a0[4], a0[5], a0[6], a0[7], mkdesc(b + 6144, 16, 1024, 1), 1);
                wgmma_rs56(ak, a0[4], a0[5], a0[6], a0[7], mkdesc(b + 8192, 16, 1024, 1), 1);
                wgmma_rs56(av, a0[4], a0[5], a0[6], a0[7], mkdesc(b + 10240, 16, 1024, 1), 1);
                wg_commit();
            }
            wg_wait<1>();
            if (it > 0) release(prev);
            prev = r.slot; r.advance();
            ldsm4(a1, xa + it * 16384 + (lx ^ 64)); ldsm4(a1 + 4, xa + it * 16384 + (lx ^ 96));
            if (wg == 1 && 2 * it + 1 == 14 - P1_LAG) bar_sync<4, 256>();
            mbar_wait(sb + BAR_FULL + 8 * r.slot, r.phase);
            {
                const uint32_t b = sb + OFF_RING + r.slot * SLOT_BYTES;
                wg_fence();
                wgmma_rs56(aq, a1[0], a1[1], a1[2], a1[3], mkdesc(b, 16, 1024, 1), 1);
                wgmma_rs56(ak, a1[0], a1[1], a1[2], a1[3], mkdesc(b + 2048, 16, 1024, 1), 1);
                wgmma_rs56(av, a1[0], a1[1], a1[2], a1[3], mkdesc(b + 4096, 16, 1024, 1), 1);
                wgmma_rs56(aq, a1[4], a1[5], a1[6], a1[7], mkdesc(b + 6144, 16, 1024, 1), 1);
                wgmma_rs56(ak, a1[4], a1[5], a1[6], a1[7], mkdesc(b + 8192, 16, 1024, 1), 1);
                wgmma_rs56(av, a1[4], a1[5], a1[6], a1[7], mkdesc(b + 10240, 16, 1024, 1), 1);
                wg_commit();
            }
            wg_wait<1>();
            release(prev);
            prev = r.slot; r.advance();
            const int nx = it < 6 ? it + 1 : 0;
            mbar_wait(sb + BAR_XFULL + 8 * nx, 0);
            ldsm4(a0, xa + nx * 16384 + lx); ldsm4(a0 + 4, xa + nx * 16384 + (lx ^ 32));
        }
        wg_wait<0>();
        reg_fence(aq); reg_fence(ak); reg_fence(av);
        release(prev);
        if (wg == 0) bar_arrive<4, 256>();
        TS(wg, 3);

        uint32_t pq[14];
        {
            uint32_t pk[14], pv[14];
            #pragma unroll
            for (int i = 0; i < 14; i++) { pk[i] = pack_bf16(phi(ak[2 * i]), phi(ak[2 * i + 1])); pv[i] = pack_bf16(av[2 * i], av[2 * i + 1]); }
            if (wg == 1) mbar_wait(sb + BAR_STGFREE, 0);
            const uint32_t sk = sb + OFF_STG + ltile, sv = sk + 8192;
            const uint32_t ones = q4 == 0 ? 0x3f803f80u : 0u;
            #pragma unroll
            for (int t = 0; t < 3; t++) {
                stsm4(sk + (lx ^ (t * 32)), pk[4 * t], pk[4 * t + 1], pk[4 * t + 2], pk[4 * t + 3]);
                stsm4(sv + (lx ^ (t * 32)), pv[4 * t], pv[4 * t + 1], pv[4 * t + 2], pv[4 * t + 3]);
            }
            stsm4(sk + (lx ^ 96), pk[12], pk[13], 0u, 0u);
            stsm4(sv + (lx ^ 96), pv[12], pv[13], ones, ones);
            fence_async_smem();
            if (wg == 0) bar_sync<1, 128>(); else bar_sync<2, 128>();
            float kv[32];
            wg_fence();
            #pragma unroll
            for (int ks = 0; ks < 4; ks++)
                wgmma_ss64_tt(kv, mkdesc(sb + OFF_STG + ks * 2048, 16, 1024, 1), mkdesc(sb + OFF_STG + 8192 + ks * 2048, 16, 1024, 1), ks);
            wg_commit();
            #pragma unroll
            for (int i = 0; i < 14; i++) pq[i] = pack_bf16(phi(aq[2 * i]), phi(aq[2 * i + 1]));
            wg_wait<0>();
            reg_fence(kv);
            if (wg == 0 && lane == 0) mbar_arrive(sb + BAR_STGFREE);
            float* dst = &g_kvacc[(cnt0 >> 7) & 1][j][0];
            #pragma unroll
            for (int hh = 0; hh < 2; hh++) {
                const int d = w4 * 16 + g8 + 8 * hh;
                #pragma unroll
                for (int t = 0; t < 8; t++) {
                    const int e = 8 * t + 2 * q4;
                    float v0 = kv[4 * t + 2 * hh], v1 = kv[4 * t + 2 * hh + 1];
                    bool ok;
                    if (t < 7) ok = d < 28 ? e < 28 : (d < 56 && e >= 28);
                    else { ok = q4 == 0 && d < 56; if (d < 28) v1 = 0.f; else v0 = 0.f; }
                    if (ok) asm volatile("red.relaxed.gpu.global.add.v2.f32 [%0], {%1, %2};" :: "l"(dst + d * 64 + e), "f"(v0), "f"(v1) : "memory");
                }
            }
            __syncwarp();
            if (lane == 0) mbar_arrive(sb + BAR_KVDONE);
        }
        TS(wg, 4);

        uint32_t hp[56];
        float acc[112];
        #pragma unroll
        for (int pass = 0; pass < 2; pass++) {
            #pragma unroll 1
            for (int it = 0; it < 7; it++) {
                mbar_wait(sb + BAR_FULL + 8 * r.slot, r.phase);
                {
                    const uint32_t b = sb + OFF_RING + r.slot * SLOT_BYTES;
                    wg_fence();
                    wgmma_rs224(acc, a0[0], a0[1], a0[2], a0[3], mkdesc(b, 1024, 512, 2), it);
                    wgmma_rs224(acc, a0[4], a0[5], a0[6], a0[7], mkdesc(b + 7168, 1024, 512, 2), 1);
                    wg_commit();
                }
                wg_wait<1>();
                if (it > 0) release(prev);
                prev = r.slot; r.advance();
                ldsm4(a1, xa + it * 16384 + (lx ^ 64)); ldsm4(a1 + 4, xa + it * 16384 + (lx ^ 96));
                mbar_wait(sb + BAR_FULL + 8 * r.slot, r.phase);
                {
                    const uint32_t b = sb + OFF_RING + r.slot * SLOT_BYTES;
                    wg_fence();
                    wgmma_rs224(acc, a1[0], a1[1], a1[2], a1[3], mkdesc(b, 1024, 512, 2), 1);
                    wgmma_rs224(acc, a1[4], a1[5], a1[6], a1[7], mkdesc(b + 7168, 1024, 512, 2), 1);
                    wg_commit();
                }
                wg_wait<1>();
                release(prev);
                prev = r.slot; r.advance();
                const int nx = it < 6 ? it + 1 : 0;
                ldsm4(a0, xa + nx * 16384 + lx); ldsm4(a0 + 4, xa + nx * 16384 + (lx ^ 32));
            }
            wg_wait<0>();
            reg_fence(acc);
            release(prev);
            if (pass == 0) {
                #pragma unroll
                for (int i = 0; i < 56; i++) hp[i] = pack_relu_bf16(acc[2 * i], acc[2 * i + 1]);
                TS(wg, 5);
            }
        }
        TS(wg, 6);

        uint32_t op[14];
        {
            mbar_wait(sb + BAR_AUX, 0);
            TS(wg, 7);
            const float g0 = *reinterpret_cast<const float*>(smem + OFF_G + (wg * 64 + w4 * 16 + g8) * 4);
            const float g1 = *reinterpret_cast<const float*>(smem + OFF_G + (wg * 64 + w4 * 16 + g8 + 8) * 4);
            const float u0 = 1.f - g0, u1 = 1.f - g1;
            #pragma unroll
            for (int i = 0; i < 28; i++) {
                const float u = (i & 1) ? u1 : u0;
                hp[i] = mul_bf16x2(hp[i], pack_bf16(acc[2 * i] * u, acc[2 * i + 1] * u));
            }
            reg_fence(hp);
            float nd[32];
            wg_fence();
            #pragma unroll
            for (int ks = 0; ks < 3; ks++)
                wgmma_rs64(nd, pq[4 * ks], pq[4 * ks + 1], pq[4 * ks + 2], pq[4 * ks + 3], mkdesc(sb + OFF_STG + ks * 2048, 16, 1024, 1), ks);
            wgmma_rs64(nd, pq[12], pq[13], 0u, 0u, mkdesc(sb + OFF_STG + 3 * 2048, 16, 1024, 1), 1);
            wg_commit();
            #pragma unroll
            for (int i = 28; i < 56; i++) {
                const float u = (i & 1) ? u1 : u0;
                hp[i] = mul_bf16x2(hp[i], pack_bf16(acc[2 * i] * u, acc[2 * i + 1] * u));
            }
            wg_wait<0>();
            reg_fence(nd);
            const int src = lane & ~3;
            const float s00 = __fdividef(g0, __shfl_sync(0xffffffffu, nd[28], src) + 1e-6f);
            const float s01 = __fdividef(g0, __shfl_sync(0xffffffffu, nd[29], src) + 1e-6f);
            const float s10 = __fdividef(g1, __shfl_sync(0xffffffffu, nd[30], src) + 1e-6f);
            const float s11 = __fdividef(g1, __shfl_sync(0xffffffffu, nd[31], src) + 1e-6f);
            #pragma unroll
            for (int t = 0; t < 7; t++) {
                const bool h1 = t > 3 || (t == 3 && q4 >= 2);
                const float sa = h1 ? s01 : s00, sc = h1 ? s11 : s10;
                op[2 * t] = pack_bf16(nd[4 * t] * sa, nd[4 * t + 1] * sa);
                op[2 * t + 1] = pack_bf16(nd[4 * t + 2] * sc, nd[4 * t + 3] * sc);
            }
        }
        TS(wg, 8);

        int c = j == 7 ? 0 : j;
        #pragma unroll 1
        for (int c0 = 0; c0 < 7; c0++) {
            float o[32];
            const bool rel = c0 < 4;
            mbar_wait(sb + BAR_FULL + 8 * r.slot, r.phase);
            uint32_t b = sb + OFF_RING + r.slot * SLOT_BYTES;
            wg_fence();
            #pragma unroll
            for (int ks = 0; ks < 7; ks++)
                wgmma_rs64(o, hp[4 * ks], hp[4 * ks + 1], hp[4 * ks + 2], hp[4 * ks + 3], mkdesc(b + ks * 2048, 16, 1024, 1), ks);
            wg_commit();
            prev = r.slot; r.advance();
            mbar_wait(sb + BAR_FULL + 8 * r.slot, r.phase);
            b = sb + OFF_RING + r.slot * SLOT_BYTES;
            wg_fence();
            #pragma unroll
            for (int ks = 0; ks < 7; ks++)
                wgmma_rs64(o, hp[28 + 4 * ks], hp[29 + 4 * ks], hp[30 + 4 * ks], hp[31 + 4 * ks], mkdesc(b + ks * 2048, 16, 1024, 1), 1);
            wg_commit();
            wg_wait<1>();
            if (c0 < 5) release(prev);
            prev = r.slot; r.advance();
            mbar_wait(sb + BAR_FULL + 8 * r.slot, r.phase);
            b = sb + OFF_RING + r.slot * SLOT_BYTES;
            wg_fence();
            #pragma unroll
            for (int ks = 0; ks < 3; ks++)
                wgmma_rs64(o, op[4 * ks], op[4 * ks + 1], op[4 * ks + 2], op[4 * ks + 3], mkdesc(b + ks * 2048, 16, 1024, 1), 1);
            wgmma_rs64(o, op[12], op[13], 0u, 0u, mkdesc(b + 3 * 2048, 16, 1024, 1), 1);
            wg_commit();
            wg_wait<1>();
            if (c0 < 5) release(prev);
            prev = r.slot; r.advance();
            wg_wait<0>();
            reg_fence(o);
            if (rel) release(prev);
            const uint32_t so = xa + c0 * 16384;
            #pragma unroll
            for (int t = 0; t < 4; t++)
                stsm4(so + (lx ^ (t * 32)), pack_bf16(o[8 * t], o[8 * t + 1]), pack_bf16(o[8 * t + 2], o[8 * t + 3]),
                      pack_bf16(o[8 * t + 4], o[8 * t + 5]), pack_bf16(o[8 * t + 6], o[8 * t + 7]));
            fence_async_smem();
            __syncwarp();
            if (lane == 0) {
                tma_reduce2d(&mOut, sb + OFF_X + c0 * 16384 + wg * 8192 + w4 * 2048, 64 * c, row0 + wg * 64 + w4 * 16);
                asm volatile("cp.async.bulk.commit_group;" ::: "memory");
            }
            if (++c == 7) c = 0;
            TS(wg, 9 + c0);
        }
        if (lane == 0) asm volatile("cp.async.bulk.wait_group.read 0;" ::: "memory");
        TS(wg, 16); TSG(wg, 17);
    }
}

typedef CUresult (*EncodeFn)(CUtensorMap*, CUtensorMapDataType, cuuint32_t, void*, const cuuint64_t*, const cuuint64_t*,
                             const cuuint32_t*, const cuuint32_t*, CUtensorMapInterleave, CUtensorMapSwizzle,
                             CUtensorMapL2promotion, CUtensorMapFloatOOBfill);

void make_map(EncodeFn enc, CUtensorMap* m, const void* base, int rank, const cuuint64_t* dims, const cuuint64_t* strides,
              const cuuint32_t* box, CUtensorMapSwizzle sw) {
    const cuuint32_t es[3] = {1, 1, 1};
    enc(m, CU_TENSOR_MAP_DATA_TYPE_BFLOAT16, rank, const_cast<void*>(base), dims, strides, box, es,
        CU_TENSOR_MAP_INTERLEAVE_NONE, sw, CU_TENSOR_MAP_L2_PROMOTION_L2_128B, CU_TENSOR_MAP_FLOAT_OOB_FILL_NONE);
}

}

extern "C" void kernel_launch(void* const* d_in, const int* in_sizes, int n_in, void* d_out, int out_size) {
    (void)in_sizes; (void)n_in; (void)out_size;
    static EncodeFn enc = nullptr;
    if (!enc) {
        void* fn = nullptr;
        cudaDriverEntryPointQueryResult st;
        cudaGetDriverEntryPoint("cuTensorMapEncodeTiled", &fn, cudaEnableDefault, &st);
        enc = (EncodeFn)fn;
        cudaFuncSetAttribute(fused_kernel, cudaFuncAttributeMaxDynamicSharedMemorySize, SMEM_BYTES);
    }
    CUtensorMap mX, mQKV, mG, mU, mD, mO, mOut;
    {
        const cuuint64_t dims[2] = {kD, kS}, str[1] = {kD * 2};
        const cuuint32_t box[2] = {64, 128}, boxo[2] = {64, 16};
        make_map(enc, &mX, d_in[0], 2, dims, str, box, CU_TENSOR_MAP_SWIZZLE_128B);
        make_map(enc, &mOut, d_out, 2, dims, str, boxo, CU_TENSOR_MAP_SWIZZLE_128B);
    }
    {
        const cuuint64_t dims[3] = {kD, kD, 3}, str[2] = {3 * kD * 2, kD * 2};
        const cuuint32_t box[3] = {64, 16, 3};
        make_map(enc, &mQKV, d_in[1], 3, dims, str, box, CU_TENSOR_MAP_SWIZZLE_128B);
    }
    {
        const cuuint64_t dims[3] = {32, kD, kF / 32}, str[2] = {kF * 2, 64};
        const cuuint32_t box[3] = {32, 16, 7};
        make_map(enc, &mG, d_in[4], 3, dims, str, box, CU_TENSOR_MAP_SWIZZLE_64B);
        make_map(enc, &mU, d_in[5], 3, dims, str, box, CU_TENSOR_MAP_SWIZZLE_64B);
    }
    {
        const cuuint64_t dimd[2] = {kD, kF}, dimo[2] = {kD, kD}, str[1] = {kD * 2};
        const cuuint32_t boxd[2] = {64, 56}, boxo[2] = {64, 32};
        make_map(enc, &mD, d_in[6], 2, dimd, str, boxd, CU_TENSOR_MAP_SWIZZLE_128B);
        make_map(enc, &mO, d_in[2], 2, dimo, str, boxo, CU_TENSOR_MAP_SWIZZLE_128B);
    }
    fused_kernel<<<NCTA, NTHREADS, SMEM_BYTES>>>(mX, mQKV, mG, mU, mD, mO, mOut,
                                                 (const __nv_bfloat16*)d_in[7], (__nv_bfloat16*)d_out);
}
```

```cpp
#include <cuda_runtime.h>
#include <cuda_bf16.h>
#include <cuda.h>
#include <stdint.h>

namespace {

constexpr int kS = 2048, kD = 448, kF = 1792;
constexpr int NTHREADS = 384;
constexpr int NCTA = 128;
constexpr uint32_t OFF_X = 0;
constexpr uint32_t OFF_RING = 114688;
constexpr uint32_t SLOT_BYTES = 16384;
constexpr int NSLOT = 6;
constexpr uint32_t OFF_STG = 212992;
constexpr uint32_t OFF_MISC = 229376;
constexpr uint32_t SMEM_BYTES = 232448;
constexpr uint32_t BAR_FULL = OFF_MISC, BAR_EMPTY = OFF_MISC + 48, BAR_XFULL = OFF_MISC + 96;
constexpr uint32_t BAR_W = OFF_MISC + 152, BAR_KVDONE = OFF_MISC + 160, BAR_AUX = OFF_MISC + 168, BAR_P4 = OFF_MISC + 176;
constexpr uint32_t OFF_W = OFF_MISC + 256;
#define EARLY 0
#define ZERO_PACE 0
#define KV_PACE 0
#define SKEW 4
#define TOK2 1
#define KSCHED 0
#define FASTFLAG 1
#define PF_LATE 0
#define PF_MODE 0

__device__ __align__(128) float g_kvacc[8][2048];
__device__ unsigned int g_counter[64];

#define STS4(n, k)
#define PTS(i)
#define PINC()
#define STS_(k)
#define STDUMP()
#define TS(role, idx)
#define TSG(role, idx)
#define TSDUMP(role, lo, hi)

__device__ __forceinline__ void mbar_init(uint32_t bar, uint32_t cnt) {
    asm volatile("mbarrier.init.shared::cta.b64 [%0], %1;" :: "r"(bar), "r"(cnt) : "memory");
}
__device__ __forceinline__ void mbar_expect_tx(uint32_t bar, uint32_t bytes) {
    asm volatile("mbarrier.arrive.expect_tx.shared::cta.b64 _, [%0], %1;" :: "r"(bar), "r"(bytes) : "memory");
}
__device__ __forceinline__ void mbar_arrive(uint32_t bar) {
    asm volatile("mbarrier.arrive.shared::cta.b64 _, [%0];" :: "r"(bar) : "memory");
}
__device__ __forceinline__ void mbar_arrive_cluster(uint32_t bar) {
    asm volatile("mbarrier.arrive.shared::cluster.b64 _, [%0];" :: "r"(bar) : "memory");
}
__device__ __forceinline__ void mbar_wait(uint32_t bar, uint32_t parity) {
    asm volatile("{\n"
                 ".reg .pred p;\n"
                 ".reg .u32 c;\n"
                 "mov.u32 c, 0;\n"
                 "AGAIN:\n"
                 "mbarrier.try_wait.parity.shared::cta.b64 p, [%0], %1;\n"
                 "@p bra DONE;\n"
                 "add.u32 c, c, 1;\n"
                 "setp.lt.u32 p, c, 4194304;\n"
                 "@p bra AGAIN;\n"
                 "trap;\n"
                 "DONE:\n"
                 "}" :: "r"(bar), "r"(parity) : "memory");
}
__device__ __forceinline__ uint32_t mapa(uint32_t addr, uint32_t cta) {
    uint32_t r; asm("mapa.shared::cluster.u32 %0, %1, %2;" : "=r"(r) : "r"(addr), "r"(cta)); return r;
}
__device__ __forceinline__ bool elect_one() {
    uint32_t p;
    asm volatile("{ .reg .pred P; elect.sync _|P, 0xffffffff; selp.u32 %0, 1, 0, P; }" : "=r"(p));
    return p;
}
__device__ __forceinline__ void tma2d(uint32_t dst, const CUtensorMap* m, int c0, int c1, uint32_t bar) {
    asm volatile("cp.async.bulk.tensor.2d.shared::cluster.global.mbarrier::complete_tx::bytes [%0], [%1, {%3, %4}], [%2];"
                 :: "r"(dst), "l"(m), "r"(bar), "r"(c0), "r"(c1) : "memory");
}
__device__ __forceinline__ void tma3d(uint32_t dst, const CUtensorMap* m, int c0, int c1, int c2, uint32_t bar) {
    asm volatile("cp.async.bulk.tensor.3d.shared::cluster.global.mbarrier::complete_tx::bytes [%0], [%1, {%3, %4, %5}], [%2];"
                 :: "r"(dst), "l"(m), "r"(bar), "r"(c0), "r"(c1), "r"(c2) : "memory");
}
__device__ __forceinline__ void tma2d_mc(uint32_t dst, const CUtensorMap* m, int c0, int c1, uint32_t bar) {
    asm volatile("cp.async.bulk.tensor.2d.shared::cluster.global.mbarrier::complete_tx::bytes.multicast::cluster [%0], [%1, {%3, %4}], [%2], %5;"
                 :: "r"(dst), "l"(m), "r"(bar), "r"(c0), "r"(c1), "h"((uint16_t)3) : "memory");
}
__device__ __forceinline__ void tma3d_mc(uint32_t dst, const CUtensorMap* m, int c0, int c1, int c2, uint32_t bar) {
    asm volatile("cp.async.bulk.tensor.3d.shared::cluster.global.mbarrier::complete_tx::bytes.multicast::cluster [%0], [%1, {%3, %4, %5}], [%2], %6;"
                 :: "r"(dst), "l"(m), "r"(bar), "r"(c0), "r"(c1), "r"(c2), "h"((uint16_t)3) : "memory");
}
__device__ __forceinline__ void tma_reduce2d(const CUtensorMap* m, uint32_t src, int c0, int c1) {
    asm volatile("cp.reduce.async.bulk.tensor.2d.global.shared::cta.add.bulk_group [%0, {%2, %3}], [%1];"
                 :: "l"(m), "r"(src), "r"(c0), "r"(c1) : "memory");
}
__device__ __forceinline__ void bulk_reduce_f32(float* dst, uint32_t src, uint32_t bytes) {
    asm volatile("cp.reduce.async.bulk.global.shared::cta.bulk_group.add.f32 [%0], [%1], %2;" :: "l"(dst), "r"(src), "r"(bytes) : "memory");
}
__device__ __forceinline__ bool mbar_try(uint32_t bar, uint32_t parity) {
    uint32_t ok;
    asm volatile("{ .reg .pred p; mbarrier.test_wait.parity.shared::cta.b64 p, [%1], %2; selp.u32 %0, 1, 0, p; }"
                 : "=r"(ok) : "r"(bar), "r"(parity) : "memory");
    return ok;
}
__device__ __forceinline__ void prefetch_map(const CUtensorMap* m) {
    asm volatile("prefetch.tensormap [%0];" :: "l"(m) : "memory");
}
__device__ __forceinline__ void prefetch_l2(const void* p) { asm volatile("prefetch.global.L2 [%0];" :: "l"(p)); }
__device__ __forceinline__ void prefetch_bulk(const void* p, uint32_t bytes) {
    asm volatile("cp.async.bulk.prefetch.L2.global [%0], %1;" :: "l"(p), "r"(bytes) : "memory");
}
__device__ __forceinline__ void wg_fence() { asm volatile("wgmma.fence.sync.aligned;" ::: "memory"); }
__device__ __forceinline__ void wg_commit() { asm volatile("wgmma.commit_group.sync.aligned;" ::: "memory"); }
template <int N> __device__ __forceinline__ void wg_wait() { asm volatile("wgmma.wait_group.sync.aligned %0;" :: "n"(N) : "memory"); }
template <int N> __device__ __forceinline__ void reg_fence(float (&d)[N]) {
#pragma unroll
    for (int i = 0; i < N; i++) asm volatile("" : "+f"(d[i]) :: "memory");
}
template <int N> __device__ __forceinline__ void reg_fence(uint32_t (&d)[N]) {
#pragma unroll
    for (int i = 0; i < N; i++) asm volatile("" : "+r"(d[i]) :: "memory");
}
template <int LO, int HI, int N> __device__ __forceinline__ void reg_fence_part(uint32_t (&d)[N]) {
#pragma unroll
    for (int i = LO; i < HI; i++) asm volatile("" : "+r"(d[i]) :: "memory");
}
__device__ __forceinline__ void fence_async_smem() { asm volatile("fence.proxy.async.shared::cta;" ::: "memory"); }
template <int ID, int N> __device__ __forceinline__ void bar_sync() { asm volatile("bar.sync %0, %1;" :: "n"(ID), "n"(N) : "memory"); }
template <int ID, int N> __device__ __forceinline__ void bar_arrive() { asm volatile("bar.arrive %0, %1;" :: "n"(ID), "n"(N) : "memory"); }
__device__ __forceinline__ void ldsm4(uint32_t* r, uint32_t addr) {
    asm volatile("ldmatrix.sync.aligned.m8n8.x4.shared.b16 {%0, %1, %2, %3}, [%4];"
                 : "=r"(r[0]), "=r"(r[1]), "=r"(r[2]), "=r"(r[3]) : "r"(addr) : "memory");
}
__device__ __forceinline__ void stsm4(uint32_t addr, uint32_t r0, uint32_t r1, uint32_t r2, uint32_t r3) {
    asm volatile("stmatrix.sync.aligned.m8n8.x4.shared.b16 [%0], {%1, %2, %3, %4};"
                 :: "r"(addr), "r"(r0), "r"(r1), "r"(r2), "r"(r3) : "memory");
}
__device__ __forceinline__ uint32_t lds32(uint32_t addr) {
    uint32_t r; asm volatile("ld.shared.u32 %0, [%1];" : "=r"(r) : "r"(addr)); return r;
}
__device__ __forceinline__ float4 lds128f(uint32_t addr) {
    float4 r; asm volatile("ld.shared.v4.f32 {%0, %1, %2, %3}, [%4];" : "=f"(r.x), "=f"(r.y), "=f"(r.z), "=f"(r.w) : "r"(addr)); return r;
}
__device__ __forceinline__ uint32_t clock32() { uint32_t t; asm volatile("mov.u32 %0, %%clock;" : "=r"(t)); return t; }
__device__ __forceinline__ uint32_t pack_bf16(float lo, float hi) {
    uint32_t r; asm("cvt.rn.bf16x2.f32 %0, %1, %2;" : "=r"(r) : "f"(hi), "f"(lo)); return r;
}
__device__ __forceinline__ uint32_t pack_relu_bf16(float lo, float hi) {
    uint32_t r; asm("cvt.rn.relu.bf16x2.f32 %0, %1, %2;" : "=r"(r) : "f"(hi), "f"(lo)); return r;
}
__device__ __forceinline__ uint32_t mul_bf16x2(uint32_t a, uint32_t b) {
    uint32_t r; asm("mul.rn.bf16x2 %0, %1, %2;" : "=r"(r) : "r"(a), "r"(b)); return r;
}
__device__ __forceinline__ float phi(float t, float log2e) {
    float r;
    asm("{ .reg .pred p; .reg .f32 e;\n"
        "mul.f32 e, %1, %2;\n"
        "ex2.approx.ftz.f32 e, e;\n"
        "setp.gt.f32 p, %1, 0f00000000;\n"
        "add.f32 %0, e, 0f358637BD;\n"
        "@p add.f32 %0, %1, 0f3F800008; }" : "=&f"(r) : "f"(t), "f"(log2e));
    return r;
}
__device__ __forceinline__ float after_issue(float v, uint32_t zero) {
    return __uint_as_float(__float_as_uint(v) | (clock32() & zero));
}
constexpr float kLog2e = 1.4426950408889634f;
__device__ __forceinline__ float bf_lo(uint32_t v) { return __uint_as_float(v << 16); }
__device__ __forceinline__ float bf_hi(uint32_t v) { return __uint_as_float(v & 0xffff0000u); }
constexpr uint32_t HI128 = (1024 >> 4) | (1u << 30);
constexpr uint32_t HI64 = (512 >> 4) | (2u << 30);
constexpr uint32_t LO128 = 1u << 16, LO64 = (1024u >> 4) << 16;
__device__ __forceinline__ void grid_arrive(unsigned int* c) {
    asm volatile("fence.acq_rel.gpu;" ::: "memory");
    asm volatile("red.relaxed.gpu.global.add.u32 [%0], 1;" :: "l"(c) : "memory");
}
__device__ __forceinline__ void grid_wait(const unsigned int* c, unsigned int target) {
    unsigned int v; int it = 0;
    do {
        asm volatile("ld.relaxed.gpu.global.u32 %0, [%1];" : "=r"(v) : "l"(c) : "memory");
        if (++it > (1 << 22)) asm volatile("trap;");
    } while ((int)(v - target) < 0);
    if (!FASTFLAG) asm volatile("ld.acquire.gpu.global.u32 %0, [%1];" : "=r"(v) : "l"(c) : "memory");
}

__host__ __device__ constexpr uint32_t p4_pack(int n) { return (n / 3) * 36864 + (n % 3) * 14336; }
__host__ __device__ constexpr uint32_t p4_off(int n) {
    return n < 6 ? OFF_X + p4_pack(n) : n < 14 ? OFF_RING + p4_pack(n - 6) : n == 14 ? OFF_X + p4_pack(6) : OFF_X + p4_pack(n - 15);
}
__host__ __device__ constexpr uint32_t p4_bar(int n) {
    return n < 6 ? BAR_XFULL + 8 * n : n < 12 ? BAR_FULL + 8 * (n - 6) : n < 14 ? BAR_P4 + 8 * (n - 12)
                 : n == 14 ? BAR_XFULL + 48 : BAR_XFULL + 8 * (n - 15);
}
__host__ __device__ constexpr uint32_t p4_par(int n) { return (n < 12 || n == 14) ? 1 : 0; }
constexpr uint32_t OFF_OUT = OFF_X + 5 * 16384;
static_assert(p4_off(13) + 14336 <= OFF_STG + 8192 && p4_off(14) + 8192 == OFF_OUT, "pass-4 layout");

struct Ring {
    uint32_t slot, phase;
    __device__ __forceinline__ void advance() { if (++slot == NSLOT) { slot = 0; phase ^= 1; } }
};

struct Maps { CUtensorMap x, kv, q, g4, g3, u4, u3, d, o, out; };

__global__ void __cluster_dims__(2, 1, 1) __launch_bounds__(NTHREADS, 1)
fused_kernel(const __grid_constant__ Maps mp, const __nv_bfloat16* __restrict__ gate_w, __nv_bfloat16* __restrict__ out,
             const char* __restrict__ pX, const char* __restrict__ pQKV, const char* __restrict__ pG,
             const char* __restrict__ pU, const char* __restrict__ pD, const char* __restrict__ pO, uint32_t zero)
{
    extern __shared__ __align__(1024) unsigned char smem[];
    const uint32_t sb = (uint32_t)__cvta_generic_to_shared(smem);
    const int tid = threadIdx.x, warp = tid >> 5, lane = tid & 31;
    const int rank = blockIdx.x & 1, j = (blockIdx.x >> 1) & 7;
    const int row0 = ((blockIdx.x >> 4) * 2 + rank) * 128;

    TSG(2, 0); TS(2, 1);
    if (warp == 8) {
        if (elect_one()) {
            prefetch_map(&mp.x); prefetch_map(&mp.kv); prefetch_map(&mp.g4);
            #pragma unroll
            for (int s = 0; s < NSLOT; s++) {
                mbar_init(sb + BAR_FULL + 8 * s, 1);
                mbar_init(sb + BAR_EMPTY + 8 * s, 4);
            }
            #pragma unroll
            for (int s = 0; s < 7; s++) mbar_init(sb + BAR_XFULL + 8 * s, 1);
            mbar_init(sb + BAR_W, 1);
            mbar_init(sb + BAR_KVDONE, 8);
            mbar_init(sb + BAR_AUX, 3);
            mbar_init(sb + BAR_P4, 1);
            mbar_init(sb + BAR_P4 + 8, 1);
            asm volatile("fence.mbarrier_init.release.cluster;" ::: "memory");
        }
        __syncwarp();
    }
    asm volatile("barrier.cluster.arrive.relaxed.aligned;" ::: "memory");
    if (warp == 8) {
        if (elect_one()) {
            mbar_expect_tx(sb + BAR_XFULL, 16384);
            tma2d(sb + OFF_X, &mp.x, 0, row0, sb + BAR_XFULL);
            #pragma unroll
            for (int s = 0; s < EARLY; s++) {
                mbar_expect_tx(sb + BAR_FULL + 8 * s, 16384);
                #pragma unroll
                for (int h = 0; h < 2; h++) {
                    tma3d(sb + OFF_RING + s * SLOT_BYTES + h * 8192, &mp.kv, 56 * j, 32 * s + 16 * h, 1, sb + BAR_FULL + 8 * s);
                    tma3d(sb + OFF_RING + s * SLOT_BYTES + h * 8192 + 4096, &mp.g4, 0, 32 * s + 16 * h, 7 * j, sb + BAR_FULL + 8 * s);
                }
            }
            mbar_expect_tx(sb + BAR_W, 896);
            asm volatile("cp.async.bulk.shared::cluster.global.mbarrier::complete_tx::bytes [%0], [%1], 896, [%2];"
                         :: "r"(sb + OFF_W), "l"(gate_w), "r"(sb + BAR_W) : "memory");
            if (sb & 1023) asm volatile("trap;");
        }
        __syncwarp();
    }
    asm volatile("barrier.cluster.wait.aligned;" ::: "memory");

    if (warp >= 8) {
        asm volatile("setmaxnreg.dec.sync.aligned.u32 40;");
        if (warp == 8) {
            if (elect_one()) {
                Ring r{EARLY, 1};
                auto acquire = [&](uint32_t bytes) -> uint32_t {
                    mbar_wait(sb + BAR_EMPTY + 8 * r.slot, r.phase);
                    PTS(pidx); PINC();
                    mbar_expect_tx(sb + BAR_FULL + 8 * r.slot, bytes);
                    return sb + OFF_RING + r.slot * SLOT_BYTES;
                };
                if (EARLY > 0) {
                    mbar_expect_tx(sb + BAR_XFULL + 8, 16384);
                    tma2d(sb + OFF_X + 16384, &mp.x, 64, row0, sb + BAR_XFULL + 8);
                }
                #pragma unroll 1
                for (int s = EARLY; s < 14; s++) {
                    const uint32_t dst = acquire(16384) + rank * 8192;
                    tma3d_mc(dst, &mp.kv, 56 * j, 32 * s + 16 * rank, 1, sb + BAR_FULL + 8 * r.slot);
                    tma3d_mc(dst + 4096, &mp.g4, 0, 32 * s + 16 * rank, 7 * j, sb + BAR_FULL + 8 * r.slot);
                    r.advance();
                    if (!(s & 1) && s < 12) {
                        const int n = (s >> 1) + 1;
                        mbar_expect_tx(sb + BAR_XFULL + 8 * n, 16384);
                        tma2d(sb + OFF_X + n * 16384, &mp.x, 64 * n, row0, sb + BAR_XFULL + 8 * n);
                    }
                    if (s == 5) { prefetch_map(&mp.q); prefetch_map(&mp.u4); prefetch_map(&mp.g3); prefetch_map(&mp.u3); prefetch_map(&mp.d); prefetch_map(&mp.o); prefetch_map(&mp.out); }
                }
                #pragma unroll 1
                for (int s = 0; s < 14; s++) {
                    const uint32_t dst = acquire(12288) + rank * 6144;
                    tma3d_mc(dst, &mp.q, 56 * j, 32 * s + 16 * rank, 0, sb + BAR_FULL + 8 * r.slot);
                    tma3d_mc(dst + 2048, &mp.u4, 0, 32 * s + 16 * rank, 7 * j, sb + BAR_FULL + 8 * r.slot);
                    r.advance();
                }
                const int cfirst = j == 7 ? 0 : j;
                auto load4 = [&](int n) {
                    PTS(42 + n);
                    int c = cfirst + n / 3;
                    if (c >= 7) c -= 7;
                    mbar_expect_tx(sb + p4_bar(n), n % 3 == 2 ? 8192 : 14336);
                    if (n % 3 == 2) tma2d_mc(sb + p4_off(n) + rank * 4096, &mp.o, 64 * c, 56 * j + 32 * rank, sb + p4_bar(n));
                    else tma2d_mc(sb + p4_off(n) + rank * 7168, &mp.d, 64 * c, 224 * j + 112 * (n % 3) + 56 * rank, sb + p4_bar(n));
                };
                #pragma unroll 1
                for (int s = 0; s < 14; s++) {
                    const uint32_t dst = acquire(12288) + rank * 6144;
                    tma3d_mc(dst, &mp.g3, 0, 32 * s + 16 * rank, 7 * j + 4, sb + BAR_FULL + 8 * r.slot);
                    tma3d_mc(dst + 3072, &mp.u3, 0, 32 * s + 16 * rank, 7 * j + 4, sb + BAR_FULL + 8 * r.slot);
                    r.advance();
                    if (s == 7) load4(0);
                    if (s == 9) load4(1);
                    if (s == 11) load4(2);
                    if (s == 13) { load4(3); load4(4); }
                }
                mbar_wait(sb + BAR_EMPTY, 0);      load4(6);
                mbar_wait(sb + BAR_EMPTY + 8, 0);  load4(5); load4(7); load4(14);
                mbar_wait(sb + BAR_EMPTY + 16, 0); load4(8);
                mbar_wait(sb + BAR_EMPTY + 24, 0); load4(9); load4(10);
                mbar_wait(sb + BAR_EMPTY + 32, 0); load4(11);
                mbar_wait(sb + BAR_EMPTY + 40, 0); load4(12);
                mbar_wait(sb + BAR_AUX, 0);        load4(13);
                #pragma unroll
                for (int n = 15; n < 21; n++) { mbar_wait(sb + BAR_EMPTY + 8 * (n - 15), 1); load4(n); }
            }
        } else {
            const int ht = tid - 288;
            unsigned int cnt0;
            asm volatile("ld.relaxed.gpu.global.u32 %0, [%1];" : "=r"(cnt0) : "l"(&g_counter[32]) : "memory");
            const unsigned int target = ((cnt0 >> 7) + 1) << 7;
            if (warp == 9) {
                reinterpret_cast<float4*>(&g_kvacc[0][0])[blockIdx.x * 32 + lane] = make_float4(0.f, 0.f, 0.f, 0.f);
                asm volatile("fence.proxy.async.global;" ::: "memory");
                __syncwarp();
                if (lane == 0) grid_arrive(&g_counter[0]);
                TS(2, 2);
                mbar_wait(sb + BAR_XFULL + 8 * 6, 0);
                uint4* o = reinterpret_cast<uint4*>(out) + blockIdx.x * 896 + lane;
                #pragma unroll 1
                for (int q = 0; q < 14; q++) {
                    o[q * 64] = make_uint4(0, 0, 0, 0);
                    o[q * 64 + 32] = make_uint4(0, 0, 0, 0);
                    if (ZERO_PACE) __nanosleep(ZERO_PACE);
                }
                asm volatile("fence.proxy.async.global;" ::: "memory");
                __syncwarp();
                if (lane == 0) {
                    if (FASTFLAG) asm volatile("fence.acq_rel.gpu;" ::: "memory");
                    grid_wait(&g_counter[0], target);
                }
                __syncwarp();
                TS(2, 7);
            }
            mbar_wait(sb + BAR_KVDONE, 0);
            TS(2, 3);
            {
                #pragma unroll
                for (int i0 = 0; i0 < 5; i0 += 3) {
                    float4 pa[3], pb[3];
                    #pragma unroll
                    for (int i = 0; i < 3 && i0 + i < 5; i++) {
                        const int q = min(ht + 96 * (i0 + i), 447);
                        pa[i] = lds128f(sb + OFF_STG + q * 16); pb[i] = lds128f(sb + OFF_STG + 8192 + q * 16);
                    }
                    #pragma unroll
                    for (int i = 0; i < 3 && i0 + i < 5; i++) {
                        const int q = ht + 96 * (i0 + i);
                        if (q < 448) asm volatile("st.shared.v4.f32 [%0], {%1, %2, %3, %4};" :: "r"(sb + OFF_STG + q * 16),
                            "f"(pa[i].x + pb[i].x), "f"(pa[i].y + pb[i].y), "f"(pa[i].z + pb[i].z), "f"(pa[i].w + pb[i].w) : "memory");
                    }
                }
                fence_async_smem();
            }
            bar_sync<3, 96>();
            if (warp == 9) {
                if (elect_one()) {
                    if (KV_PACE) {
                        #pragma unroll 1
                        for (int q = 0; q < 7; q++) {
                            bulk_reduce_f32(&g_kvacc[j][q * 256], sb + OFF_STG + q * 1024, 1024);
                            __nanosleep(KV_PACE);
                        }
                    } else {
                        bulk_reduce_f32(&g_kvacc[j][0], sb + OFF_STG, 7168);
                    }
                    asm volatile("cp.async.bulk.commit_group;" ::: "memory");
                    asm volatile("cp.async.bulk.wait_group 0;" ::: "memory");
                    if (FASTFLAG) asm volatile("red.relaxed.gpu.global.add.u32 [%0], 1;" :: "l"(&g_counter[32]) : "memory");
                    else grid_arrive(&g_counter[32]);
                    TS(2, 4);
                }
            }
            __syncwarp();
            #pragma unroll
            for (int i = 0; i < 3; i++) {
                const int q = ht + 96 * i;
                const int d = q < 168 ? q / 3 : 56 + ((q - 168) >> 3);
                const int c = q < 168 ? (q - 3 * d + (d < 28 ? 4 : 0)) : (q & 7);
                if (q < 232) asm volatile("st.shared.v4.u32 [%0], {%1, %1, %1, %1};" :: "r"(sb + OFF_STG + 8192 + d * 128 + ((c ^ (d & 7)) << 4)), "r"(0) : "memory");
            }
            if (lane == 0) grid_wait(&g_counter[32], target);
            __syncwarp();
            TS(2, 5);
            const float4* src = reinterpret_cast<const float4*>(&g_kvacc[j][0]);
            float4 va[3], vb[3];
            #pragma unroll
            for (int i = 0; i < 3; i++) {
                const int q = ht + 96 * i, d = q / 5, m = q - 5 * d;
                const int pc = m < 4 ? m : (d < 28 ? 3 : 0);
                if (q < 280) { va[i] = __ldcg(src + d * 8 + 2 * (pc ^ (d & 3))); vb[i] = __ldcg(src + d * 8 + 2 * (pc ^ (d & 3)) + 1); }
            }
            #pragma unroll
            for (int i = 0; i < 3; i++) {
                const int q = ht + 96 * i, d = q / 5, m = q - 5 * d;
                const bool h0 = d < 28;
                const int c = m == 4 ? 7 : (h0 ? m : m + 3);
                uint32_t w0 = pack_bf16(va[i].x, va[i].y), w1 = pack_bf16(va[i].z, va[i].w);
                uint32_t w2 = pack_bf16(vb[i].x, vb[i].y), w3 = pack_bf16(vb[i].z, vb[i].w);
                if (m == 4) { w0 = h0 ? (w2 & 0xffffu) : (w0 << 16); w1 = w2 = w3 = 0u; }
                else if (c == 3) { if (h0) w2 = w3 = 0u; else w0 = w1 = 0u; }
                if (q < 280)
                    asm volatile("st.shared.v4.u32 [%0], {%1, %2, %3, %4};"
                                 :: "r"(sb + OFF_STG + 8192 + d * 128 + ((c ^ (d & 7)) << 4)), "r"(w0), "r"(w1), "r"(w2), "r"(w3) : "memory");
            }
            fence_async_smem();
            __syncwarp();
            if (lane == 0) mbar_arrive(sb + BAR_AUX);
            TS(2, 6); TSDUMP(2, 1, 7);
        }
    } else {
        asm volatile("setmaxnreg.inc.sync.aligned.u32 232;");
        const int wg = warp >> 2, w4 = warp & 3;
        const int q4 = lane & 3, g8 = lane >> 2;
        const uint32_t lx = ((lane >> 4) ^ (lane & 7)) << 4;
        const uint32_t xa = sb + OFF_X + (warp * 16 + (lane & 15)) * 128;
        const uint32_t empty_dst = mapa(sb + BAR_EMPTY, w4 & 1);
        const bool signaller = lane == 0 && w4 < 2;
        const uint32_t dsb = (sb & 0x3FFFF) >> 4;
        Ring r{0, 0};
        uint32_t cur = 0, old = 0;
        bool ready = false;
        auto release = [&](uint32_t slot) { if (signaller) mbar_arrive_cluster(empty_dst + 8 * slot); };
        auto turn_wait = [&]() { if (wg == 0) bar_sync<6, 256>(); else bar_sync<7, 256>(); };
        auto turn_pass = [&]() { if (wg == 0) bar_arrive<7, 256>(); else bar_arrive<6, 256>(); };
        auto begin = [&]() -> uint32_t {
            STS_(0);
            if (!ready) mbar_wait(sb + BAR_FULL + 8 * r.slot, r.phase);
            STS_(1);
            wg_fence();
            return dsb + (OFF_RING >> 4) + r.slot * (SLOT_BYTES >> 4);
        };
        auto commit = [&]() { wg_commit(); old = cur; cur = r.slot; r.advance(); };
        auto retire = [&]() { wg_wait<1>(); release(old); };
        auto peek = [&]() { ready = mbar_try(sb + BAR_FULL + 8 * r.slot, r.phase); };
        auto skew_hold = [&](int pass) { if (((SKEW >> pass) & 1) && wg == 1) bar_sync<4, 256>(); };
        auto skew_go = [&](int pass) { if (((SKEW >> pass) & 1) && wg == 0) bar_arrive<4, 256>(); };
        uint32_t a0[8], a1[8];
        auto load_a0 = [&](int kc) { ldsm4(a0, xa + kc * 16384 + lx); ldsm4(a0 + 4, xa + kc * 16384 + (lx ^ 32)); };
        auto load_a1 = [&](int kc) { ldsm4(a1, xa + kc * 16384 + (lx ^ 64)); ldsm4(a1 + 4, xa + kc * 16384 + (lx ^ 96)); };
        TS(wg, 0);

        uint32_t hp[56], pv[14];
        float g0, g1, ak[28];
        {
            float av[28], ag[64];
            float d0 = 0.f, d1 = 0.f, d2 = 0.f, d3 = 0.f;
            uint32_t w0[4], w1[4];
            auto issue1 = [&](uint32_t (&a)[8], int sd) {
                const uint32_t b = begin();
                wgmma_rs56<HI128>(ak, a[0], a[1], a[2], a[3], b + LO128, sd);
                wgmma_rs56<HI128>(av, a[0], a[1], a[2], a[3], b + LO128 + 128, sd);
                wgmma_rs128<HI64>(ag, a[0], a[1], a[2], a[3], b + LO64 + 256, sd);
                wgmma_rs56<HI128>(ak, a[4], a[5], a[6], a[7], b + LO128 + 512, 1);
                wgmma_rs56<HI128>(av, a[4], a[5], a[6], a[7], b + LO128 + 640, 1);
                wgmma_rs128<HI64>(ag, a[4], a[5], a[6], a[7], b + LO64 + 768, 1);
                commit();
            };
            auto load_w = [&](uint32_t (&w)[4], int s) {
                #pragma unroll
                for (int e = 0; e < 4; e++) w[e] = lds32(sb + OFF_W + s * 64 + q4 * 4 + e * 16);
            };
            auto dot = [&](uint32_t (&a)[8], uint32_t (&w)[4]) {
                #pragma unroll
                for (int e = 0; e < 4; e++) {
                    d0 = fmaf(bf_lo(a[2 * e]), bf_lo(w[e]), d0);     d2 = fmaf(bf_hi(a[2 * e]), bf_hi(w[e]), d2);
                    d1 = fmaf(bf_lo(a[2 * e + 1]), bf_lo(w[e]), d1); d3 = fmaf(bf_hi(a[2 * e + 1]), bf_hi(w[e]), d3);
                }
                asm volatile("" : "+f"(d0), "+f"(d1), "+f"(d2), "+f"(d3));
            };
            mbar_wait(sb + BAR_XFULL, 0);
            TS(wg, 1);
            load_a0(0);
            mbar_wait(sb + BAR_W, 0);
            load_w(w0, 0);
            #pragma unroll 1
            for (int it = 0; it < 7; it++) {
                if (it == 6) skew_hold(0);
                issue1(a0, it);
                if (it == 0) TS(wg, 2);
                wg_wait<1>();
                if (it > 0) release(old);
                load_a1(it);
                load_w(w1, 2 * it + 1);
                peek();
                const int nx = it < 6 ? it + 1 : 0;
                const bool xok = mbar_try(sb + BAR_XFULL + 8 * nx, 0);
                dot(a0, w0);
                issue1(a1, 1);
                if (it == 6) skew_go(0);
                retire();
                if (!xok) mbar_wait(sb + BAR_XFULL + 8 * nx, 0);
                load_a0(nx);
                load_w(w0, 2 * nx);
                peek();
                dot(a1, w1);
            }
            d0 += d2; d1 += d3;
            d0 += __shfl_xor_sync(0xffffffffu, d0, 1); d1 += __shfl_xor_sync(0xffffffffu, d1, 1);
            d0 += __shfl_xor_sync(0xffffffffu, d0, 2); d1 += __shfl_xor_sync(0xffffffffu, d1, 2);
            wg_wait<0>();
            reg_fence(ak); reg_fence(av); reg_fence(ag);
            release(cur);
            if (wg == 0) bar_arrive<8, 256>();
            #pragma unroll
            for (int i = 0; i < 32; i++) hp[i] = pack_relu_bf16(ag[2 * i], ag[2 * i + 1]);
            #pragma unroll
            for (int i = 0; i < 14; i++) pv[i] = pack_bf16(av[2 * i], av[2 * i + 1]);
            reg_fence_part<0, 32>(hp); reg_fence(pv);
            g0 = d0; g1 = d1;
        }
        TS(wg, 3);

        float aq[28], au[64];
        {
            auto issue2 = [&](uint32_t (&a)[8], int sd) {
                const uint32_t b = begin();
                wgmma_rs56<HI128>(aq, a[0], a[1], a[2], a[3], b + LO128, sd);
                wgmma_rs128<HI64>(au, a[0], a[1], a[2], a[3], b + LO64 + 128, sd);
                wgmma_rs56<HI128>(aq, a[4], a[5], a[6], a[7], b + LO128 + 384, 1);
                wgmma_rs128<HI64>(au, a[4], a[5], a[6], a[7], b + LO64 + 512, 1);
            };
            const uint32_t st_base = wg == 0 ? OFF_STG : OFF_RING + 12288, st_step = wg == 0 ? 2048 : SLOT_BYTES, st_v = wg == 0 ? 8192 : 2048;
            const uint32_t sk = sb + st_base + w4 * st_step + (lane & 15) * 128;
            auto stage_k = [&](int t) {
                const float l2e = TOK2 ? after_issue(kLog2e, zero) : kLog2e;
                uint32_t p[4];
                #pragma unroll
                for (int e = 0; e < 4; e++)
                    p[e] = 4 * t + e < 14 ? pack_bf16(phi(ak[8 * t + 2 * e], l2e), phi(ak[8 * t + 2 * e + 1], l2e)) : 0u;
                stsm4(sk + (lx ^ (t * 32)), p[0], p[1], p[2], p[3]);
            };
            issue2(a0, 0); commit();
            load_a1(0); peek();
            if (wg == 1) bar_sync<8, 256>();
            {
                const uint32_t ones = q4 == 0 ? 0x3f803f80u : 0u;
                #pragma unroll
                for (int t = 0; t < 3; t++) stsm4(sk + st_v + (lx ^ (t * 32)), pv[4 * t], pv[4 * t + 1], pv[4 * t + 2], pv[4 * t + 3]);
                stsm4(sk + st_v + (lx ^ 96), pv[12], pv[13], ones, ones);
            }
            if (KSCHED == 0) {
                issue2(a1, 1); commit();
                retire(); load_a0(1); peek();
                stage_k(0);
                issue2(a0, 1); commit();
                retire(); load_a1(1); peek();
                stage_k(1);
                issue2(a1, 1); commit();
                retire(); load_a0(2); peek();
                stage_k(2);
                issue2(a0, 1); commit();
                retire(); load_a1(2); peek();
                stage_k(3);
                issue2(a1, 1); commit();
                retire(); load_a0(3); peek();
                fence_async_smem();
            } else {
                issue2(a1, 1); commit();
                stage_k(0);
                retire(); load_a0(1); peek();
                issue2(a0, 1); commit();
                stage_k(1);
                retire(); load_a1(1); peek();
                issue2(a1, 1); commit();
                stage_k(2);
                retire(); load_a0(2); peek();
                issue2(a0, 1); commit();
                stage_k(3);
                retire(); load_a1(2); peek();
                issue2(a1, 1); commit();
                fence_async_smem();
                retire(); load_a0(3); peek();
            }
            if (wg == 0) bar_sync<1, 128>(); else bar_sync<2, 128>();
            float kv[32];
            issue2(a0, 1);
            {
                const uint32_t dk = dsb + LO128 + (st_base >> 4), ds = st_step >> 4, dv = st_v >> 4;
                #pragma unroll
                for (int ks = 0; ks < 4; ks++) wgmma_ss64_tt<HI128>(kv, dk + ks * ds, dk + ks * ds + dv, ks);
            }
            commit();
            retire(); load_a1(3); peek();
            {
                const float l2e = TOK2 ? after_issue(-kLog2e, zero) : -kLog2e;
                float e0, e1;
                asm("ex2.approx.ftz.f32 %0, %1;" : "=f"(e0) : "f"(g0 * l2e));
                asm("ex2.approx.ftz.f32 %0, %1;" : "=f"(e1) : "f"(g1 * l2e));
                g0 = __fdividef(1.f, 1.f + e0);
                g1 = __fdividef(1.f, 1.f + e1);
                asm volatile("" : "+f"(g0), "+f"(g1));
            }
            issue2(a1, 1); commit();
            retire(); load_a0(4); peek();
            reg_fence(kv);
            if (wg == 0) bar_arrive<5, 256>(); else bar_sync<5, 256>();
            auto stage_kv = [&](int hh) {
                const int d = w4 * 16 + g8 + 8 * hh;
                const bool h0 = d < 28;
                const uint32_t rowa = sb + OFF_STG + wg * 8192 + d * 128 + q4 * 8;
                #pragma unroll
                for (int t = 0; t < 4; t++) {
                    float v0 = h0 ? kv[4 * t + 2 * hh] : kv[4 * t + 12 + 2 * hh];
                    float v1 = h0 ? kv[4 * t + 2 * hh + 1] : kv[4 * t + 13 + 2 * hh];
                    if (t == 0 && !h0 && q4 == 0) v0 = kv[28 + 2 * hh];
                    if (d < 56 && !(t == 3 && h0 && q4 == 2))
                        asm volatile("st.shared.v2.f32 [%0], {%1, %2};" :: "r"(rowa + ((t ^ (g8 & 3)) << 5)), "f"(v0), "f"(v1) : "memory");
                }
                if (h0 && q4 == 0)
                    asm volatile("st.shared.v2.f32 [%0], {%1, %1};" :: "r"(rowa + ((3 ^ (g8 & 3)) << 5) + 16), "f"(kv[28 + 2 * hh]) : "memory");
            };
            stage_kv(0);
            issue2(a0, 1); commit();
            retire(); load_a1(4); peek();
            stage_kv(1);
            __syncwarp();
            if (lane == 0) mbar_arrive(sb + BAR_KVDONE);
            TS(wg, 4);
            issue2(a1, 1); commit();
            retire(); load_a0(5); peek();
            #pragma unroll 1
            for (int it = 5; it < 7; it++) {
                if (it == 6) skew_hold(1);
                issue2(a0, 1); commit();
                retire(); load_a1(it); peek();
                issue2(a1, 1); commit();
                if (it == 6) skew_go(1);
                retire(); load_a0(it < 6 ? it + 1 : 0); peek();
            }
            wg_wait<0>();
            reg_fence(aq); reg_fence(au);
            release(cur);
        }
        const float u0 = 1.f - g0, u1 = 1.f - g1;
        #pragma unroll
        for (int i = 0; i < 32; i++) {
            const float u = (i & 1) ? u1 : u0;
            hp[i] = mul_bf16x2(hp[i], pack_bf16(au[2 * i] * u, au[2 * i + 1] * u));
        }
        reg_fence_part<0, 32>(hp);
        TS(wg, 5);

        float ag[96], nd[32];
        uint32_t op[16];
        {
            auto issue3 = [&](uint32_t (&a)[8], int sd) {
                const uint32_t b = begin();
                wgmma_rs192<HI64>(ag, a[0], a[1], a[2], a[3], b + LO64, sd);
                wgmma_rs192<HI64>(ag, a[4], a[5], a[6], a[7], b + LO64 + 384, 1);
            };
            uint32_t pq[16];
            issue3(a0, 0); commit();
            load_a1(0); peek();
            issue3(a1, 1); commit();
            {
                const float l2e = after_issue(kLog2e, zero);
                #pragma unroll
                for (int i = 0; i < 14; i++) pq[i] = pack_bf16(phi(aq[2 * i], l2e), phi(aq[2 * i + 1], l2e));
                pq[14] = 0u; pq[15] = 0u;
                reg_fence(pq);
            }
            retire(); load_a0(1); peek();
            #pragma unroll 1
            for (int it = 1; it < 6; it++) {
                issue3(a0, 1); commit();
                retire(); load_a1(it); peek();
                issue3(a1, 1); commit();
                retire(); load_a0(it + 1); peek();
            }
            skew_hold(2);
            issue3(a0, 1); commit();
            const bool aux = mbar_try(sb + BAR_AUX, 0);
            retire(); load_a1(6); peek();
            if (!aux) mbar_wait(sb + BAR_AUX, 0);
            TS(wg, 7);
            issue3(a1, 1);
            {
                const uint32_t dk = dsb + LO128 + ((OFF_STG + 8192) >> 4);
                #pragma unroll
                for (int ks = 0; ks < 4; ks++) wgmma_rs64<HI128>(nd, pq[4 * ks], pq[4 * ks + 1], pq[4 * ks + 2], pq[4 * ks + 3], dk + ks * 128, ks);
            }
            commit();
            skew_go(2);
            ready = mbar_try(sb + p4_bar(0), p4_par(0));
            retire();
        }
        TS(wg, 6);

        float oa[32], ob[32];
        int c = j == 7 ? 0 : j;
        auto issue4 = [&](float (&o)[32], int n) {
            STS4(n, 0);
            if (!ready) mbar_wait(sb + p4_bar(n), p4_par(n));
            STS4(n, 1);
            if (n < 20) ready = mbar_try(sb + p4_bar(n + 1), p4_par(n + 1));
            wg_fence();
            const uint32_t b = dsb + LO128 + (p4_off(n) >> 4);
            if (n % 3 == 2) {
                #pragma unroll
                for (int ks = 0; ks < 4; ks++) wgmma_rs64<HI128>(o, op[4 * ks], op[4 * ks + 1], op[4 * ks + 2], op[4 * ks + 3], b + ks * 128, 1);
            } else {
                const int h = (n % 3) * 28;
                #pragma unroll
                for (int ks = 0; ks < 7; ks++)
                    wgmma_rs64<HI128>(o, hp[h + 4 * ks], hp[h + 4 * ks + 1], hp[h + 4 * ks + 2], hp[h + 4 * ks + 3], b + ks * 128, n % 3 + ks);
            }
            wg_commit();
        };
        auto ship = [&](float (&o)[32], int c0) {
            reg_fence(o);
            const uint32_t so = xa + OFF_OUT + (c0 & 1) * 16384;
            #pragma unroll
            for (int t = 0; t < 4; t++)
                stsm4(so + (lx ^ (t * 32)), pack_bf16(o[8 * t], o[8 * t + 1]), pack_bf16(o[8 * t + 2], o[8 * t + 3]),
                      pack_bf16(o[8 * t + 4], o[8 * t + 5]), pack_bf16(o[8 * t + 6], o[8 * t + 7]));
            fence_async_smem();
            __syncwarp();
            if (elect_one()) {
                tma_reduce2d(&mp.out, sb + OFF_OUT + (c0 & 1) * 16384 + warp * 2048, 64 * c, row0 + warp * 16);
                asm volatile("cp.async.bulk.commit_group;" ::: "memory");
            }
            if (++c == 7) c = 0;
            TS(wg, 9 + c0);
        };
        auto finish_h = [&]() {
            reg_fence(ag);
            release(cur);
            #pragma unroll
            for (int i = 0; i < 24; i++) {
                const float u = (i & 1) ? u1 : u0;
                hp[32 + i] = mul_bf16x2(pack_relu_bf16(ag[2 * i], ag[2 * i + 1]), pack_bf16(ag[48 + 2 * i] * u, ag[49 + 2 * i] * u));
            }
            reg_fence_part<32, 56>(hp);
        };
        wg_wait<0>();
        reg_fence(nd);
        const int src = lane & ~3;
        const float n0 = __shfl_sync(0xffffffffu, nd[28], src), n1 = __shfl_sync(0xffffffffu, nd[29], src);
        const float n2 = __shfl_sync(0xffffffffu, nd[30], src), n3 = __shfl_sync(0xffffffffu, nd[31], src);
        finish_h();
        auto finish_o = [&]() {
            const float gg0 = after_issue(g0, zero), gg1 = after_issue(g1, zero);
            const float s00 = __fdividef(gg0, n0 + 1e-6f), s01 = __fdividef(gg0, n1 + 1e-6f);
            const float s10 = __fdividef(gg1, n2 + 1e-6f), s11 = __fdividef(gg1, n3 + 1e-6f);
            #pragma unroll
            for (int t = 0; t < 7; t++) {
                const bool h1 = t > 3 || (t == 3 && q4 >= 2);
                const float sa = h1 ? s01 : s00, sc = h1 ? s11 : s10;
                op[2 * t] = pack_bf16(nd[4 * t] * sa, nd[4 * t + 1] * sa);
                op[2 * t + 1] = pack_bf16(nd[4 * t + 2] * sc, nd[4 * t + 3] * sc);
            }
            op[14] = 0u; op[15] = 0u;
            reg_fence(op);
            TS(wg, 8);
        };
        #pragma unroll
        for (int c0 = 0; c0 < 7; c0++) {
            float (&o)[32] = (c0 & 1) ? ob : oa;
            if (c0 > 0 || wg == 1) turn_wait();
            issue4(o, 3 * c0);
            if (c0 == 0) finish_o();
            issue4(o, 3 * c0 + 1); issue4(o, 3 * c0 + 2);
            if (!(c0 == 6 && wg == 1)) turn_pass();
            if (c0 >= 2) {
                if (elect_one()) asm volatile("cp.async.bulk.wait_group.read 1;" ::: "memory");
                __syncwarp();
            }
            wg_wait<0>();
            if (c0 < 2) { release(3 * c0); release(3 * c0 + 1); release(3 * c0 + 2); }
            ship(o, c0);
        }
        if (elect_one()) asm volatile("cp.async.bulk.wait_group.read 0;" ::: "memory");
        TS(wg, 16); TSG(wg, 17); TSDUMP(wg, 0, 16); STDUMP();
    }
}

typedef CUresult (*EncodeFn)(CUtensorMap*, CUtensorMapDataType, cuuint32_t, void*, const cuuint64_t*, const cuuint64_t*,
                             const cuuint32_t*, const cuuint32_t*, CUtensorMapInterleave, CUtensorMapSwizzle,
                             CUtensorMapL2promotion, CUtensorMapFloatOOBfill);

void make_map(EncodeFn enc, CUtensorMap* m, const void* base, int rank, const cuuint64_t* dims, const cuuint64_t* strides,
              cuuint32_t b0, cuuint32_t b1, cuuint32_t b2, CUtensorMapSwizzle sw) {
    const cuuint32_t es[3] = {1, 1, 1}, box[3] = {b0, b1, b2};
    enc(m, CU_TENSOR_MAP_DATA_TYPE_BFLOAT16, rank, const_cast<void*>(base), dims, strides, box, es,
        CU_TENSOR_MAP_INTERLEAVE_NONE, sw, CU_TENSOR_MAP_L2_PROMOTION_L2_128B, CU_TENSOR_MAP_FLOAT_OOB_FILL_NONE);
}

}

extern "C" void kernel_launch(void* const* d_in, const int* in_sizes, int n_in, void* d_out, int out_size) {
    (void)in_sizes; (void)n_in; (void)out_size;
    static EncodeFn enc = nullptr;
    if (!enc) {
        void* fn = nullptr;
        cudaDriverEntryPointQueryResult st;
        cudaGetDriverEntryPoint("cuTensorMapEncodeTiled", &fn, cudaEnableDefault, &st);
        enc = (EncodeFn)fn;
        cudaFuncSetAttribute(fused_kernel, cudaFuncAttributeMaxDynamicSharedMemorySize, SMEM_BYTES);
    }
    Maps mp;
    const cuuint64_t dimx[2] = {kD, kS}, dimd[2] = {kD, kF}, dimo[2] = {kD, kD}, strd[1] = {kD * 2};
    make_map(enc, &mp.x, d_in[0], 2, dimx, strd, 64, 128, 1, CU_TENSOR_MAP_SWIZZLE_128B);
    make_map(enc, &mp.out, d_out, 2, dimx, strd, 64, 16, 1, CU_TENSOR_MAP_SWIZZLE_128B);
    make_map(enc, &mp.d, d_in[6], 2, dimd, strd, 64, 56, 1, CU_TENSOR_MAP_SWIZZLE_128B);
    make_map(enc, &mp.o, d_in[2], 2, dimo, strd, 64, 32, 1, CU_TENSOR_MAP_SWIZZLE_128B);
    const cuuint64_t dimq[3] = {kD, kD, 3}, strq[2] = {3 * kD * 2, kD * 2};
    make_map(enc, &mp.kv, d_in[1], 3, dimq, strq, 64, 16, 2, CU_TENSOR_MAP_SWIZZLE_128B);
    make_map(enc, &mp.q, d_in[1], 3, dimq, strq, 64, 16, 1, CU_TENSOR_MAP_SWIZZLE_128B);
    const cuuint64_t dimf[3] = {32, kD, kF / 32}, strf[2] = {kF * 2, 64};
    make_map(enc, &mp.g4, d_in[4], 3, dimf, strf, 32, 16, 4, CU_TENSOR_MAP_SWIZZLE_64B);
    make_map(enc, &mp.g3, d_in[4], 3, dimf, strf, 32, 16, 3, CU_TENSOR_MAP_SWIZZLE_64B);
    make_map(enc, &mp.u4, d_in[5], 3, dimf, strf, 32, 16, 4, CU_TENSOR_MAP_SWIZZLE_64B);
    make_map(enc, &mp.u3, d_in[5], 3, dimf, strf, 32, 16, 3, CU_TENSOR_MAP_SWIZZLE_64B);
    fused_kernel<<<NCTA, NTHREADS, SMEM_BYTES>>>(mp, (const __nv_bfloat16*)d_in[7], (__nv_bfloat16*)d_out,
                                                 (const char*)d_in[0], (const char*)d_in[1], (const char*)d_in[4],
                                                 (const char*)d_in[5], (const char*)d_in[6], (const char*)d_in[2], 0u);
}
```

```cpp
#include <cuda_runtime.h>
#include <cuda_bf16.h>
#include <cuda.h>
#include <stdint.h>

namespace {

constexpr int kS = 2048, kD = 448, kF = 1792;
constexpr int NTHREADS = 384;
constexpr int NCTA = 128;
constexpr uint32_t OFF_X = 0;
constexpr uint32_t OFF_RING = 114688;
constexpr uint32_t SLOT_BYTES = 16384;
constexpr int NSLOT = 6;
constexpr uint32_t OFF_STG = 212992;
constexpr uint32_t OFF_MISC = 229376;
constexpr uint32_t SMEM_BYTES = 232448;
constexpr uint32_t BAR_FULL = OFF_MISC, BAR_EMPTY = OFF_MISC + 48, BAR_XFULL = OFF_MISC + 96;
constexpr uint32_t BAR_W = OFF_MISC + 152, BAR_KVDONE = OFF_MISC + 160, BAR_AUX = OFF_MISC + 168, BAR_P4 = OFF_MISC + 176;
constexpr uint32_t OFF_W = OFF_MISC + 256;
constexpr uint32_t SB = 1024;
#define ZERO_PACE 0
#define KV_PACE 0
#define SKEW 4
#define HDOT 1
#define P4PACE 100
#define OASYM 0
#define QSPLIT 1
#define PRESCALE 1
#define PFN 0
#define PROMO 0
#define BOX56 1
#define ALIGNG 1
#define FASTSTART 1
#define CONSTSB 8
#define TOK2 1
#define FASTFLAG 1
#define PF_LATE 0

__device__ __align__(128) float g_kvacc[8][2048];
__device__ unsigned int g_counter[64];

#define STS4(n, k)
#define PTS(i)
#define PINC()
#define STS_(k)
#define STDUMP()
#define TS(role, idx)
#define TSG(role, idx)
#define TSDUMP(role, lo, hi)

__device__ __forceinline__ void mbar_init(uint32_t bar, uint32_t cnt) {
    asm volatile("mbarrier.init.shared::cta.b64 [%0], %1;" :: "r"(bar), "r"(cnt) : "memory");
}
__device__ __forceinline__ void mbar_expect_tx(uint32_t bar, uint32_t bytes) {
    asm volatile("mbarrier.arrive.expect_tx.shared::cta.b64 _, [%0], %1;" :: "r"(bar), "r"(bytes) : "memory");
}
__device__ __forceinline__ void mbar_arrive(uint32_t bar) {
    asm volatile("mbarrier.arrive.shared::cta.b64 _, [%0];" :: "r"(bar) : "memory");
}
__device__ __forceinline__ void mbar_arrive_cluster(uint32_t bar) {
    asm volatile("mbarrier.arrive.shared::cluster.b64 _, [%0];" :: "r"(bar) : "memory");
}
__device__ __forceinline__ void mbar_wait(uint32_t bar, uint32_t parity) {
    asm volatile("{\n"
                 ".reg .pred p;\n"
                 ".reg .u32 c;\n"
                 "mov.u32 c, 0;\n"
                 "AGAIN:\n"
                 "mbarrier.try_wait.parity.shared::cta.b64 p, [%0], %1;\n"
                 "@p bra DONE;\n"
                 "add.u32 c, c, 1;\n"
                 "setp.lt.u32 p, c, 4194304;\n"
                 "@p bra AGAIN;\n"
                 "trap;\n"
                 "DONE:\n"
                 "}" :: "r"(bar), "r"(parity) : "memory");
}
__device__ __forceinline__ uint32_t mapa(uint32_t addr, uint32_t cta) {
    uint32_t r; asm("mapa.shared::cluster.u32 %0, %1, %2;" : "=r"(r) : "r"(addr), "r"(cta)); return r;
}
__device__ __forceinline__ bool elect_one() {
    uint32_t p;
    asm volatile("{ .reg .pred P; elect.sync _|P, 0xffffffff; selp.u32 %0, 1, 0, P; }" : "=r"(p));
    return p;
}
__device__ __forceinline__ void tma2d(uint32_t dst, const CUtensorMap* m, int c0, int c1, uint32_t bar) {
    asm volatile("cp.async.bulk.tensor.2d.shared::cluster.global.mbarrier::complete_tx::bytes [%0], [%1, {%3, %4}], [%2];"
                 :: "r"(dst), "l"(m), "r"(bar), "r"(c0), "r"(c1) : "memory");
}
__device__ __forceinline__ void tma3d(uint32_t dst, const CUtensorMap* m, int c0, int c1, int c2, uint32_t bar) {
    asm volatile("cp.async.bulk.tensor.3d.shared::cluster.global.mbarrier::complete_tx::bytes [%0], [%1, {%3, %4, %5}], [%2];"
                 :: "r"(dst), "l"(m), "r"(bar), "r"(c0), "r"(c1), "r"(c2) : "memory");
}
__device__ __forceinline__ void tma2d_mc(uint32_t dst, const CUtensorMap* m, int c0, int c1, uint32_t bar) {
    asm volatile("cp.async.bulk.tensor.2d.shared::cluster.global.mbarrier::complete_tx::bytes.multicast::cluster [%0], [%1, {%3, %4}], [%2], %5;"
                 :: "r"(dst), "l"(m), "r"(bar), "r"(c0), "r"(c1), "h"((uint16_t)3) : "memory");
}
__device__ __forceinline__ void tma3d_mc(uint32_t dst, const CUtensorMap* m, int c0, int c1, int c2, uint32_t bar) {
    asm volatile("cp.async.bulk.tensor.3d.shared::cluster.global.mbarrier::complete_tx::bytes.multicast::cluster [%0], [%1, {%3, %4, %5}], [%2], %6;"
                 :: "r"(dst), "l"(m), "r"(bar), "r"(c0), "r"(c1), "r"(c2), "h"((uint16_t)3) : "memory");
}
__device__ __forceinline__ void tma_reduce2d(const CUtensorMap* m, uint32_t src, int c0, int c1) {
    asm volatile("cp.reduce.async.bulk.tensor.2d.global.shared::cta.add.bulk_group [%0, {%2, %3}], [%1];"
                 :: "l"(m), "r"(src), "r"(c0), "r"(c1) : "memory");
}
__device__ __forceinline__ void bulk_reduce_f32(float* dst, uint32_t src, uint32_t bytes) {
    asm volatile("cp.reduce.async.bulk.global.shared::cta.bulk_group.add.f32 [%0], [%1], %2;" :: "l"(dst), "r"(src), "r"(bytes) : "memory");
}
__device__ __forceinline__ bool mbar_try(uint32_t bar, uint32_t parity) {
    uint32_t ok;
    asm volatile("{ .reg .pred p; mbarrier.test_wait.parity.shared::cta.b64 p, [%1], %2; selp.u32 %0, 1, 0, p; }"
                 : "=r"(ok) : "r"(bar), "r"(parity) : "memory");
    return ok;
}
__device__ __forceinline__ void prefetch_map(const CUtensorMap* m) {
    asm volatile("prefetch.tensormap [%0];" :: "l"(m) : "memory");
}
__device__ __forceinline__ void prefetch3d(const CUtensorMap* m, int c0, int c1, int c2) {
    asm volatile("cp.async.bulk.prefetch.tensor.3d.L2.global.tile [%0, {%1, %2, %3}];" :: "l"(m), "r"(c0), "r"(c1), "r"(c2) : "memory");
}
__device__ __forceinline__ void prefetch2d(const CUtensorMap* m, int c0, int c1) {
    asm volatile("cp.async.bulk.prefetch.tensor.2d.L2.global.tile [%0, {%1, %2}];" :: "l"(m), "r"(c0), "r"(c1) : "memory");
}
__device__ __forceinline__ void prefetch_l2(const void* p) { asm volatile("prefetch.global.L2 [%0];" :: "l"(p)); }
__device__ __forceinline__ void prefetch_bulk(const void* p, uint32_t bytes) {
    asm volatile("cp.async.bulk.prefetch.L2.global [%0], %1;" :: "l"(p), "r"(bytes) : "memory");
}
__device__ __forceinline__ void wg_fence() { asm volatile("wgmma.fence.sync.aligned;" ::: "memory"); }
__device__ __forceinline__ void wg_commit() { asm volatile("wgmma.commit_group.sync.aligned;" ::: "memory"); }
template <int N> __device__ __forceinline__ void wg_wait() { asm volatile("wgmma.wait_group.sync.aligned %0;" :: "n"(N) : "memory"); }
template <int N> __device__ __forceinline__ void reg_fence(float (&d)[N]) {
#pragma unroll
    for (int i = 0; i < N; i++) asm volatile("" : "+f"(d[i]) :: "memory");
}
template <int N> __device__ __forceinline__ void reg_fence(uint32_t (&d)[N]) {
#pragma unroll
    for (int i = 0; i < N; i++) asm volatile("" : "+r"(d[i]) :: "memory");
}
template <int LO, int HI, int N> __device__ __forceinline__ void reg_fence_part(uint32_t (&d)[N]) {
#pragma unroll
    for (int i = LO; i < HI; i++) asm volatile("" : "+r"(d[i]) :: "memory");
}
__device__ __forceinline__ void fence_async_smem() { asm volatile("fence.proxy.async.shared::cta;" ::: "memory"); }
template <int ID, int N> __device__ __forceinline__ void bar_sync() { asm volatile("bar.sync %0, %1;" :: "n"(ID), "n"(N) : "memory"); }
template <int ID, int N> __device__ __forceinline__ void bar_arrive() { asm volatile("bar.arrive %0, %1;" :: "n"(ID), "n"(N) : "memory"); }
__device__ __forceinline__ void ldsm4(uint32_t* r, uint32_t addr) {
    asm volatile("ldmatrix.sync.aligned.m8n8.x4.shared.b16 {%0, %1, %2, %3}, [%4];"
                 : "=r"(r[0]), "=r"(r[1]), "=r"(r[2]), "=r"(r[3]) : "r"(addr) : "memory");
}
__device__ __forceinline__ void stsm4(uint32_t addr, uint32_t r0, uint32_t r1, uint32_t r2, uint32_t r3) {
    asm volatile("stmatrix.sync.aligned.m8n8.x4.shared.b16 [%0], {%1, %2, %3, %4};"
                 :: "r"(addr), "r"(r0), "r"(r1), "r"(r2), "r"(r3) : "memory");
}
__device__ __forceinline__ uint32_t lds32(uint32_t addr) {
    uint32_t r; asm volatile("ld.shared.u32 %0, [%1];" : "=r"(r) : "r"(addr)); return r;
}
__device__ __forceinline__ float4 lds128f(uint32_t addr) {
    float4 r; asm volatile("ld.shared.v4.f32 {%0, %1, %2, %3}, [%4];" : "=f"(r.x), "=f"(r.y), "=f"(r.z), "=f"(r.w) : "r"(addr)); return r;
}
__device__ __forceinline__ uint32_t clock32() { uint32_t t; asm volatile("mov.u32 %0, %%clock;" : "=r"(t)); return t; }
__device__ __forceinline__ uint32_t pack_bf16(float lo, float hi) {
    uint32_t r; asm("cvt.rn.bf16x2.f32 %0, %1, %2;" : "=r"(r) : "f"(hi), "f"(lo)); return r;
}
__device__ __forceinline__ uint32_t pack_relu_bf16(float lo, float hi) {
    uint32_t r; asm("cvt.rn.relu.bf16x2.f32 %0, %1, %2;" : "=r"(r) : "f"(hi), "f"(lo)); return r;
}
__device__ __forceinline__ uint32_t mul_bf16x2(uint32_t a, uint32_t b) {
    uint32_t r; asm("mul.rn.bf16x2 %0, %1, %2;" : "=r"(r) : "r"(a), "r"(b)); return r;
}
__device__ __forceinline__ uint32_t fma_bf16x2(uint32_t a, uint32_t b, uint32_t c) {
    uint32_t r; asm("fma.rn.bf16x2 %0, %1, %2, %3;" : "=r"(r) : "r"(a), "r"(b), "r"(c)); return r;
}
__device__ __forceinline__ float phi(float t, float log2e) {
    float r;
    asm("{ .reg .pred p; .reg .f32 e;\n"
        "mul.f32 e, %1, %2;\n"
        "ex2.approx.ftz.f32 e, e;\n"
        "setp.gt.f32 p, %1, 0f00000000;\n"
        "add.f32 %0, e, 0f358637BD;\n"
        "@p add.f32 %0, %1, 0f3F800008; }" : "=&f"(r) : "f"(t), "f"(log2e));
    return r;
}
__device__ __forceinline__ float after_issue(float v, uint32_t zero) {
    return __uint_as_float(__float_as_uint(v) | (clock32() & zero));
}
constexpr float kLog2e = 1.4426950408889634f;
__device__ __forceinline__ float bf_lo(uint32_t v) { return __uint_as_float(v << 16); }
__device__ __forceinline__ float bf_hi(uint32_t v) { return __uint_as_float(v & 0xffff0000u); }
constexpr uint32_t HI128 = (1024 >> 4) | (1u << 30);
constexpr uint32_t HI64 = (512 >> 4) | (2u << 30);
constexpr uint32_t LO128 = 1u << 16, LO64 = (1024u >> 4) << 16, LO128X2 = (2048u >> 4) << 16;
constexpr uint32_t HIG4 = ALIGNG ? HI128 : HI64, LOG4 = ALIGNG ? LO128X2 : LO64;
constexpr uint32_t QB = BOX56 ? 16 * 112 : 2048;
constexpr uint32_t TX1 = 2 * (2 * QB + 4096), TX2 = 2 * (QB + 4096);
__device__ __forceinline__ void grid_arrive(unsigned int* c) {
    asm volatile("fence.acq_rel.gpu;" ::: "memory");
    asm volatile("red.relaxed.gpu.global.add.u32 [%0], 1;" :: "l"(c) : "memory");
}
__device__ __forceinline__ void grid_wait(const unsigned int* c, unsigned int target) {
    unsigned int v; int it = 0;
    do {
        asm volatile("ld.relaxed.gpu.global.u32 %0, [%1];" : "=r"(v) : "l"(c) : "memory");
        if (++it > (1 << 22)) asm volatile("trap;");
    } while ((int)(v - target) < 0);
    if (!FASTFLAG) asm volatile("ld.acquire.gpu.global.u32 %0, [%1];" : "=r"(v) : "l"(c) : "memory");
}

__host__ __device__ constexpr uint32_t p4_pack(int n) { return (n / 3) * 36864 + (n % 3) * 14336; }
__host__ __device__ constexpr uint32_t p4_off(int n) {
    return n < 6 ? OFF_X + p4_pack(n) : n < 14 ? OFF_RING + p4_pack(n - 6) : n == 14 ? OFF_X + p4_pack(6) : OFF_X + p4_pack(n - 15);
}
__host__ __device__ constexpr uint32_t p4_bar(int n) {
    return n < 6 ? BAR_XFULL + 8 * n : n < 12 ? BAR_FULL + 8 * (n - 6) : n < 14 ? BAR_P4 + 8 * (n - 12)
                 : n == 14 ? BAR_XFULL + 48 : BAR_XFULL + 8 * (n - 15);
}
__host__ __device__ constexpr uint32_t p4_par(int n) { return (n < 12 || n == 14) ? 1 : 0; }
constexpr uint32_t OFF_OUT = OFF_X + 5 * 16384;
static_assert(p4_off(7) == p4_off(6) + 14336 && p4_off(13) == p4_off(12) + 14336 && p4_off(16) == p4_off(15) + 14336, "Wd halves");
static_assert(p4_off(13) + 14336 <= OFF_STG + 8192 && p4_off(14) + 8192 == OFF_OUT, "pass-4 layout");

struct Ring {
    uint32_t slot, phase;
    __device__ __forceinline__ void advance() { if (++slot == NSLOT) { slot = 0; phase ^= 1; } }
};

struct Maps { CUtensorMap x, kv, q, g4, g3, u4, u3, d, o, out; };

__global__ void __cluster_dims__(2, 1, 1) __launch_bounds__(NTHREADS, 1)
fused_kernel(const __grid_constant__ Maps mp, const __nv_bfloat16* __restrict__ gate_w, __nv_bfloat16* __restrict__ out,
             const char* __restrict__ pX, const char* __restrict__ pQKV, const char* __restrict__ pG,
             const char* __restrict__ pU, const char* __restrict__ pD, const char* __restrict__ pO, uint32_t zero)
{
    extern __shared__ __align__(1024) unsigned char smem[];
    const uint32_t sb = (uint32_t)__cvta_generic_to_shared(smem);
    const int tid = threadIdx.x, warp = tid >> 5, lane = tid & 31;
    const int rank = blockIdx.x & 1, j = (blockIdx.x >> 1) & 7;
    const int row0 = ((blockIdx.x >> 4) * 2 + rank) * 128;
    const int par = ALIGNG ? (j & 1) : 0;
    const int g4i = ALIGNG ? (7 * j + 3 * par) >> 1 : 7 * j;

    TSG(2, 0); TS(2, 1);
    if (warp == 8) {
        if (elect_one()) {
            prefetch_map(&mp.kv); prefetch_map(&mp.g4);
            #pragma unroll
            for (int s = 0; s < NSLOT; s++) {
                mbar_init(sb + BAR_FULL + 8 * s, 1);
                mbar_init(sb + BAR_EMPTY + 8 * s, 4);
            }
            asm volatile("fence.mbarrier_init.release.cluster;" ::: "memory");
        }
        __syncwarp();
    } else if (warp == 9) {
        if (elect_one()) {
            prefetch_map(&mp.x);
            mbar_init(sb + BAR_XFULL, 1);
            mbar_init(sb + BAR_W, 1);
            asm volatile("fence.mbarrier_init.release.cluster;" ::: "memory");
            mbar_expect_tx(sb + BAR_XFULL, 16384);
            tma2d(sb + OFF_X, &mp.x, 0, row0, sb + BAR_XFULL);
            mbar_expect_tx(sb + BAR_W, 896);
            asm volatile("cp.async.bulk.shared::cluster.global.mbarrier::complete_tx::bytes [%0], [%1], 896, [%2];"
                         :: "r"(sb + OFF_W), "l"(gate_w), "r"(sb + BAR_W) : "memory");
        }
        __syncwarp();
    } else if (warp == 10) {
        if (elect_one()) {
            #pragma unroll
            for (int s = 1; s < 7; s++) mbar_init(sb + BAR_XFULL + 8 * s, 1);
            mbar_init(sb + BAR_KVDONE, 8);
            mbar_init(sb + BAR_AUX, 3);
            mbar_init(sb + BAR_P4, 1);
            mbar_init(sb + BAR_P4 + 8, 1);
            asm volatile("fence.mbarrier_init.release.cluster;" ::: "memory");
            if ((sb & 0xFFFFFF) != SB) asm volatile("trap;");
        }
        __syncwarp();
    }
    asm volatile("barrier.cluster.arrive.relaxed.aligned;" ::: "memory");
    if (FASTSTART && warp == 8) {
        if (elect_one()) {
            #pragma unroll
            for (int s = 0; s < FASTSTART; s++) mbar_expect_tx(sb + BAR_FULL + 8 * s, TX1);
        }
        __syncwarp();
    }
    asm volatile("barrier.cluster.wait.aligned;" ::: "memory");
    if (FASTSTART && warp == 8) {
        if (elect_one()) {
            #pragma unroll
            for (int s = 0; s < FASTSTART; s++) {
                const uint32_t dst = sb + OFF_RING + s * SLOT_BYTES + rank * 8192;
                tma3d_mc(dst, &mp.kv, 56 * j, 32 * s + 16 * rank, 1, sb + BAR_FULL + 8 * s);
                tma3d_mc(dst + 4096, &mp.g4, 0, 32 * s + 16 * rank, g4i, sb + BAR_FULL + 8 * s);
                if (s & 1) {
                    const int n = (s >> 1) + 1;
                    mbar_expect_tx(sb + BAR_XFULL + 8 * n, 16384);
                    tma2d(sb + OFF_X + n * 16384, &mp.x, 64 * n, row0, sb + BAR_XFULL + 8 * n);
                }
            }
        }
        __syncwarp();
    }

    if (warp >= 8) {
        asm volatile("setmaxnreg.dec.sync.aligned.u32 40;");
        if (warp == 8) {
            if (elect_one()) {
                Ring r{FASTSTART, 1};
                const int pcl = blockIdx.x >> 4;
                auto acquire = [&](uint32_t bytes) -> uint32_t {
                    mbar_wait(sb + BAR_EMPTY + 8 * r.slot, r.phase);
                    PTS(pidx); PINC();
                    mbar_expect_tx(sb + BAR_FULL + 8 * r.slot, bytes);
                    return sb + OFF_RING + r.slot * SLOT_BYTES;
                };
                #pragma unroll 1
                for (int s = FASTSTART; s < 14; s++) {
                    const uint32_t dst = acquire(TX1) + rank * 8192;
                    tma3d_mc(dst, &mp.kv, 56 * j, 32 * s + 16 * rank, 1, sb + BAR_FULL + 8 * r.slot);
                    tma3d_mc(dst + 4096, &mp.g4, 0, 32 * s + 16 * rank, g4i, sb + BAR_FULL + 8 * r.slot);
                    r.advance();
                    if ((s & 1) && s < 12) {
                        const int n = (s >> 1) + 1;
                        mbar_expect_tx(sb + BAR_XFULL + 8 * n, 16384);
                        tma2d(sb + OFF_X + n * 16384, &mp.x, 64 * n, row0, sb + BAR_XFULL + 8 * n);
                    }
                    if ((PFN & 1) && s >= 6 && ((s - pcl) & 3) == 0) {
                        const int t = (s >= 10 ? 8 : 0) + pcl;
                        if (t < 14) { prefetch3d(&mp.q, 56 * j, 32 * t + 16 * rank, 0); prefetch3d(&mp.u4, 0, 32 * t + 16 * rank, g4i); }
                    }
                    if (s == 5 + FASTSTART - FASTSTART) { prefetch_map(&mp.q); prefetch_map(&mp.u4); prefetch_map(&mp.g3); prefetch_map(&mp.u3); prefetch_map(&mp.d); prefetch_map(&mp.o); prefetch_map(&mp.out); }
                }
                #pragma unroll 1
                for (int s = 0; s < 14; s++) {
                    const uint32_t dst = acquire(TX2) + rank * 6144;
                    tma3d_mc(dst, &mp.q, 56 * j, 32 * s + 16 * rank, 0, sb + BAR_FULL + 8 * r.slot);
                    tma3d_mc(dst + 2048, &mp.u4, 0, 32 * s + 16 * rank, g4i, sb + BAR_FULL + 8 * r.slot);
                    r.advance();
                    if ((PFN & 2) && ((s - pcl) & 7) == 0) {
                        prefetch3d(&mp.g3, 0, 32 * s + 16 * rank, 7 * j + 4 - 4 * par);
                        prefetch3d(&mp.u3, 0, 32 * s + 16 * rank, 7 * j + 4 - 4 * par);
                    }
                    if ((PFN & 4) && s >= 7 && pcl < 7) {
                        if (s < 9) prefetch2d(&mp.d, 64 * pcl, 224 * j + 112 * (s - 7) + 56 * rank);
                        else if (s == 9) prefetch2d(&mp.o, 64 * pcl, 56 * j + 32 * rank);
                    }
                }
                const int cfirst = j == 7 ? 0 : j;
                auto load4 = [&](int n) {
                    PTS(42 + n);
                    int c = cfirst + n / 3;
                    if (c >= 7) c -= 7;
                    mbar_expect_tx(sb + p4_bar(n), n % 3 == 2 ? 8192 : 14336);
                    if (n % 3 == 2) tma2d_mc(sb + p4_off(n) + rank * 4096, &mp.o, 64 * c, 56 * j + 32 * rank, sb + p4_bar(n));
                    else tma2d_mc(sb + p4_off(n) + rank * 7168, &mp.d, 64 * c, 224 * j + 112 * (n % 3) + 56 * rank, sb + p4_bar(n));
                };
                #pragma unroll 1
                for (int s = 0; s < 14; s++) {
                    const uint32_t dst = acquire(12288) + rank * 6144;
                    tma3d_mc(dst, &mp.g3, 0, 32 * s + 16 * rank, 7 * j + 4 - 4 * par, sb + BAR_FULL + 8 * r.slot);
                    tma3d_mc(dst + 3072, &mp.u3, 0, 32 * s + 16 * rank, 7 * j + 4 - 4 * par, sb + BAR_FULL + 8 * r.slot);
                    r.advance();
                    if (s == 7) load4(0);
                    if (s == 9) load4(1);
                    if (s == 11) load4(2);
                    if (s == 13) { load4(3); load4(4); }
                }
                mbar_wait(sb + BAR_EMPTY, 0);      load4(6);
                mbar_wait(sb + BAR_EMPTY + 8, 0);  load4(5); load4(7); load4(14);
                mbar_wait(sb + BAR_EMPTY + 16, 0); load4(8);
                mbar_wait(sb + BAR_EMPTY + 24, 0); load4(9); load4(10);
                mbar_wait(sb + BAR_EMPTY + 32, 0); load4(11);
                mbar_wait(sb + BAR_EMPTY + 40, 0); load4(12);
                mbar_wait(sb + BAR_AUX, 0);        load4(13);
                #pragma unroll
                for (int n = 15; n < 21; n++) { mbar_wait(sb + BAR_EMPTY + 8 * (n - 15), 1); if (P4PACE) __nanosleep(P4PACE); load4(n); }
            }
        } else {
            const int ht = tid - 288;
            unsigned int cnt0;
            asm volatile("ld.relaxed.gpu.global.u32 %0, [%1];" : "=r"(cnt0) : "l"(&g_counter[32]) : "memory");
            const unsigned int target = ((cnt0 >> 7) + 1) << 7;
            if (warp == 9) {
                reinterpret_cast<float4*>(&g_kvacc[0][0])[blockIdx.x * 32 + lane] = make_float4(0.f, 0.f, 0.f, 0.f);
                asm volatile("fence.proxy.async.global;" ::: "memory");
                __syncwarp();
                if (lane == 0) grid_arrive(&g_counter[0]);
                TS(2, 2);
                mbar_wait(sb + BAR_XFULL + 8 * 6, 0);
                uint4* o = reinterpret_cast<uint4*>(out) + blockIdx.x * 896 + lane;
                #pragma unroll 1
                for (int q = 0; q < 14; q++) {
                    o[q * 64] = make_uint4(0, 0, 0, 0);
                    o[q * 64 + 32] = make_uint4(0, 0, 0, 0);
                    if (ZERO_PACE) __nanosleep(ZERO_PACE);
                }
                asm volatile("fence.proxy.async.global;" ::: "memory");
                __syncwarp();
                if (lane == 0) {
                    if (FASTFLAG) asm volatile("fence.acq_rel.gpu;" ::: "memory");
                    grid_wait(&g_counter[0], target);
                }
                __syncwarp();
                TS(2, 7);
            }
            mbar_wait(sb + BAR_KVDONE, 0);
            TS(2, 3);
            {
                #pragma unroll
                for (int i0 = 0; i0 < 5; i0 += 3) {
                    float4 pa[3], pb[3];
                    #pragma unroll
                    for (int i = 0; i < 3 && i0 + i < 5; i++) {
                        const int q = min(ht + 96 * (i0 + i), 447);
                        pa[i] = lds128f(sb + OFF_STG + q * 16); pb[i] = lds128f(sb + OFF_STG + 8192 + q * 16);
                    }
                    #pragma unroll
                    for (int i = 0; i < 3 && i0 + i < 5; i++) {
                        const int q = ht + 96 * (i0 + i);
                        if (q < 448) asm volatile("st.shared.v4.f32 [%0], {%1, %2, %3, %4};" :: "r"(sb + OFF_STG + q * 16),
                            "f"(pa[i].x + pb[i].x), "f"(pa[i].y + pb[i].y), "f"(pa[i].z + pb[i].z), "f"(pa[i].w + pb[i].w) : "memory");
                    }
                }
                fence_async_smem();
            }
            bar_sync<3, 96>();
            if (warp == 9) {
                if (elect_one()) {
                    if (KV_PACE) {
                        #pragma unroll 1
                        for (int q = 0; q < 7; q++) {
                            bulk_reduce_f32(&g_kvacc[j][q * 256], sb + OFF_STG + q * 1024, 1024);
                            __nanosleep(KV_PACE);
                        }
                    } else {
                        bulk_reduce_f32(&g_kvacc[j][0], sb + OFF_STG, 7168);
                    }
                    asm volatile("cp.async.bulk.commit_group;" ::: "memory");
                    asm volatile("cp.async.bulk.wait_group 0;" ::: "memory");
                    if (FASTFLAG) asm volatile("red.relaxed.gpu.global.add.u32 [%0], 1;" :: "l"(&g_counter[32]) : "memory");
                    else grid_arrive(&g_counter[32]);
                    TS(2, 4);
                }
            }
            __syncwarp();
            #pragma unroll
            for (int i = 0; i < 3; i++) {
                const int q = ht + 96 * i;
                const int d = q < 168 ? q / 3 : 56 + ((q - 168) >> 3);
                const int c = q < 168 ? (q - 3 * d + (d < 28 ? 4 : 0)) : (q & 7);
                if (q < 232) asm volatile("st.shared.v4.u32 [%0], {%1, %1, %1, %1};" :: "r"(sb + OFF_STG + 8192 + d * 128 + ((c ^ (d & 7)) << 4)), "r"(0) : "memory");
            }
            if (lane == 0) grid_wait(&g_counter[32], target);
            __syncwarp();
            TS(2, 5);
            const float4* src = reinterpret_cast<const float4*>(&g_kvacc[j][0]);
            float4 va[3], vb[3];
            #pragma unroll
            for (int i = 0; i < 3; i++) {
                const int q = ht + 96 * i, d = q / 5, m = q - 5 * d;
                const int pc = m < 4 ? m : (d < 28 ? 3 : 0);
                if (q < 280) { va[i] = __ldcg(src + d * 8 + 2 * (pc ^ (d & 3))); vb[i] = __ldcg(src + d * 8 + 2 * (pc ^ (d & 3)) + 1); }
            }
            #pragma unroll
            for (int i = 0; i < 3; i++) {
                const int q = ht + 96 * i, d = q / 5, m = q - 5 * d;
                const bool h0 = d < 28;
                const int c = m == 4 ? 7 : (h0 ? m : m + 3);
                uint32_t w0 = pack_bf16(va[i].x, va[i].y), w1 = pack_bf16(va[i].z, va[i].w);
                uint32_t w2 = pack_bf16(vb[i].x, vb[i].y), w3 = pack_bf16(vb[i].z, vb[i].w);
                if (m == 4) { w0 = h0 ? (w2 & 0xffffu) : (w0 << 16); w1 = w2 = w3 = 0u; }
                else if (c == 3) { if (h0) w2 = w3 = 0u; else w0 = w1 = 0u; }
                if (q < 280)
                    asm volatile("st.shared.v4.u32 [%0], {%1, %2, %3, %4};"
                                 :: "r"(sb + OFF_STG + 8192 + d * 128 + ((c ^ (d & 7)) << 4)), "r"(w0), "r"(w1), "r"(w2), "r"(w3) : "memory");
            }
            fence_async_smem();
            __syncwarp();
            if (lane == 0) mbar_arrive(sb + BAR_AUX);
            TS(2, 6); TSDUMP(2, 1, 7);
        }
    } else {
        asm volatile("setmaxnreg.inc.sync.aligned.u32 232;");
        const int wg = warp >> 2, w4 = warp & 3;
        const int q4 = lane & 3, g8 = lane >> 2;
        const uint32_t lx = ((lane >> 4) ^ (lane & 7)) << 4;
        const uint32_t xa = ((CONSTSB & 1) ? SB : sb) + OFF_X + (warp * 16 + (lane & 15)) * 128;
        const uint32_t empty_dst = mapa(sb + BAR_EMPTY, w4 & 1);
        const uint32_t cb = (CONSTSB & 1) ? SB : sb;
        const uint32_t mb = (CONSTSB & 2) ? SB : sb, tb = (CONSTSB & 4) ? SB : sb;
        const bool signaller = lane == 0 && w4 < 2;
        const uint32_t dsb = (CONSTSB & 8) ? SB >> 4 : (cb & 0x3FFFF) >> 4;
        Ring r{0, 0};
        uint32_t cur = 0, old = 0;
        bool ready = false;
        auto release = [&](uint32_t slot) { if (signaller) mbar_arrive_cluster(empty_dst + 8 * slot); };
        auto turn_wait = [&]() { if (wg == 0) bar_sync<6, 256>(); else bar_sync<7, 256>(); };
        auto turn_pass = [&]() { if (wg == 0) bar_arrive<7, 256>(); else bar_arrive<6, 256>(); };
        auto begin = [&]() -> uint32_t {
            STS_(0);
            if (!ready) mbar_wait(mb + BAR_FULL + 8 * r.slot, r.phase);
            STS_(1);
            wg_fence();
            return dsb + (OFF_RING >> 4) + r.slot * (SLOT_BYTES >> 4);
        };
        auto commit = [&]() { wg_commit(); old = cur; cur = r.slot; r.advance(); };
        auto retire = [&]() { wg_wait<1>(); release(old); };
        auto peek = [&]() { ready = mbar_try(mb + BAR_FULL + 8 * r.slot, r.phase); };
        auto skew_hold = [&](int pass) { if (((SKEW >> pass) & 1) && wg == 1) bar_sync<4, 256>(); };
        auto skew_go = [&](int pass) { if (((SKEW >> pass) & 1) && wg == 0) bar_arrive<4, 256>(); };
        uint32_t a0[8], a1[8];
        auto load_a0 = [&](int kc) { ldsm4(a0, xa + kc * 16384 + lx); ldsm4(a0 + 4, xa + kc * 16384 + (lx ^ 32)); };
        auto load_a1 = [&](int kc) { ldsm4(a1, xa + kc * 16384 + (lx ^ 64)); ldsm4(a1 + 4, xa + kc * 16384 + (lx ^ 96)); };
        TS(wg, 0);

        uint32_t hp[56], pv[14];
        float g0, g1, ak[28];
        {
            float av[28], ag[64];
            float d0 = 0.f, d1 = 0.f, d2 = 0.f, d3 = 0.f;
            uint32_t w0[4], w1[4];
            auto issue1 = [&](uint32_t (&a)[8], int sd) {
                const uint32_t b = begin();
                wgmma_rs56<HI128>(ak, a[0], a[1], a[2], a[3], b + LO128, sd);
                wgmma_rs56<HI128>(av, a[0], a[1], a[2], a[3], b + LO128 + 128, sd);
                wgmma_rs128<HIG4>(ag, a[0], a[1], a[2], a[3], b + LOG4 + 256, sd);
                wgmma_rs56<HI128>(ak, a[4], a[5], a[6], a[7], b + LO128 + 512, 1);
                wgmma_rs56<HI128>(av, a[4], a[5], a[6], a[7], b + LO128 + 640, 1);
                wgmma_rs128<HIG4>(ag, a[4], a[5], a[6], a[7], b + LOG4 + 768, 1);
                commit();
            };
            auto load_w = [&](uint32_t (&w)[4], int s) {
                #pragma unroll
                for (int e = 0; e < 4; e++) w[e] = lds32(cb + OFF_W + s * 64 + q4 * 4 + e * 16);
            };
            auto dot = [&](uint32_t (&a)[8], uint32_t (&w)[4]) {
                if (HDOT) {
                    uint32_t p0 = mul_bf16x2(a[0], w[0]), p1 = mul_bf16x2(a[1], w[0]);
                    #pragma unroll
                    for (int e = 1; e < 4; e++) { p0 = fma_bf16x2(a[2 * e], w[e], p0); p1 = fma_bf16x2(a[2 * e + 1], w[e], p1); }
                    d0 += bf_lo(p0); d2 += bf_hi(p0); d1 += bf_lo(p1); d3 += bf_hi(p1);
                } else
                #pragma unroll
                for (int e = 0; e < 4; e++) {
                    d0 = fmaf(bf_lo(a[2 * e]), bf_lo(w[e]), d0);     d2 = fmaf(bf_hi(a[2 * e]), bf_hi(w[e]), d2);
                    d1 = fmaf(bf_lo(a[2 * e + 1]), bf_lo(w[e]), d1); d3 = fmaf(bf_hi(a[2 * e + 1]), bf_hi(w[e]), d3);
                }
                asm volatile("" : "+f"(d0), "+f"(d1), "+f"(d2), "+f"(d3));
            };
            mbar_wait(mb + BAR_XFULL, 0);
            TS(wg, 1);
            load_a0(0);
            mbar_wait(mb + BAR_W, 0);
            load_w(w0, 0);
            #pragma unroll 1
            for (int it = 0; it < 7; it++) {
                if (it == 6) skew_hold(0);
                issue1(a0, it);
                if (it == 0) TS(wg, 2);
                wg_wait<1>();
                if (it > 0) release(old);
                load_a1(it);
                load_w(w1, 2 * it + 1);
                peek();
                const int nx = it < 6 ? it + 1 : 0;
                const bool xok = mbar_try(mb + BAR_XFULL + 8 * nx, 0);
                dot(a0, w0);
                issue1(a1, 1);
                if (it == 6) skew_go(0);
                retire();
                if (!xok) mbar_wait(mb + BAR_XFULL + 8 * nx, 0);
                load_a0(nx);
                load_w(w0, 2 * nx);
                peek();
                dot(a1, w1);
            }
            d0 += d2; d1 += d3;
            d0 += __shfl_xor_sync(0xffffffffu, d0, 1); d1 += __shfl_xor_sync(0xffffffffu, d1, 1);
            d0 += __shfl_xor_sync(0xffffffffu, d0, 2); d1 += __shfl_xor_sync(0xffffffffu, d1, 2);
            wg_wait<0>();
            reg_fence(ak); reg_fence(av); reg_fence(ag);
            release(cur);
            if (wg == 0) bar_arrive<8, 256>();
            #pragma unroll
            for (int i = 0; i < 32; i++) hp[i] = pack_relu_bf16(ag[2 * i], ag[2 * i + 1]);
            #pragma unroll
            for (int i = 0; i < 14; i++) pv[i] = pack_bf16(av[2 * i], av[2 * i + 1]);
            reg_fence_part<0, 32>(hp); reg_fence(pv);
            g0 = d0; g1 = d1;
        }
        TS(wg, 3);

        float aq[28], au[64];
        {
            auto issue2 = [&](uint32_t (&a)[8], int sd) {
                const uint32_t b = begin();
                wgmma_rs56<HI128>(aq, a[0], a[1], a[2], a[3], b + LO128, sd);
                wgmma_rs128<HIG4>(au, a[0], a[1], a[2], a[3], b + LOG4 + 128, sd);
                wgmma_rs56<HI128>(aq, a[4], a[5], a[6], a[7], b + LO128 + 384, 1);
                wgmma_rs128<HIG4>(au, a[4], a[5], a[6], a[7], b + LOG4 + 512, 1);
            };
            const uint32_t st_base = wg == 0 ? OFF_STG : OFF_RING + 12288, st_step = wg == 0 ? 2048 : SLOT_BYTES, st_v = wg == 0 ? 8192 : 2048;
            const uint32_t sk = cb + st_base + w4 * st_step + (lane & 15) * 128;
            auto stage_k = [&](int t) {
                const float l2e = TOK2 ? after_issue(kLog2e, zero) : kLog2e;
                uint32_t p[4];
                #pragma unroll
                for (int e = 0; e < 4; e++)
                    p[e] = 4 * t + e < 14 ? pack_bf16(phi(ak[8 * t + 2 * e], l2e), phi(ak[8 * t + 2 * e + 1], l2e)) : 0u;
                stsm4(sk + (lx ^ (t * 32)), p[0], p[1], p[2], p[3]);
            };
            issue2(a0, 0); commit();
            load_a1(0); peek();
            if (wg == 1) bar_sync<8, 256>();
            {
                const uint32_t ones = q4 == 0 ? 0x3f803f80u : 0u;
                #pragma unroll
                for (int t = 0; t < 3; t++) stsm4(sk + st_v + (lx ^ (t * 32)), pv[4 * t], pv[4 * t + 1], pv[4 * t + 2], pv[4 * t + 3]);
                stsm4(sk + st_v + (lx ^ 96), pv[12], pv[13], ones, ones);
            }
            issue2(a1, 1); commit();
            retire(); load_a0(1); peek();
            stage_k(0);
            issue2(a0, 1); commit();
            retire(); load_a1(1); peek();
            stage_k(1);
            issue2(a1, 1); commit();
            retire(); load_a0(2); peek();
            stage_k(2);
            issue2(a0, 1); commit();
            retire(); load_a1(2); peek();
            stage_k(3);
            issue2(a1, 1); commit();
            retire(); load_a0(3); peek();
            fence_async_smem();
            if (wg == 0) bar_sync<1, 128>(); else bar_sync<2, 128>();
            float kv[32];
            issue2(a0, 1);
            {
                const uint32_t dk = dsb + LO128 + (st_base >> 4), ds = st_step >> 4, dv = st_v >> 4;
                #pragma unroll
                for (int ks = 0; ks < 4; ks++) wgmma_ss64_tt<HI128>(kv, dk + ks * ds, dk + ks * ds + dv, ks);
            }
            commit();
            retire(); load_a1(3); peek();
            {
                const float l2e = TOK2 ? after_issue(-kLog2e, zero) : -kLog2e;
                float e0, e1;
                asm("ex2.approx.ftz.f32 %0, %1;" : "=f"(e0) : "f"(g0 * l2e));
                asm("ex2.approx.ftz.f32 %0, %1;" : "=f"(e1) : "f"(g1 * l2e));
                g0 = __fdividef(1.f, 1.f + e0);
                g1 = __fdividef(1.f, 1.f + e1);
                asm volatile("" : "+f"(g0), "+f"(g1));
            }
            issue2(a1, 1); commit();
            retire(); load_a0(4); peek();
            reg_fence(kv);
            if (wg == 0) bar_arrive<5, 256>(); else bar_sync<5, 256>();
            auto stage_kv = [&](int hh) {
                const int d = w4 * 16 + g8 + 8 * hh;
                const bool h0 = d < 28;
                const uint32_t rowa = cb + OFF_STG + wg * 8192 + d * 128 + q4 * 8;
                #pragma unroll
                for (int t = 0; t < 4; t++) {
                    float v0 = h0 ? kv[4 * t + 2 * hh] : kv[4 * t + 12 + 2 * hh];
                    float v1 = h0 ? kv[4 * t + 2 * hh + 1] : kv[4 * t + 13 + 2 * hh];
                    if (t == 0 && !h0 && q4 == 0) v0 = kv[28 + 2 * hh];
                    if (d < 56 && !(t == 3 && h0 && q4 == 2))
                        asm volatile("st.shared.v2.f32 [%0], {%1, %2};" :: "r"(rowa + ((t ^ (g8 & 3)) << 5)), "f"(v0), "f"(v1) : "memory");
                }
                if (h0 && q4 == 0)
                    asm volatile("st.shared.v2.f32 [%0], {%1, %1};" :: "r"(rowa + ((3 ^ (g8 & 3)) << 5) + 16), "f"(kv[28 + 2 * hh]) : "memory");
            };
            stage_kv(0);
            issue2(a0, 1); commit();
            retire(); load_a1(4); peek();
            stage_kv(1);
            __syncwarp();
            if (lane == 0) mbar_arrive(mb + BAR_KVDONE);
            TS(wg, 4);
            issue2(a1, 1); commit();
            retire(); load_a0(5); peek();
            if (PRESCALE) {
                const uint32_t s0 = pack_bf16(1.f - g0, 1.f - g0), s1 = pack_bf16(1.f - g1, 1.f - g1);
                #pragma unroll
                for (int i = 0; i < 32; i++) hp[i] = mul_bf16x2(hp[i], (i & 1) ? s1 : s0);
                reg_fence_part<0, 32>(hp);
            }
            #pragma unroll 1
            for (int it = 5; it < 7; it++) {
                if (it == 6) skew_hold(1);
                issue2(a0, 1); commit();
                retire(); load_a1(it); peek();
                issue2(a1, 1); commit();
                if (it == 6) skew_go(1);
                retire(); load_a0(it < 6 ? it + 1 : 0); peek();
            }
            wg_wait<0>();
            reg_fence(aq); reg_fence(au);
            release(cur);
        }
        const float u0 = 1.f - g0, u1 = 1.f - g1;
        #pragma unroll
        for (int i = 0; i < 32; i++) {
            const float u = (i & 1) ? u1 : u0;
            hp[i] = mul_bf16x2(hp[i], PRESCALE ? pack_bf16(au[2 * i], au[2 * i + 1]) : pack_bf16(au[2 * i] * u, au[2 * i + 1] * u));
        }
        reg_fence_part<0, 32>(hp);
        TS(wg, 5);

        float ag[96], nd[32];
        uint32_t op[16];
        {
            auto issue3 = [&](uint32_t (&a)[8], int sd) {
                const uint32_t b = begin();
                wgmma_rs192<HI64>(ag, a[0], a[1], a[2], a[3], b + LO64, sd);
                wgmma_rs192<HI64>(ag, a[4], a[5], a[6], a[7], b + LO64 + 384, 1);
            };
            uint32_t pq[16];
            issue3(a0, 0); commit();
            load_a1(0); peek();
            auto phi_q = [&](int lo, int hi) {
                const float l2e = after_issue(kLog2e, zero);
                #pragma unroll
                for (int i = 0; i < 14; i++) if (i >= lo && i < hi) pq[i] = pack_bf16(phi(aq[2 * i], l2e), phi(aq[2 * i + 1], l2e));
            };
            pq[14] = 0u; pq[15] = 0u;
            issue3(a1, 1); commit();
            if (QSPLIT) {
                retire(); load_a0(1); peek();
                phi_q(0, 5); reg_fence_part<0, 5>(pq);
                issue3(a0, 1); commit();
                retire(); load_a1(1); peek();
                phi_q(5, 10); reg_fence_part<5, 10>(pq);
                issue3(a1, 1); commit();
                retire(); load_a0(2); peek();
                phi_q(10, 14); reg_fence_part<10, 16>(pq);
            } else {
                phi_q(0, 14); reg_fence(pq);
                retire(); load_a0(1); peek();
            }
            #pragma unroll 1
            for (int it = QSPLIT ? 2 : 1; it < 6; it++) {
                issue3(a0, 1); commit();
                retire(); load_a1(it); peek();
                issue3(a1, 1); commit();
                retire(); load_a0(it + 1); peek();
            }
            skew_hold(2);
            issue3(a0, 1); commit();
            const bool aux = mbar_try(mb + BAR_AUX, 0);
            retire(); load_a1(6); peek();
            if (!aux) mbar_wait(mb + BAR_AUX, 0);
            TS(wg, 7);
            issue3(a1, 1);
            {
                const uint32_t dk = dsb + LO128 + ((OFF_STG + 8192) >> 4);
                #pragma unroll
                for (int ks = 0; ks < 4; ks++) wgmma_rs64<HI128>(nd, pq[4 * ks], pq[4 * ks + 1], pq[4 * ks + 2], pq[4 * ks + 3], dk + ks * 128, ks);
            }
            commit();
            skew_go(2);
            ready = mbar_try(mb + p4_bar(0), p4_par(0));
            retire();
        }
        TS(wg, 6);

        float oa[32], ob[32];
        int c = j == 7 ? 0 : j;
        const int wsh = __shfl_sync(0xffffffffu, warp * 16, 0);
        const uint32_t sh0 = par * 768, sh1 = par * 1024;
        bool ready2 = false;
        auto issue_d = [&](float (&o)[32], int c0, int half) {
            const int n = 3 * c0;
            if (half == 0) {
                STS4(n, 0);
                if (!ready) mbar_wait(mb + p4_bar(n), p4_par(n));
                if (!ready2) mbar_wait(mb + p4_bar(n + 1), p4_par(n + 1));
                STS4(n, 1);
                ready = mbar_try(mb + p4_bar(n + 2), p4_par(n + 2));
            }
            wg_fence();
            const uint32_t b = dsb + LO128 + (p4_off(n) >> 4);
            #pragma unroll
            for (int ks = 7 * half; ks < 7 * half + 7; ks++)
                wgmma_rs64<HI128>(o, hp[4 * ks], hp[4 * ks + 1], hp[4 * ks + 2], hp[4 * ks + 3],
                                  b + ks * 128 + (ks < 8 ? sh0 : 0u - sh1), ks);
        };
        auto issue_o = [&](float (&o)[32], int c0) {
            const int n = 3 * c0 + 2;
            STS4(n, 0);
            if (!ready) mbar_wait(mb + p4_bar(n), p4_par(n));
            STS4(n, 1);
            if (c0 < 6) {
                ready = mbar_try(mb + p4_bar(n + 1), p4_par(n + 1));
                ready2 = mbar_try(mb + p4_bar(n + 2), p4_par(n + 2));
            }
            wg_fence();
            const uint32_t b = dsb + LO128 + (p4_off(n) >> 4);
            #pragma unroll
            for (int ks = 0; ks < 4; ks++) wgmma_rs64<HI128>(o, op[4 * ks], op[4 * ks + 1], op[4 * ks + 2], op[4 * ks + 3], b + ks * 128, 1);
            wg_commit();
        };
        auto ship = [&](float (&o)[32], int c0) {
            reg_fence(o);
            const uint32_t so = xa + OFF_OUT + (c0 & 1) * 16384;
            #pragma unroll
            for (int t = 0; t < 4; t++)
                stsm4(so + (lx ^ (t * 32)), pack_bf16(o[8 * t], o[8 * t + 1]), pack_bf16(o[8 * t + 2], o[8 * t + 3]),
                      pack_bf16(o[8 * t + 4], o[8 * t + 5]), pack_bf16(o[8 * t + 6], o[8 * t + 7]));
            fence_async_smem();
            __syncwarp();
            if (elect_one()) {
                tma_reduce2d(&mp.out, tb + OFF_OUT + (c0 & 1) * 16384 + wsh * 128, 64 * c, row0 + wsh);
                asm volatile("cp.async.bulk.commit_group;" ::: "memory");
            }
            if (++c == 7) c = 0;
            TS(wg, 9 + c0);
        };
        auto finish_h = [&]() {
            reg_fence(ag);
            release(cur);
            #pragma unroll
            for (int i = 0; i < 24; i++) {
                const float u = (i & 1) ? u1 : u0;
                hp[32 + i] = mul_bf16x2(pack_relu_bf16(ag[2 * i], ag[2 * i + 1]), pack_bf16(ag[48 + 2 * i] * u, ag[49 + 2 * i] * u));
            }
            reg_fence_part<32, 56>(hp);
        };
        ready2 = mbar_try(mb + p4_bar(1), p4_par(1));
        wg_wait<0>();
        reg_fence(nd);
        const int src = lane & ~3;
        const float n0 = __shfl_sync(0xffffffffu, nd[28], src), n1 = __shfl_sync(0xffffffffu, nd[29], src);
        const float n2 = __shfl_sync(0xffffffffu, nd[30], src), n3 = __shfl_sync(0xffffffffu, nd[31], src);
        finish_h();
        auto finish_o = [&]() {
            const float gg0 = after_issue(g0, zero), gg1 = after_issue(g1, zero);
            const float s00 = __fdividef(gg0, n0 + 1e-6f), s01 = __fdividef(gg0, n1 + 1e-6f);
            const float s10 = __fdividef(gg1, n2 + 1e-6f), s11 = __fdividef(gg1, n3 + 1e-6f);
            #pragma unroll
            for (int t = 0; t < 7; t++) {
                const bool h1 = t > 3 || (t == 3 && q4 >= 2);
                const float sa = h1 ? s01 : s00, sc = h1 ? s11 : s10;
                op[2 * t] = pack_bf16(nd[4 * t] * sa, nd[4 * t + 1] * sa);
                op[2 * t + 1] = pack_bf16(nd[4 * t + 2] * sc, nd[4 * t + 3] * sc);
            }
            op[14] = 0u; op[15] = 0u;
            reg_fence(op);
            TS(wg, 8);
        };
        #pragma unroll
        for (int c0 = 0; c0 < 7; c0++) {
            float (&o)[32] = (c0 & 1) ? ob : oa;
            if (OASYM && c0 == 0 && wg == 1) finish_o();
            if (c0 > 0 || wg == 1) turn_wait();
            issue_d(o, c0, 0);
            if (!OASYM && c0 == 0) finish_o();
            issue_d(o, c0, 1);
            if (OASYM && c0 == 0 && wg == 0) finish_o();
            issue_o(o, c0);
            if (!(c0 == 6 && wg == 1)) turn_pass();
            if (c0 >= 2) {
                if (elect_one()) asm volatile("cp.async.bulk.wait_group.read 1;" ::: "memory");
                __syncwarp();
            }
            wg_wait<0>();
            if (c0 < 2) { release(3 * c0); release(3 * c0 + 1); release(3 * c0 + 2); }
            ship(o, c0);
        }
        if (elect_one()) asm volatile("cp.async.bulk.wait_group.read 0;" ::: "memory");
        TS(wg, 16); TSG(wg, 17); TSDUMP(wg, 0, 16); STDUMP();
    }
}

typedef CUresult (*EncodeFn)(CUtensorMap*, CUtensorMapDataType, cuuint32_t, void*, const cuuint64_t*, const cuuint64_t*,
                             const cuuint32_t*, const cuuint32_t*, CUtensorMapInterleave, CUtensorMapSwizzle,
                             CUtensorMapL2promotion, CUtensorMapFloatOOBfill);

void make_map(EncodeFn enc, CUtensorMap* m, const void* base, int rank, const cuuint64_t* dims, const cuuint64_t* strides,
              cuuint32_t b0, cuuint32_t b1, cuuint32_t b2, CUtensorMapSwizzle sw, int wide = 0) {
    const cuuint32_t es[3] = {1, 1, 1}, box[3] = {b0, b1, b2};
    enc(m, CU_TENSOR_MAP_DATA_TYPE_BFLOAT16, rank, const_cast<void*>(base), dims, strides, box, es,
        CU_TENSOR_MAP_INTERLEAVE_NONE, sw, wide ? CU_TENSOR_MAP_L2_PROMOTION_L2_256B : CU_TENSOR_MAP_L2_PROMOTION_L2_128B, CU_TENSOR_MAP_FLOAT_OOB_FILL_NONE);
}

}

extern "C" void kernel_launch(void* const* d_in, const int* in_sizes, int n_in, void* d_out, int out_size) {
    (void)in_sizes; (void)n_in; (void)out_size;
    static EncodeFn enc = nullptr;
    if (!enc) {
        void* fn = nullptr;
        cudaDriverEntryPointQueryResult st;
        cudaGetDriverEntryPoint("cuTensorMapEncodeTiled", &fn, cudaEnableDefault, &st);
        enc = (EncodeFn)fn;
        cudaFuncSetAttribute(fused_kernel, cudaFuncAttributeMaxDynamicSharedMemorySize, SMEM_BYTES);
    }
    Maps mp;
    const cuuint64_t dimx[2] = {kD, kS}, dimd[2] = {kD, kF}, dimo[2] = {kD, kD}, strd[1] = {kD * 2};
    make_map(enc, &mp.x, d_in[0], 2, dimx, strd, 64, 128, 1, CU_TENSOR_MAP_SWIZZLE_128B, PROMO & 4);
    make_map(enc, &mp.out, d_out, 2, dimx, strd, 64, 16, 1, CU_TENSOR_MAP_SWIZZLE_128B);
    make_map(enc, &mp.d, d_in[6], 2, dimd, strd, 64, 56, 1, CU_TENSOR_MAP_SWIZZLE_128B, PROMO & 2);
    make_map(enc, &mp.o, d_in[2], 2, dimo, strd, 64, 32, 1, CU_TENSOR_MAP_SWIZZLE_128B, PROMO & 2);
    const cuuint64_t dimq[3] = {kD, kD, 3}, strq[2] = {3 * kD * 2, kD * 2};
    make_map(enc, &mp.kv, d_in[1], 3, dimq, strq, BOX56 ? 56 : 64, 16, 2, CU_TENSOR_MAP_SWIZZLE_128B, PROMO & 8);
    make_map(enc, &mp.q, d_in[1], 3, dimq, strq, BOX56 ? 56 : 64, 16, 1, CU_TENSOR_MAP_SWIZZLE_128B, PROMO & 8);
    const cuuint64_t dimf[3] = {32, kD, kF / 32}, strf[2] = {kF * 2, 64};
    const cuuint64_t dimw[3] = {64, kD, kF / 64}, strw[2] = {kF * 2, 128};
    if (ALIGNG) {
        make_map(enc, &mp.g4, d_in[4], 3, dimw, strw, 64, 16, 2, CU_TENSOR_MAP_SWIZZLE_128B, PROMO & 1);
        make_map(enc, &mp.u4, d_in[5], 3, dimw, strw, 64, 16, 2, CU_TENSOR_MAP_SWIZZLE_128B, PROMO & 1);
    } else {
        make_map(enc, &mp.g4, d_in[4], 3, dimf, strf, 32, 16, 4, CU_TENSOR_MAP_SWIZZLE_64B);
        make_map(enc, &mp.u4, d_in[5], 3, dimf, strf, 32, 16, 4, CU_TENSOR_MAP_SWIZZLE_64B);
    }
    make_map(enc, &mp.g3, d_in[4], 3, dimf, strf, 32, 16, 3, CU_TENSOR_MAP_SWIZZLE_64B, PROMO & 16);
    make_map(enc, &mp.u3, d_in[5], 3, dimf, strf, 32, 16, 3, CU_TENSOR_MAP_SWIZZLE_64B, PROMO & 16);
    fused_kernel<<<NCTA, NTHREADS, SMEM_BYTES>>>(mp, (const __nv_bfloat16*)d_in[7], (__nv_bfloat16*)d_out,
                                                 (const char*)d_in[0], (const char*)d_in[1], (const char*)d_in[4],
                                                 (const char*)d_in[5], (const char*)d_in[6], (const char*)d_in[2], 0u);
}
```

```cpp
#include <cuda_runtime.h>
#include <cuda_bf16.h>
#include <cuda.h>
#include <stdint.h>

namespace {

constexpr int kS = 2048, kD = 448, kF = 1792;
constexpr int NTHREADS = 384;
constexpr int NCTA = 128;
constexpr uint32_t OFF_X = 0;
constexpr uint32_t OFF_RING = 114688;
constexpr uint32_t SLOT_BYTES = 16384;
constexpr int NSLOT = 6;
constexpr uint32_t OFF_STG = 212992;
constexpr uint32_t OFF_MISC = 229376;
constexpr uint32_t SMEM_BYTES = 232448;
constexpr uint32_t BAR_FULL = OFF_MISC, BAR_EMPTY = OFF_MISC + 48, BAR_XFULL = OFF_MISC + 96;
constexpr uint32_t BAR_W = OFF_MISC + 152, BAR_KVDONE = OFF_MISC + 160, BAR_AUX = OFF_MISC + 168, BAR_P4 = OFF_MISC + 176;
constexpr uint32_t OFF_W = OFF_MISC + 256;
constexpr uint32_t SB = 1024;

__device__ __align__(128) float g_kvacc[8][2048];
__device__ unsigned int g_counter[64];

__device__ __forceinline__ void mbar_init(uint32_t bar, uint32_t cnt) {
    asm volatile("mbarrier.init.shared::cta.b64 [%0], %1;" :: "r"(bar), "r"(cnt) : "memory");
}
__device__ __forceinline__ void mbar_expect_tx(uint32_t bar, uint32_t bytes) {
    asm volatile("mbarrier.arrive.expect_tx.shared::cta.b64 _, [%0], %1;" :: "r"(bar), "r"(bytes) : "memory");
}
__device__ __forceinline__ void mbar_arrive(uint32_t bar) {
    asm volatile("mbarrier.arrive.shared::cta.b64 _, [%0];" :: "r"(bar) : "memory");
}
__device__ __forceinline__ void mbar_arrive_cluster(uint32_t bar) {
    asm volatile("mbarrier.arrive.shared::cluster.b64 _, [%0];" :: "r"(bar) : "memory");
}
__device__ __forceinline__ void mbar_wait(uint32_t bar, uint32_t parity) {
    asm volatile("{\n"
                 ".reg .pred p;\n"
                 ".reg .u32 c;\n"
                 "mov.u32 c, 0;\n"
                 "AGAIN:\n"
                 "mbarrier.try_wait.parity.shared::cta.b64 p, [%0], %1;\n"
                 "@p bra DONE;\n"
                 "add.u32 c, c, 1;\n"
                 "setp.lt.u32 p, c, 4194304;\n"
                 "@p bra AGAIN;\n"
                 "trap;\n"
                 "DONE:\n"
                 "}" :: "r"(bar), "r"(parity) : "memory");
}
__device__ __forceinline__ uint32_t mapa(uint32_t addr, uint32_t cta) {
    uint32_t r; asm("mapa.shared::cluster.u32 %0, %1, %2;" : "=r"(r) : "r"(addr), "r"(cta)); return r;
}
__device__ __forceinline__ bool elect_one() {
    uint32_t p;
    asm volatile("{ .reg .pred P; elect.sync _|P, 0xffffffff; selp.u32 %0, 1, 0, P; }" : "=r"(p));
    return p;
}
__device__ __forceinline__ void tma2d(uint32_t dst, const CUtensorMap* m, int c0, int c1, uint32_t bar) {
    asm volatile("cp.async.bulk.tensor.2d.shared::cluster.global.mbarrier::complete_tx::bytes [%0], [%1, {%3, %4}], [%2];"
                 :: "r"(dst), "l"(m), "r"(bar), "r"(c0), "r"(c1) : "memory");
}
__device__ __forceinline__ void tma2d_mc(uint32_t dst, const CUtensorMap* m, int c0, int c1, uint32_t bar) {
    asm volatile("cp.async.bulk.tensor.2d.shared::cluster.global.mbarrier::complete_tx::bytes.multicast::cluster [%0], [%1, {%3, %4}], [%2], %5;"
                 :: "r"(dst), "l"(m), "r"(bar), "r"(c0), "r"(c1), "h"((uint16_t)3) : "memory");
}
__device__ __forceinline__ void tma3d_mc(uint32_t dst, const CUtensorMap* m, int c0, int c1, int c2, uint32_t bar) {
    asm volatile("cp.async.bulk.tensor.3d.shared::cluster.global.mbarrier::complete_tx::bytes.multicast::cluster [%0], [%1, {%3, %4, %5}], [%2], %6;"
                 :: "r"(dst), "l"(m), "r"(bar), "r"(c0), "r"(c1), "r"(c2), "h"((uint16_t)3) : "memory");
}
__device__ __forceinline__ void tma_reduce2d(const CUtensorMap* m, uint32_t src, int c0, int c1) {
    asm volatile("cp.reduce.async.bulk.tensor.2d.global.shared::cta.add.bulk_group [%0, {%2, %3}], [%1];"
                 :: "l"(m), "r"(src), "r"(c0), "r"(c1) : "memory");
}
__device__ __forceinline__ void bulk_reduce_f32(float* dst, uint32_t src, uint32_t bytes) {
    asm volatile("cp.reduce.async.bulk.global.shared::cta.bulk_group.add.f32 [%0], [%1], %2;" :: "l"(dst), "r"(src), "r"(bytes) : "memory");
}
__device__ __forceinline__ bool mbar_try(uint32_t bar, uint32_t parity) {
    uint32_t ok;
    asm volatile("{ .reg .pred p; mbarrier.test_wait.parity.shared::cta.b64 p, [%1], %2; selp.u32 %0, 1, 0, p; }"
                 : "=r"(ok) : "r"(bar), "r"(parity) : "memory");
    return ok;
}
__device__ __forceinline__ void prefetch_map(const CUtensorMap* m) {
    asm volatile("prefetch.tensormap [%0];" :: "l"(m) : "memory");
}
__device__ __forceinline__ void wg_fence() { asm volatile("wgmma.fence.sync.aligned;" ::: "memory"); }
__device__ __forceinline__ void wg_commit() { asm volatile("wgmma.commit_group.sync.aligned;" ::: "memory"); }
template <int N> __device__ __forceinline__ void wg_wait() { asm volatile("wgmma.wait_group.sync.aligned %0;" :: "n"(N) : "memory"); }
template <int N> __device__ __forceinline__ void reg_fence(float (&d)[N]) {
#pragma unroll
    for (int i = 0; i < N; i++) asm volatile("" : "+f"(d[i]) :: "memory");
}
template <int N> __device__ __forceinline__ void reg_fence(uint32_t (&d)[N]) {
#pragma unroll
    for (int i = 0; i < N; i++) asm volatile("" : "+r"(d[i]) :: "memory");
}
template <int LO, int HI, int N> __device__ __forceinline__ void reg_fence_part(uint32_t (&d)[N]) {
#pragma unroll
    for (int i = LO; i < HI; i++) asm volatile("" : "+r"(d[i]) :: "memory");
}
__device__ __forceinline__ void fence_async_smem() { asm volatile("fence.proxy.async.shared::cta;" ::: "memory"); }
template <int ID, int N> __device__ __forceinline__ void bar_sync() { asm volatile("bar.sync %0, %1;" :: "n"(ID), "n"(N) : "memory"); }
template <int ID, int N> __device__ __forceinline__ void bar_arrive() { asm volatile("bar.arrive %0, %1;" :: "n"(ID), "n"(N) : "memory"); }
__device__ __forceinline__ void ldsm4(uint32_t* r, uint32_t addr) {
    asm volatile("ldmatrix.sync.aligned.m8n8.x4.shared.b16 {%0, %1, %2, %3}, [%4];"
                 : "=r"(r[0]), "=r"(r[1]), "=r"(r[2]), "=r"(r[3]) : "r"(addr) : "memory");
}
__device__ __forceinline__ void stsm4(uint32_t addr, uint32_t r0, uint32_t r1, uint32_t r2, uint32_t r3) {
    asm volatile("stmatrix.sync.aligned.m8n8.x4.shared.b16 [%0], {%1, %2, %3, %4};"
                 :: "r"(addr), "r"(r0), "r"(r1), "r"(r2), "r"(r3) : "memory");
}
__device__ __forceinline__ uint32_t lds32(uint32_t addr) {
    uint32_t r; asm volatile("ld.shared.u32 %0, [%1];" : "=r"(r) : "r"(addr)); return r;
}
__device__ __forceinline__ float4 lds128f(uint32_t addr) {
    float4 r; asm volatile("ld.shared.v4.f32 {%0, %1, %2, %3}, [%4];" : "=f"(r.x), "=f"(r.y), "=f"(r.z), "=f"(r.w) : "r"(addr)); return r;
}
__device__ __forceinline__ uint32_t clock32() { uint32_t t; asm volatile("mov.u32 %0, %%clock;" : "=r"(t)); return t; }
__device__ __forceinline__ uint32_t pack_bf16(float lo, float hi) {
    uint32_t r; asm("cvt.rn.bf16x2.f32 %0, %1, %2;" : "=r"(r) : "f"(hi), "f"(lo)); return r;
}
__device__ __forceinline__ uint32_t pack_relu_bf16(float lo, float hi) {
    uint32_t r; asm("cvt.rn.relu.bf16x2.f32 %0, %1, %2;" : "=r"(r) : "f"(hi), "f"(lo)); return r;
}
__device__ __forceinline__ uint32_t mul_bf16x2(uint32_t a, uint32_t b) {
    uint32_t r; asm("mul.rn.bf16x2 %0, %1, %2;" : "=r"(r) : "r"(a), "r"(b)); return r;
}
__device__ __forceinline__ uint32_t fma_bf16x2(uint32_t a, uint32_t b, uint32_t c) {
    uint32_t r; asm("fma.rn.bf16x2 %0, %1, %2, %3;" : "=r"(r) : "r"(a), "r"(b), "r"(c)); return r;
}
__device__ __forceinline__ float phi(float t, float log2e) {
    float e;
    asm("ex2.approx.ftz.f32 %0, %1;" : "=f"(e) : "f"(fminf(t * log2e, 0.f)));
    return e + (fmaxf(t, 0.f) + 1e-6f);
}
__device__ __forceinline__ float after_issue(float v, uint32_t zero) {
    return __uint_as_float(__float_as_uint(v) | (clock32() & zero));
}
constexpr float kLog2e = 1.4426950408889634f;
__device__ __forceinline__ float bf_lo(uint32_t v) { return __uint_as_float(v << 16); }
__device__ __forceinline__ float bf_hi(uint32_t v) { return __uint_as_float(v & 0xffff0000u); }
constexpr uint32_t HI128 = (1024 >> 4) | (1u << 30);
constexpr uint32_t HI64 = (512 >> 4) | (2u << 30);
constexpr uint32_t LO128 = 1u << 16, LO64 = (1024u >> 4) << 16, LO128X2 = (2048u >> 4) << 16;
constexpr uint32_t QB = 16 * 112;
constexpr uint32_t TX1 = 2 * (2 * QB + 4096), TX2 = 2 * (QB + 4096), TX3 = 12288;
__device__ __forceinline__ void grid_arrive(unsigned int* c) {
    asm volatile("fence.acq_rel.gpu;" ::: "memory");
    asm volatile("red.relaxed.gpu.global.add.u32 [%0], 1;" :: "l"(c) : "memory");
}
__device__ __forceinline__ void grid_wait(const unsigned int* c, unsigned int target) {
    unsigned int v; int it = 0;
    do {
        asm volatile("ld.relaxed.gpu.global.u32 %0, [%1];" : "=r"(v) : "l"(c) : "memory");
        if (++it > (1 << 22)) asm volatile("trap;");
    } while ((int)(v - target) < 0);
    asm volatile("ld.acquire.gpu.global.u32 %0, [%1];" : "=r"(v) : "l"(c) : "memory");
}


__host__ __device__ constexpr uint32_t p4_pack(int n) { return (n / 3) * 36864 + (n % 3) * 14336; }
__host__ __device__ constexpr uint32_t p4_off(int n) {
    return n < 6 ? OFF_X + p4_pack(n) : n < 14 ? OFF_RING + p4_pack(n - 6) : n == 14 ? OFF_X + p4_pack(6) : OFF_X + p4_pack(n - 15);
}
__host__ __device__ constexpr uint32_t p4_bar(int n) {
    return n < 6 ? BAR_XFULL + 8 * n : n < 12 ? BAR_FULL + 8 * (n - 6) : n < 14 ? BAR_P4 + 8 * (n - 12)
                 : n == 14 ? BAR_XFULL + 48 : BAR_XFULL + 8 * (n - 15);
}
__host__ __device__ constexpr uint32_t p4_par(int n) { return (n < 12 || n == 14) ? 1 : 0; }
constexpr uint32_t OFF_OUT = OFF_X + 5 * 16384;
static_assert(p4_off(7) == p4_off(6) + 14336 && p4_off(13) == p4_off(12) + 14336 && p4_off(16) == p4_off(15) + 14336, "Wd halves");
static_assert(p4_off(13) + 14336 <= OFF_STG + 8192 && p4_off(14) + 8192 == OFF_OUT, "pass-4 layout");

struct Ring {
    uint32_t slot, phase;
    __device__ __forceinline__ void advance() { if (++slot == NSLOT) { slot = 0; phase ^= 1; } }
};

struct Maps { CUtensorMap x, kv, q, g4, g3, u4, u3, d, o, out; };

__global__ void __cluster_dims__(2, 1, 1) __launch_bounds__(NTHREADS, 1)
fused_kernel(const __grid_constant__ Maps mp, const __nv_bfloat16* __restrict__ gate_w, __nv_bfloat16* __restrict__ out,
             uint32_t zero)
{
    extern __shared__ __align__(1024) unsigned char smem[];
    const uint32_t sb = (uint32_t)__cvta_generic_to_shared(smem);
    const int tid = threadIdx.x, warp = tid >> 5, lane = tid & 31;
    const int rank = blockIdx.x & 1, j = (blockIdx.x >> 1) & 7;
    const int row0 = ((blockIdx.x >> 4) * 2 + rank) * 128;
    const int par = j & 1;
    const int g4i = (7 * j + 3 * par) >> 1;

    if (warp == 8) {
        if (elect_one()) {
            prefetch_map(&mp.kv); prefetch_map(&mp.g4);
            #pragma unroll
            for (int s = 0; s < NSLOT; s++) {
                mbar_init(sb + BAR_FULL + 8 * s, 1);
                mbar_init(sb + BAR_EMPTY + 8 * s, 4);
            }
            asm volatile("fence.mbarrier_init.release.cluster;" ::: "memory");
        }
        __syncwarp();
    } else if (warp == 9) {
        if (elect_one()) {
            prefetch_map(&mp.x);
            mbar_init(sb + BAR_XFULL, 1);
            mbar_init(sb + BAR_W, 1);
            asm volatile("fence.mbarrier_init.release.cluster;" ::: "memory");
            mbar_expect_tx(sb + BAR_XFULL, 16384);
            tma2d(sb + OFF_X, &mp.x, 0, row0, sb + BAR_XFULL);
            mbar_expect_tx(sb + BAR_W, 896);
            asm volatile("cp.async.bulk.shared::cluster.global.mbarrier::complete_tx::bytes [%0], [%1], 896, [%2];"
                         :: "r"(sb + OFF_W), "l"(gate_w), "r"(sb + BAR_W) : "memory");
        }
        __syncwarp();
    } else if (warp == 10) {
        if (elect_one()) {
            #pragma unroll
            for (int s = 1; s < 7; s++) mbar_init(sb + BAR_XFULL + 8 * s, 1);
            mbar_init(sb + BAR_KVDONE, 8);
            mbar_init(sb + BAR_AUX, 3);
            mbar_init(sb + BAR_P4, 1);
            mbar_init(sb + BAR_P4 + 8, 1);
            asm volatile("fence.mbarrier_init.release.cluster;" ::: "memory");
            if ((sb & 0xFFFFFF) != SB) asm volatile("trap;");
        }
        __syncwarp();
    }
    asm volatile("barrier.cluster.arrive.relaxed.aligned;" ::: "memory");
    if (warp == 8) {
        if (elect_one()) mbar_expect_tx(sb + BAR_FULL, TX1);
        __syncwarp();
    }
    asm volatile("barrier.cluster.wait.aligned;" ::: "memory");
    if (warp == 8) {
        if (elect_one()) {
            tma3d_mc(sb + OFF_RING + rank * 8192, &mp.kv, 56 * j, 16 * rank, 1, sb + BAR_FULL);
            tma3d_mc(sb + OFF_RING + rank * 8192 + 4096, &mp.g4, 0, 16 * rank, g4i, sb + BAR_FULL);
        }
        __syncwarp();
    }

    if (warp >= 8) {
        asm volatile("setmaxnreg.dec.sync.aligned.u32 40;");
        if (warp == 8) {
            if (elect_one()) {
                Ring r{1, 1};
                auto acquire = [&](uint32_t bytes) -> uint32_t {
                    mbar_wait(sb + BAR_EMPTY + 8 * r.slot, r.phase);
                    mbar_expect_tx(sb + BAR_FULL + 8 * r.slot, bytes);
                    return sb + OFF_RING + r.slot * SLOT_BYTES;
                };
                #pragma unroll 1
                for (int s = 1; s < 14; s++) {
                    const uint32_t dst = acquire(TX1) + rank * 8192;
                    tma3d_mc(dst, &mp.kv, 56 * j, 32 * s + 16 * rank, 1, sb + BAR_FULL + 8 * r.slot);
                    tma3d_mc(dst + 4096, &mp.g4, 0, 32 * s + 16 * rank, g4i, sb + BAR_FULL + 8 * r.slot);
                    r.advance();
                    if ((s & 1) && s < 12) {
                        const int n = (s >> 1) + 1;
                        mbar_expect_tx(sb + BAR_XFULL + 8 * n, 16384);
                        tma2d(sb + OFF_X + n * 16384, &mp.x, 64 * n, row0, sb + BAR_XFULL + 8 * n);
                    }
                    if (s == 5) {
                        prefetch_map(&mp.q); prefetch_map(&mp.u4); prefetch_map(&mp.g3); prefetch_map(&mp.u3);
                        prefetch_map(&mp.d); prefetch_map(&mp.o); prefetch_map(&mp.out);
                    }
                }
                #pragma unroll 1
                for (int s = 0; s < 14; s++) {
                    const uint32_t dst = acquire(TX2) + rank * 6144;
                    tma3d_mc(dst, &mp.q, 56 * j, 32 * s + 16 * rank, 0, sb + BAR_FULL + 8 * r.slot);
                    tma3d_mc(dst + 2048, &mp.u4, 0, 32 * s + 16 * rank, g4i, sb + BAR_FULL + 8 * r.slot);
                    r.advance();
                }
                const int cfirst = j == 7 ? 0 : j;
                auto load4 = [&](int n) {
                    int c = cfirst + n / 3;
                    if (c >= 7) c -= 7;
                    mbar_expect_tx(sb + p4_bar(n), n % 3 == 2 ? 8192 : 14336);
                    if (n % 3 == 2) tma2d_mc(sb + p4_off(n) + rank * 4096, &mp.o, 64 * c, 56 * j + 32 * rank, sb + p4_bar(n));
                    else tma2d_mc(sb + p4_off(n) + rank * 7168, &mp.d, 64 * c, 224 * j + 112 * (n % 3) + 56 * rank, sb + p4_bar(n));
                };
                #pragma unroll 1
                for (int s = 0; s < 14; s++) {
                    const uint32_t dst = acquire(TX3) + rank * 6144;
                    tma3d_mc(dst, &mp.g3, 0, 32 * s + 16 * rank, 7 * j + 4 - 4 * par, sb + BAR_FULL + 8 * r.slot);
                    tma3d_mc(dst + 3072, &mp.u3, 0, 32 * s + 16 * rank, 7 * j + 4 - 4 * par, sb + BAR_FULL + 8 * r.slot);
                    r.advance();
                    if (s == 7) load4(0);
                    if (s == 9) load4(1);
                    if (s == 11) load4(2);
                    if (s == 13) { load4(3); load4(4); }
                }
                mbar_wait(sb + BAR_EMPTY, 0);      load4(6);
                mbar_wait(sb + BAR_EMPTY + 8, 0);  load4(5); load4(7); load4(14);
                mbar_wait(sb + BAR_EMPTY + 16, 0); load4(8);
                mbar_wait(sb + BAR_EMPTY + 24, 0); load4(9); load4(10);
                mbar_wait(sb + BAR_EMPTY + 32, 0); load4(11);
                mbar_wait(sb + BAR_EMPTY + 40, 0); load4(12);
                mbar_wait(sb + BAR_AUX, 0);        load4(13);
                #pragma unroll
                for (int n = 15; n < 21; n++) {
                    mbar_wait(sb + BAR_EMPTY + 8 * (n - 15), 1);
                    __nanosleep(100);
                    load4(n);
                }
            }
        } else {
            const int ht = tid - 288;
            unsigned int cnt0;
            asm volatile("ld.relaxed.gpu.global.u32 %0, [%1];" : "=r"(cnt0) : "l"(&g_counter[32]) : "memory");
            const unsigned int target = ((cnt0 >> 7) + 1) << 7;
            if (warp == 9) {
                reinterpret_cast<float4*>(&g_kvacc[0][0])[blockIdx.x * 32 + lane] = make_float4(0.f, 0.f, 0.f, 0.f);
                asm volatile("fence.proxy.async.global;" ::: "memory");
                __syncwarp();
                if (lane == 0) grid_arrive(&g_counter[0]);
                mbar_wait(sb + BAR_XFULL + 8 * 6, 0);
                uint4* o = reinterpret_cast<uint4*>(out) + blockIdx.x * 896 + lane;
                #pragma unroll 4
                for (int q = 0; q < 28; q++) o[q * 32] = make_uint4(0, 0, 0, 0);
                asm volatile("fence.proxy.async.global;" ::: "memory");
                __syncwarp();
                if (lane == 0) {
                    asm volatile("fence.acq_rel.gpu;" ::: "memory");
                    grid_wait(&g_counter[0], target);
                }
                __syncwarp();
            }
            mbar_wait(sb + BAR_KVDONE, 0);
            {
                #pragma unroll
                for (int i0 = 0; i0 < 5; i0 += 3) {
                    float4 pa[3], pb[3];
                    #pragma unroll
                    for (int i = 0; i < 3 && i0 + i < 5; i++) {
                        const int q = min(ht + 96 * (i0 + i), 447);
                        pa[i] = lds128f(sb + OFF_STG + q * 16); pb[i] = lds128f(sb + OFF_STG + 8192 + q * 16);
                    }
                    #pragma unroll
                    for (int i = 0; i < 3 && i0 + i < 5; i++) {
                        const int q = ht + 96 * (i0 + i);
                        if (q < 448) asm volatile("st.shared.v4.f32 [%0], {%1, %2, %3, %4};" :: "r"(sb + OFF_STG + q * 16),
                            "f"(pa[i].x + pb[i].x), "f"(pa[i].y + pb[i].y), "f"(pa[i].z + pb[i].z), "f"(pa[i].w + pb[i].w) : "memory");
                    }
                }
                fence_async_smem();
            }
            bar_sync<3, 96>();
            if (warp == 9) {
                if (elect_one()) {
                    bulk_reduce_f32(&g_kvacc[j][0], sb + OFF_STG, 7168);
                    asm volatile("cp.async.bulk.commit_group;" ::: "memory");
                    asm volatile("cp.async.bulk.wait_group 0;" ::: "memory");
                    asm volatile("red.relaxed.gpu.global.add.u32 [%0], 1;" :: "l"(&g_counter[32]) : "memory");
                }
            }
            __syncwarp();
            #pragma unroll
            for (int i = 0; i < 3; i++) {
                const int q = ht + 96 * i;
                const int d = q < 168 ? q / 3 : 56 + ((q - 168) >> 3);
                const int c = q < 168 ? (q - 3 * d + (d < 28 ? 4 : 0)) : (q & 7);
                if (q < 232) asm volatile("st.shared.v4.u32 [%0], {%1, %1, %1, %1};" :: "r"(sb + OFF_STG + 8192 + d * 128 + ((c ^ (d & 7)) << 4)), "r"(0) : "memory");
            }
            if (lane == 0) grid_wait(&g_counter[32], target);
            __syncwarp();
            const float4* src = reinterpret_cast<const float4*>(&g_kvacc[j][0]);
            float4 va[3], vb[3];
            #pragma unroll
            for (int i = 0; i < 3; i++) {
                const int q = ht + 96 * i, d = q / 5, m = q - 5 * d;
                const int pc = m < 4 ? m : (d < 28 ? 3 : 0);
                if (q < 280) { va[i] = __ldcg(src + d * 8 + 2 * (pc ^ (d & 3))); vb[i] = __ldcg(src + d * 8 + 2 * (pc ^ (d & 3)) + 1); }
            }
            #pragma unroll
            for (int i = 0; i < 3; i++) {
                const int q = ht + 96 * i, d = q / 5, m = q - 5 * d;
                const bool h0 = d < 28;
                const int c = m == 4 ? 7 : (h0 ? m : m + 3);
                uint32_t w0 = pack_bf16(va[i].x, va[i].y), w1 = pack_bf16(va[i].z, va[i].w);
                uint32_t w2 = pack_bf16(vb[i].x, vb[i].y), w3 = pack_bf16(vb[i].z, vb[i].w);
                if (m == 4) { w0 = h0 ? (w2 & 0xffffu) : (w0 << 16); w1 = w2 = w3 = 0u; }
                else if (c == 3) { if (h0) w2 = w3 = 0u; else w0 = w1 = 0u; }
                if (q < 280)
                    asm volatile("st.shared.v4.u32 [%0], {%1, %2, %3, %4};"
                                 :: "r"(sb + OFF_STG + 8192 + d * 128 + ((c ^ (d & 7)) << 4)), "r"(w0), "r"(w1), "r"(w2), "r"(w3) : "memory");
            }
            fence_async_smem();
            __syncwarp();
            if (lane == 0) mbar_arrive(sb + BAR_AUX);
        }
    } else {
        asm volatile("setmaxnreg.inc.sync.aligned.u32 232;");
        const int wg = warp >> 2, w4 = warp & 3;
        const int q4 = lane & 3, g8 = lane >> 2;
        const uint32_t lx = ((lane >> 4) ^ (lane & 7)) << 4;
        const uint32_t xa = sb + OFF_X + (warp * 16 + (lane & 15)) * 128;
        const uint32_t empty_dst = mapa(sb + BAR_EMPTY, w4 & 1);
        const bool signaller = lane == 0 && w4 < 2;
        constexpr uint32_t dsb = SB >> 4;
        Ring r{0, 0};
        uint32_t cur = 0, old = 0;
        bool ready = false;
        auto release = [&](uint32_t slot) { if (signaller) mbar_arrive_cluster(empty_dst + 8 * slot); };
        auto turn_wait = [&]() { if (wg == 0) bar_sync<6, 256>(); else bar_sync<7, 256>(); };
        auto turn_pass = [&]() { if (wg == 0) bar_arrive<7, 256>(); else bar_arrive<6, 256>(); };
        auto begin = [&]() -> uint32_t {
            if (!ready) mbar_wait(sb + BAR_FULL + 8 * r.slot, r.phase);
            wg_fence();
            return dsb + (OFF_RING >> 4) + r.slot * (SLOT_BYTES >> 4);
        };
        auto commit = [&]() { wg_commit(); old = cur; cur = r.slot; r.advance(); };
        auto retire = [&]() { wg_wait<1>(); release(old); };
        auto peek = [&]() { ready = mbar_try(sb + BAR_FULL + 8 * r.slot, r.phase); };
        uint32_t a0[8], a1[8];
        auto load_a0 = [&](int kc) { ldsm4(a0, xa + kc * 16384 + lx); ldsm4(a0 + 4, xa + kc * 16384 + (lx ^ 32)); };
        auto load_a1 = [&](int kc) { ldsm4(a1, xa + kc * 16384 + (lx ^ 64)); ldsm4(a1 + 4, xa + kc * 16384 + (lx ^ 96)); };

        uint32_t hp[56];
        float g0, g1, ak[28], av[28];
        {
            float ag[64];
            float d0 = 0.f, d1 = 0.f, d2 = 0.f, d3 = 0.f;
            uint32_t w0[4], w1[4];
            auto issue1 = [&](uint32_t (&a)[8], int sd) {
                const uint32_t b = begin();
                wgmma_rs56<HI128>(ak, a[0], a[1], a[2], a[3], b + LO128, sd);
                wgmma_rs56<HI128>(av, a[0], a[1], a[2], a[3], b + LO128 + 128, sd);
                wgmma_rs128<HI128>(ag, a[0], a[1], a[2], a[3], b + LO128X2 + 256, sd);
                wgmma_rs56<HI128>(ak, a[4], a[5], a[6], a[7], b + LO128 + 512, 1);
                wgmma_rs56<HI128>(av, a[4], a[5], a[6], a[7], b + LO128 + 640, 1);
                wgmma_rs128<HI128>(ag, a[4], a[5], a[6], a[7], b + LO128X2 + 768, 1);
                commit();
            };
            auto issue1s = [&](uint32_t (&a)[8]) {
                const uint32_t b = begin();
                wgmma_rs128<HI128>(ag, a[0], a[1], a[2], a[3], b + LO128X2 + 256, 1);
                wgmma_rs128<HI128>(ag, a[4], a[5], a[6], a[7], b + LO128X2 + 768, 1);
                wg_commit();
                wgmma_rs56<HI128>(ak, a[0], a[1], a[2], a[3], b + LO128, 1);
                wgmma_rs56<HI128>(av, a[0], a[1], a[2], a[3], b + LO128 + 128, 1);
                wgmma_rs56<HI128>(ak, a[4], a[5], a[6], a[7], b + LO128 + 512, 1);
                wgmma_rs56<HI128>(av, a[4], a[5], a[6], a[7], b + LO128 + 640, 1);
                commit();
            };
            auto load_w = [&](uint32_t (&w)[4], int s) {
                #pragma unroll
                for (int e = 0; e < 4; e++) w[e] = lds32(sb + OFF_W + s * 64 + q4 * 4 + e * 16);
            };
            auto dot = [&](uint32_t (&a)[8], uint32_t (&w)[4]) {
                uint32_t p0 = mul_bf16x2(a[0], w[0]), p1 = mul_bf16x2(a[1], w[0]);
                #pragma unroll
                for (int e = 1; e < 4; e++) { p0 = fma_bf16x2(a[2 * e], w[e], p0); p1 = fma_bf16x2(a[2 * e + 1], w[e], p1); }
                d0 += bf_lo(p0); d2 += bf_hi(p0); d1 += bf_lo(p1); d3 += bf_hi(p1);
                asm volatile("" : "+f"(d0), "+f"(d1), "+f"(d2), "+f"(d3));
            };
            mbar_wait(sb + BAR_XFULL, 0);
            load_a0(0);
            mbar_wait(sb + BAR_W, 0);
            load_w(w0, 0);
            auto odd_stage = [&](int it, bool first, bool last) {
                wg_wait<1>();
                if (!first) release(old);
                load_a1(it);
                load_w(w1, 2 * it + 1);
                peek();
                dot(a0, w0);
                if (last && wg == 1) bar_sync<4, 256>();
                issue1s(a1);
                if (last && wg == 0) bar_arrive<4, 256>();
            };
            issue1(a0, 0);
            #pragma unroll
            for (int it = 0; it < 6; it++) {
                const bool xok = mbar_try(sb + BAR_XFULL + 8 * (it + 1), 0);
                odd_stage(it, it == 0, false);
                wg_wait<2>(); release(old);
                if (!xok) mbar_wait(sb + BAR_XFULL + 8 * (it + 1), 0);
                load_a0(it + 1);
                load_w(w0, 2 * it + 2);
                peek();
                dot(a1, w1);
                issue1(a0, 1);
            }
            odd_stage(6, false, true);
            wg_wait<2>(); release(old);
            load_a0(0);
            peek();
            dot(a1, w1);
            wg_wait<1>();
            reg_fence(ag);
            #pragma unroll
            for (int i = 0; i < 32; i++) hp[i] = pack_relu_bf16(ag[2 * i], ag[2 * i + 1]);
            reg_fence_part<0, 32>(hp);
            g0 = d0 + d2; g1 = d1 + d3;
        }

        float aq[28], au[64];
        {
            auto issue2 = [&](uint32_t (&a)[8], int sd) {
                const uint32_t b = begin();
                wgmma_rs56<HI128>(aq, a[0], a[1], a[2], a[3], b + LO128, sd);
                wgmma_rs128<HI128>(au, a[0], a[1], a[2], a[3], b + LO128X2 + 128, sd);
                wgmma_rs56<HI128>(aq, a[4], a[5], a[6], a[7], b + LO128 + 384, 1);
                wgmma_rs128<HI128>(au, a[4], a[5], a[6], a[7], b + LO128X2 + 512, 1);
            };
            const uint32_t st_base = wg == 0 ? OFF_STG : OFF_RING + 12288, st_step = wg == 0 ? 2048 : SLOT_BYTES, st_v = wg == 0 ? 8192 : 2048;
            const uint32_t sk = sb + st_base + w4 * st_step + (lane & 15) * 128;
            auto stage_k = [&](int t) {
                const float l2e = after_issue(kLog2e, zero);
                uint32_t p[4];
                #pragma unroll
                for (int e = 0; e < 4; e++)
                    p[e] = 4 * t + e < 14 ? pack_bf16(phi(ak[8 * t + 2 * e], l2e), phi(ak[8 * t + 2 * e + 1], l2e)) : 0u;
                stsm4(sk + (lx ^ (t * 32)), p[0], p[1], p[2], p[3]);
            };
            issue2(a0, 0); commit();
            retire();
            reg_fence(ak); reg_fence(av);
            if (wg == 0) bar_arrive<8, 256>();
            load_a1(0); peek();
            uint32_t pv[14];
            #pragma unroll
            for (int i = 0; i < 14; i++) pv[i] = pack_bf16(av[2 * i], av[2 * i + 1]);
            if (wg == 1) bar_sync<8, 256>();
            {
                const uint32_t ones = q4 == 0 ? 0x3f803f80u : 0u;
                #pragma unroll
                for (int t = 0; t < 3; t++) stsm4(sk + st_v + (lx ^ (t * 32)), pv[4 * t], pv[4 * t + 1], pv[4 * t + 2], pv[4 * t + 3]);
                stsm4(sk + st_v + (lx ^ 96), pv[12], pv[13], ones, ones);
            }
            issue2(a1, 1); commit();
            retire(); load_a0(1); peek();
            stage_k(0);
            issue2(a0, 1); commit();
            retire(); load_a1(1); peek();
            stage_k(1);
            issue2(a1, 1); commit();
            retire(); load_a0(2); peek();
            stage_k(2);
            issue2(a0, 1); commit();
            retire(); load_a1(2); peek();
            stage_k(3);
            issue2(a1, 1); commit();
            retire(); load_a0(3); peek();
            g0 += __shfl_xor_sync(0xffffffffu, g0, 1); g1 += __shfl_xor_sync(0xffffffffu, g1, 1);
            fence_async_smem();
            g0 += __shfl_xor_sync(0xffffffffu, g0, 2); g1 += __shfl_xor_sync(0xffffffffu, g1, 2);
            if (wg == 0) bar_sync<1, 128>(); else bar_sync<2, 128>();
            float kv[32];
            issue2(a0, 1);
            {
                const uint32_t dk = dsb + LO128 + (st_base >> 4), ds = st_step >> 4, dv = st_v >> 4;
                #pragma unroll
                for (int ks = 0; ks < 4; ks++) wgmma_ss64_tt<HI128>(kv, dk + ks * ds, dk + ks * ds + dv, ks);
            }
            commit();
            retire(); load_a1(3); peek();
            {
                const float l2e = after_issue(-kLog2e, zero);
                float e0, e1;
                asm("ex2.approx.ftz.f32 %0, %1;" : "=f"(e0) : "f"(g0 * l2e));
                asm("ex2.approx.ftz.f32 %0, %1;" : "=f"(e1) : "f"(g1 * l2e));
                g0 = __fdividef(1.f, 1.f + e0);
                g1 = __fdividef(1.f, 1.f + e1);
                asm volatile("" : "+f"(g0), "+f"(g1));
            }
            issue2(a1, 1); commit();
            retire(); load_a0(4); peek();
            reg_fence(kv);
            if (wg == 0) { bar_arrive<5, 256>(); bar_sync<1, 128>(); } else bar_sync<5, 256>();
            auto stage_kv = [&](int hh) {
                const int d = w4 * 16 + g8 + 8 * hh;
                const bool h0 = d < 28;
                const uint32_t rowa = sb + OFF_STG + wg * 8192 + d * 128 + q4 * 8;
                #pragma unroll
                for (int t = 0; t < 4; t++) {
                    float v0 = h0 ? kv[4 * t + 2 * hh] : kv[4 * t + 12 + 2 * hh];
                    float v1 = h0 ? kv[4 * t + 2 * hh + 1] : kv[4 * t + 13 + 2 * hh];
                    if (t == 0 && !h0 && q4 == 0) v0 = kv[28 + 2 * hh];
                    if (d < 56 && !(t == 3 && h0 && q4 == 2))
                        asm volatile("st.shared.v2.f32 [%0], {%1, %2};" :: "r"(rowa + ((t ^ (g8 & 3)) << 5)), "f"(v0), "f"(v1) : "memory");
                }
                if (h0 && q4 == 0)
                    asm volatile("st.shared.v2.f32 [%0], {%1, %1};" :: "r"(rowa + ((3 ^ (g8 & 3)) << 5) + 16), "f"(kv[28 + 2 * hh]) : "memory");
            };
            stage_kv(0);
            issue2(a0, 1); commit();
            retire(); load_a1(4); peek();
            stage_kv(1);
            __syncwarp();
            if (lane == 0) mbar_arrive(sb + BAR_KVDONE);
            issue2(a1, 1); commit();
            retire(); load_a0(5); peek();
            {
                const uint32_t s0 = pack_bf16(1.f - g0, 1.f - g0), s1 = pack_bf16(1.f - g1, 1.f - g1);
                #pragma unroll
                for (int i = 0; i < 32; i++) hp[i] = mul_bf16x2(hp[i], (i & 1) ? s1 : s0);
                reg_fence_part<0, 32>(hp);
            }
            issue2(a0, 1); commit();
            retire(); load_a1(5); peek();
            issue2(a1, 1); commit();
            retire(); load_a0(6); peek();
            issue2(a0, 1); commit();
            retire(); load_a1(6); peek();
            if (wg == 1) bar_sync<4, 256>();
            const uint32_t b = begin();
            wgmma_rs128<HI128>(au, a1[0], a1[1], a1[2], a1[3], b + LO128X2 + 128, 1);
            wgmma_rs128<HI128>(au, a1[4], a1[5], a1[6], a1[7], b + LO128X2 + 512, 1);
            wg_commit();
            wgmma_rs56<HI128>(aq, a1[0], a1[1], a1[2], a1[3], b + LO128, 1);
            wgmma_rs56<HI128>(aq, a1[4], a1[5], a1[6], a1[7], b + LO128 + 384, 1);
            commit();
            if (wg == 0) bar_arrive<4, 256>();
            wg_wait<2>(); release(old);
            load_a0(0); peek();
            wg_wait<1>();
            reg_fence(au);
        }
        #pragma unroll
        for (int i = 0; i < 32; i++) hp[i] = mul_bf16x2(hp[i], pack_bf16(au[2 * i], au[2 * i + 1]));
        reg_fence_part<0, 32>(hp);

        float ag[96];
        uint32_t op[16];
        {
            auto issue3 = [&](uint32_t (&a)[8], int sd) {
                const uint32_t b = begin();
                wgmma_rs192<HI64>(ag, a[0], a[1], a[2], a[3], b + LO64, sd);
                wgmma_rs192<HI64>(ag, a[4], a[5], a[6], a[7], b + LO64 + 384, 1);
            };
            uint32_t pq[16];
            issue3(a0, 0); commit();
            retire();
            reg_fence(aq);
            load_a1(0); peek();
            auto phi_q = [&](int lo, int hi) {
                const float l2e = after_issue(kLog2e, zero);
                #pragma unroll
                for (int i = 0; i < 14; i++) if (i >= lo && i < hi) pq[i] = pack_bf16(phi(aq[2 * i], l2e), phi(aq[2 * i + 1], l2e));
            };
            pq[14] = 0u; pq[15] = 0u;
            issue3(a1, 1); commit();
            retire(); load_a0(1); peek();
            phi_q(0, 5); reg_fence_part<0, 5>(pq);
            issue3(a0, 1); commit();
            retire(); load_a1(1); peek();
            phi_q(5, 10); reg_fence_part<5, 10>(pq);
            issue3(a1, 1); commit();
            retire(); load_a0(2); peek();
            phi_q(10, 14); reg_fence_part<10, 16>(pq);
            issue3(a0, 1); commit();
            #pragma unroll
            for (int it = 2; it < 5; it++) {
                retire(); load_a1(it); peek();
                issue3(a1, 1); commit();
                retire(); load_a0(it + 1); peek();
                issue3(a0, 1); commit();
            }
            retire(); load_a1(5); peek();
            issue3(a1, 1); commit();
            const bool aux = mbar_try(sb + BAR_AUX, 0);
            retire(); load_a0(6); peek();
            if (!aux) mbar_wait(sb + BAR_AUX, 0);
            if (wg == 1) bar_sync<4, 256>();
            float nd[32];
            issue3(a0, 1);
            {
                const uint32_t dk = dsb + LO128 + ((OFF_STG + 8192) >> 4);
                #pragma unroll
                for (int ks = 0; ks < 4; ks++) wgmma_rs64<HI128>(nd, pq[4 * ks], pq[4 * ks + 1], pq[4 * ks + 2], pq[4 * ks + 3], dk + ks * 128, ks);
            }
            commit();
            retire(); load_a1(6); peek();
            issue3(a1, 1); commit();
            if (wg == 0) bar_arrive<4, 256>();
            ready = mbar_try(sb + p4_bar(0), p4_par(0));
            retire();
            reg_fence(nd);
            const int src = lane & ~3;
            const float s00 = __fdividef(g0, __shfl_sync(0xffffffffu, nd[28], src) + 1e-6f);
            const float s01 = __fdividef(g0, __shfl_sync(0xffffffffu, nd[29], src) + 1e-6f);
            const float s10 = __fdividef(g1, __shfl_sync(0xffffffffu, nd[30], src) + 1e-6f);
            const float s11 = __fdividef(g1, __shfl_sync(0xffffffffu, nd[31], src) + 1e-6f);
            #pragma unroll
            for (int t = 0; t < 7; t++) {
                const bool h1 = t > 3 || (t == 3 && q4 >= 2);
                const float sa = h1 ? s01 : s00, sc = h1 ? s11 : s10;
                op[2 * t] = pack_bf16(nd[4 * t] * sa, nd[4 * t + 1] * sa);
                op[2 * t + 1] = pack_bf16(nd[4 * t + 2] * sc, nd[4 * t + 3] * sc);
            }
            op[14] = 0u; op[15] = 0u;
            reg_fence(op);
        }

        float oa[32], ob[32];
        int c = j == 7 ? 0 : j;
        const int wsh = __shfl_sync(0xffffffffu, warp * 16, 0);
        const uint32_t sh0 = par * 768, sh1 = par * 1024;
        bool ready2 = false;
        auto issue_d = [&](float (&o)[32], int c0, int half) {
            const int n = 3 * c0;
            if (half == 0) {
                if (!ready) mbar_wait(sb + p4_bar(n), p4_par(n));
                if (!ready2) mbar_wait(sb + p4_bar(n + 1), p4_par(n + 1));
                ready = mbar_try(sb + p4_bar(n + 2), p4_par(n + 2));
            }
            wg_fence();
            const uint32_t b = dsb + LO128 + (p4_off(n) >> 4);
            #pragma unroll
            for (int ks = 7 * half; ks < 7 * half + 7; ks++)
                wgmma_rs64<HI128>(o, hp[4 * ks], hp[4 * ks + 1], hp[4 * ks + 2], hp[4 * ks + 3],
                                  b + ks * 128 + (ks < 8 ? sh0 : 0u - sh1), ks);
        };
        auto issue_o = [&](float (&o)[32], int c0) {
            const int n = 3 * c0 + 2;
            if (!ready) mbar_wait(sb + p4_bar(n), p4_par(n));
            if (c0 < 6) {
                ready = mbar_try(sb + p4_bar(n + 1), p4_par(n + 1));
                ready2 = mbar_try(sb + p4_bar(n + 2), p4_par(n + 2));
            }
            wg_fence();
            const uint32_t b = dsb + LO128 + (p4_off(n) >> 4);
            #pragma unroll
            for (int ks = 0; ks < 4; ks++) wgmma_rs64<HI128>(o, op[4 * ks], op[4 * ks + 1], op[4 * ks + 2], op[4 * ks + 3], b + ks * 128, 1);
            wg_commit();
        };
        auto ship = [&](float (&o)[32], int c0) {
            reg_fence(o);
            const uint32_t so = xa + OFF_OUT + (c0 & 1) * 16384;
            #pragma unroll
            for (int t = 0; t < 4; t++)
                stsm4(so + (lx ^ (t * 32)), pack_bf16(o[8 * t], o[8 * t + 1]), pack_bf16(o[8 * t + 2], o[8 * t + 3]),
                      pack_bf16(o[8 * t + 4], o[8 * t + 5]), pack_bf16(o[8 * t + 6], o[8 * t + 7]));
            fence_async_smem();
            __syncwarp();
            if (elect_one()) {
                tma_reduce2d(&mp.out, sb + OFF_OUT + (c0 & 1) * 16384 + wsh * 128, 64 * c, row0 + wsh);
                asm volatile("cp.async.bulk.commit_group;" ::: "memory");
            }
            if (++c == 7) c = 0;
        };
        auto finish_h = [&]() {
            reg_fence(ag);
            release(cur);
            const float u0 = 1.f - g0, u1 = 1.f - g1;
            #pragma unroll
            for (int i = 0; i < 24; i++) {
                const float u = (i & 1) ? u1 : u0;
                hp[32 + i] = mul_bf16x2(pack_relu_bf16(ag[2 * i], ag[2 * i + 1]), pack_bf16(ag[48 + 2 * i] * u, ag[49 + 2 * i] * u));
            }
            reg_fence_part<32, 56>(hp);
        };
        ready2 = mbar_try(sb + p4_bar(1), p4_par(1));
        wg_wait<0>();
        finish_h();
        #pragma unroll
        for (int c0 = 0; c0 < 7; c0++) {
            float (&o)[32] = (c0 & 1) ? ob : oa;
            if (c0 > 0 || wg == 1) turn_wait();
            issue_d(o, c0, 0);
            issue_d(o, c0, 1);
            issue_o(o, c0);
            if (!(c0 == 6 && wg == 1)) turn_pass();
            if (c0 >= 2) {
                if (elect_one()) asm volatile("cp.async.bulk.wait_group.read 1;" ::: "memory");
                __syncwarp();
            }
            wg_wait<0>();
            if (c0 < 2) { release(3 * c0); release(3 * c0 + 1); release(3 * c0 + 2); }
            ship(o, c0);
        }
        if (elect_one()) asm volatile("cp.async.bulk.wait_group.read 0;" ::: "memory");
    }
}

typedef CUresult (*EncodeFn)(CUtensorMap*, CUtensorMapDataType, cuuint32_t, void*, const cuuint64_t*, const cuuint64_t*,
                             const cuuint32_t*, const cuuint32_t*, CUtensorMapInterleave, CUtensorMapSwizzle,
                             CUtensorMapL2promotion, CUtensorMapFloatOOBfill);

void make_map(EncodeFn enc, CUtensorMap* m, const void* base, int rank, const cuuint64_t* dims, const cuuint64_t* strides,
              cuuint32_t b0, cuuint32_t b1, cuuint32_t b2, CUtensorMapSwizzle sw) {
    const cuuint32_t es[3] = {1, 1, 1}, box[3] = {b0, b1, b2};
    enc(m, CU_TENSOR_MAP_DATA_TYPE_BFLOAT16, rank, const_cast<void*>(base), dims, strides, box, es,
        CU_TENSOR_MAP_INTERLEAVE_NONE, sw, CU_TENSOR_MAP_L2_PROMOTION_L2_128B, CU_TENSOR_MAP_FLOAT_OOB_FILL_NONE);
}

}

extern "C" void kernel_launch(void* const* d_in, const int* in_sizes, int n_in, void* d_out, int out_size) {
    (void)in_sizes; (void)n_in; (void)out_size;
    static EncodeFn enc = nullptr;
    if (!enc) {
        void* fn = nullptr;
        cudaDriverEntryPointQueryResult st;
        cudaGetDriverEntryPoint("cuTensorMapEncodeTiled", &fn, cudaEnableDefault, &st);
        enc = (EncodeFn)fn;
        cudaFuncSetAttribute(fused_kernel, cudaFuncAttributeMaxDynamicSharedMemorySize, SMEM_BYTES);
    }
    Maps mp;
    const cuuint64_t dimx[2] = {kD, kS}, dimd[2] = {kD, kF}, dimo[2] = {kD, kD}, strd[1] = {kD * 2};
    make_map(enc, &mp.x, d_in[0], 2, dimx, strd, 64, 128, 1, CU_TENSOR_MAP_SWIZZLE_128B);
    make_map(enc, &mp.out, d_out, 2, dimx, strd, 64, 16, 1, CU_TENSOR_MAP_SWIZZLE_128B);
    make_map(enc, &mp.d, d_in[6], 2, dimd, strd, 64, 56, 1, CU_TENSOR_MAP_SWIZZLE_128B);
    make_map(enc, &mp.o, d_in[2], 2, dimo, strd, 64, 32, 1, CU_TENSOR_MAP_SWIZZLE_128B);
    const cuuint64_t dimq[3] = {kD, kD, 3}, strq[2] = {3 * kD * 2, kD * 2};
    make_map(enc, &mp.kv, d_in[1], 3, dimq, strq, 56, 16, 2, CU_TENSOR_MAP_SWIZZLE_128B);
    make_map(enc, &mp.q, d_in[1], 3, dimq, strq, 56, 16, 1, CU_TENSOR_MAP_SWIZZLE_128B);
    const cuuint64_t dimf[3] = {32, kD, kF / 32}, strf[2] = {kF * 2, 64};
    const cuuint64_t dimw[3] = {64, kD, kF / 64}, strw[2] = {kF * 2, 128};
    make_map(enc, &mp.g4, d_in[4], 3, dimw, strw, 64, 16, 2, CU_TENSOR_MAP_SWIZZLE_128B);
    make_map(enc, &mp.u4, d_in[5], 3, dimw, strw, 64, 16, 2, CU_TENSOR_MAP_SWIZZLE_128B);
    make_map(enc, &mp.g3, d_in[4], 3, dimf, strf, 32, 16, 3, CU_TENSOR_MAP_SWIZZLE_64B);
    make_map(enc, &mp.u3, d_in[5], 3, dimf, strf, 32, 16, 3, CU_TENSOR_MAP_SWIZZLE_64B);
    fused_kernel<<<NCTA, NTHREADS, SMEM_BYTES>>>(mp, (const __nv_bfloat16*)d_in[7], (__nv_bfloat16*)d_out, 0u);
}
```

```cpp
#include <cuda_runtime.h>
#include <cuda_bf16.h>
#include <cuda.h>
#include <stdint.h>

namespace {

constexpr int kS = 2048, kD = 448, kF = 1792;
constexpr int NTHREADS = 384;
constexpr int NCTA = 128;
constexpr uint32_t OFF_X = 0;
constexpr uint32_t OFF_RING = 114688;
constexpr uint32_t SLOT_BYTES = 16384;
constexpr int NSLOT = 6;
constexpr uint32_t OFF_STG = 212992;
constexpr uint32_t OFF_MISC = 229376;
constexpr uint32_t SMEM_BYTES = 232448;
constexpr uint32_t BAR_FULL = OFF_MISC, BAR_EMPTY = OFF_MISC + 48, BAR_XFULL = OFF_MISC + 96;
constexpr uint32_t BAR_W = OFF_MISC + 152, BAR_KVDONE = OFF_MISC + 160, BAR_AUX = OFF_MISC + 168, BAR_P4 = OFF_MISC + 176;
constexpr uint32_t OFF_W = OFF_MISC + 256;
constexpr uint32_t SB = 1024;

__device__ __align__(128) float g_kvacc[8][2048];
__device__ unsigned int g_counter[64];

__device__ __forceinline__ void mbar_init(uint32_t bar, uint32_t cnt) {
    asm volatile("mbarrier.init.shared::cta.b64 [%0], %1;" :: "r"(bar), "r"(cnt) : "memory");
}
__device__ __forceinline__ void mbar_expect_tx(uint32_t bar, uint32_t bytes) {
    asm volatile("mbarrier.arrive.expect_tx.shared::cta.b64 _, [%0], %1;" :: "r"(bar), "r"(bytes) : "memory");
}
__device__ __forceinline__ void mbar_arrive(uint32_t bar) {
    asm volatile("mbarrier.arrive.shared::cta.b64 _, [%0];" :: "r"(bar) : "memory");
}
__device__ __forceinline__ void mbar_arrive_cluster(uint32_t bar) {
    asm volatile("mbarrier.arrive.shared::cluster.b64 _, [%0];" :: "r"(bar) : "memory");
}
__device__ __forceinline__ void mbar_wait(uint32_t bar, uint32_t parity) {
    asm volatile("{\n"
                 ".reg .pred p;\n"
                 ".reg .u32 c;\n"
                 "mov.u32 c, 0;\n"
                 "AGAIN:\n"
                 "mbarrier.try_wait.parity.shared::cta.b64 p, [%0], %1;\n"
                 "@p bra DONE;\n"
                 "add.u32 c, c, 1;\n"
                 "setp.lt.u32 p, c, 4194304;\n"
                 "@p bra AGAIN;\n"
                 "trap;\n"
                 "DONE:\n"
                 "}" :: "r"(bar), "r"(parity) : "memory");
}
__device__ __forceinline__ uint32_t mapa(uint32_t addr, uint32_t cta) {
    uint32_t r; asm("mapa.shared::cluster.u32 %0, %1, %2;" : "=r"(r) : "r"(addr), "r"(cta)); return r;
}
__device__ __forceinline__ bool elect_one() {
    uint32_t p;
    asm volatile("{ .reg .pred P; elect.sync _|P, 0xffffffff; selp.u32 %0, 1, 0, P; }" : "=r"(p));
    return p;
}
__device__ __forceinline__ void tma2d(uint32_t dst, const CUtensorMap* m, int c0, int c1, uint32_t bar) {
    asm volatile("cp.async.bulk.tensor.2d.shared::cluster.global.mbarrier::complete_tx::bytes [%0], [%1, {%3, %4}], [%2];"
                 :: "r"(dst), "l"(m), "r"(bar), "r"(c0), "r"(c1) : "memory");
}
__device__ __forceinline__ void tma2d_mc(uint32_t dst, const CUtensorMap* m, int c0, int c1, uint32_t bar) {
    asm volatile("cp.async.bulk.tensor.2d.shared::cluster.global.mbarrier::complete_tx::bytes.multicast::cluster [%0], [%1, {%3, %4}], [%2], %5;"
                 :: "r"(dst), "l"(m), "r"(bar), "r"(c0), "r"(c1), "h"((uint16_t)3) : "memory");
}
__device__ __forceinline__ void tma3d_mc(uint32_t dst, const CUtensorMap* m, int c0, int c1, int c2, uint32_t bar) {
    asm volatile("cp.async.bulk.tensor.3d.shared::cluster.global.mbarrier::complete_tx::bytes.multicast::cluster [%0], [%1, {%3, %4, %5}], [%2], %6;"
                 :: "r"(dst), "l"(m), "r"(bar), "r"(c0), "r"(c1), "r"(c2), "h"((uint16_t)3) : "memory");
}
__device__ __forceinline__ void tma_reduce2d(const CUtensorMap* m, uint32_t src, int c0, int c1) {
    asm volatile("cp.reduce.async.bulk.tensor.2d.global.shared::cta.add.bulk_group [%0, {%2, %3}], [%1];"
                 :: "l"(m), "r"(src), "r"(c0), "r"(c1) : "memory");
}
__device__ __forceinline__ void bulk_reduce_f32(float* dst, uint32_t src, uint32_t bytes) {
    asm volatile("cp.reduce.async.bulk.global.shared::cta.bulk_group.add.f32 [%0], [%1], %2;" :: "l"(dst), "r"(src), "r"(bytes) : "memory");
}
__device__ __forceinline__ bool mbar_try(uint32_t bar, uint32_t parity) {
    uint32_t ok;
    asm volatile("{ .reg .pred p; mbarrier.test_wait.parity.shared::cta.b64 p, [%1], %2; selp.u32 %0, 1, 0, p; }"
                 : "=r"(ok) : "r"(bar), "r"(parity) : "memory");
    return ok;
}
__device__ __forceinline__ void prefetch_map(const CUtensorMap* m) {
    asm volatile("prefetch.tensormap [%0];" :: "l"(m) : "memory");
}
__device__ __forceinline__ void wg_fence() { asm volatile("wgmma.fence.sync.aligned;" ::: "memory"); }
__device__ __forceinline__ void wg_commit() { asm volatile("wgmma.commit_group.sync.aligned;" ::: "memory"); }
template <int N> __device__ __forceinline__ void wg_wait() { asm volatile("wgmma.wait_group.sync.aligned %0;" :: "n"(N) : "memory"); }
template <int N> __device__ __forceinline__ void reg_fence(float (&d)[N]) {
#pragma unroll
    for (int i = 0; i < N; i++) asm volatile("" : "+f"(d[i]) :: "memory");
}
template <int N> __device__ __forceinline__ void reg_fence(uint32_t (&d)[N]) {
#pragma unroll
    for (int i = 0; i < N; i++) asm volatile("" : "+r"(d[i]) :: "memory");
}
template <int LO, int HI, int N> __device__ __forceinline__ void reg_fence_part(uint32_t (&d)[N]) {
#pragma unroll
    for (int i = LO; i < HI; i++) asm volatile("" : "+r"(d[i]) :: "memory");
}
__device__ __forceinline__ void fence_async_smem() { asm volatile("fence.proxy.async.shared::cta;" ::: "memory"); }
template <int ID, int N> __device__ __forceinline__ void bar_sync() { asm volatile("bar.sync %0, %1;" :: "n"(ID), "n"(N) : "memory"); }
template <int ID, int N> __device__ __forceinline__ void bar_arrive() { asm volatile("bar.arrive %0, %1;" :: "n"(ID), "n"(N) : "memory"); }
__device__ __forceinline__ void ldsm4(uint32_t* r, uint32_t addr) {
    asm volatile("ldmatrix.sync.aligned.m8n8.x4.shared.b16 {%0, %1, %2, %3}, [%4];"
                 : "=r"(r[0]), "=r"(r[1]), "=r"(r[2]), "=r"(r[3]) : "r"(addr) : "memory");
}
__device__ __forceinline__ void stsm4(uint32_t addr, uint32_t r0, uint32_t r1, uint32_t r2, uint32_t r3) {
    asm volatile("stmatrix.sync.aligned.m8n8.x4.shared.b16 [%0], {%1, %2, %3, %4};"
                 :: "r"(addr), "r"(r0), "r"(r1), "r"(r2), "r"(r3) : "memory");
}
__device__ __forceinline__ uint32_t lds32(uint32_t addr) {
    uint32_t r; asm volatile("ld.shared.u32 %0, [%1];" : "=r"(r) : "r"(addr)); return r;
}
__device__ __forceinline__ float4 lds128f(uint32_t addr) {
    float4 r; asm volatile("ld.shared.v4.f32 {%0, %1, %2, %3}, [%4];" : "=f"(r.x), "=f"(r.y), "=f"(r.z), "=f"(r.w) : "r"(addr)); return r;
}
__device__ __forceinline__ uint32_t clock32() { uint32_t t; asm volatile("mov.u32 %0, %%clock;" : "=r"(t)); return t; }
__device__ __forceinline__ uint32_t pack_bf16(float lo, float hi) {
    uint32_t r; asm("cvt.rn.bf16x2.f32 %0, %1, %2;" : "=r"(r) : "f"(hi), "f"(lo)); return r;
}
__device__ __forceinline__ uint32_t pack_relu_bf16(float lo, float hi) {
    uint32_t r; asm("cvt.rn.relu.bf16x2.f32 %0, %1, %2;" : "=r"(r) : "f"(hi), "f"(lo)); return r;
}
__device__ __forceinline__ uint32_t mul_bf16x2(uint32_t a, uint32_t b) {
    uint32_t r; asm("mul.rn.bf16x2 %0, %1, %2;" : "=r"(r) : "r"(a), "r"(b)); return r;
}
__device__ __forceinline__ uint32_t fma_bf16x2(uint32_t a, uint32_t b, uint32_t c) {
    uint32_t r; asm("fma.rn.bf16x2 %0, %1, %2, %3;" : "=r"(r) : "r"(a), "r"(b), "r"(c)); return r;
}
__device__ __forceinline__ float phi(float t, float log2e) {
    float e;
    asm("ex2.approx.ftz.f32 %0, %1;" : "=f"(e) : "f"(fminf(t * log2e, 0.f)));
    return e + (fmaxf(t, 0.f) + 1e-6f);
}
__device__ __forceinline__ float after_issue(float v, uint32_t zero) {
    return __uint_as_float(__float_as_uint(v) | (clock32() & zero));
}
constexpr float kLog2e = 1.4426950408889634f;
__device__ __forceinline__ float bf_lo(uint32_t v) { return __uint_as_float(v << 16); }
__device__ __forceinline__ float bf_hi(uint32_t v) { return __uint_as_float(v & 0xffff0000u); }
constexpr uint32_t HI128 = (1024 >> 4) | (1u << 30);
constexpr uint32_t HI64 = (512 >> 4) | (2u << 30);
constexpr uint32_t LO128 = 1u << 16, LO64 = (1024u >> 4) << 16, LO128X2 = (2048u >> 4) << 16;
constexpr uint32_t QB = 16 * 112;
constexpr uint32_t TX1 = 2 * (2 * QB + 4096), TX2 = 2 * (QB + 4096), TX3 = 12288;
__device__ __forceinline__ void grid_arrive(unsigned int* c) {
    asm volatile("fence.acq_rel.gpu;" ::: "memory");
    asm volatile("red.relaxed.gpu.global.add.u32 [%0], 1;" :: "l"(c) : "memory");
}
__device__ __forceinline__ void grid_wait(const unsigned int* c, unsigned int target) {
    unsigned int v; int it = 0;
    do {
        asm volatile("ld.relaxed.gpu.global.u32 %0, [%1];" : "=r"(v) : "l"(c) : "memory");
        if (++it > (1 << 22)) asm volatile("trap;");
    } while ((int)(v - target) < 0);
    asm volatile("ld.acquire.gpu.global.u32 %0, [%1];" : "=r"(v) : "l"(c) : "memory");
}


__host__ __device__ constexpr uint32_t p4_pack(int n) { return (n / 3) * 36864 + (n % 3) * 14336; }
__host__ __device__ constexpr uint32_t p4_off(int n) {
    return n < 6 ? OFF_X + p4_pack(n) : n < 14 ? OFF_RING + p4_pack(n - 6) : n == 14 ? OFF_X + p4_pack(6) : OFF_X + p4_pack(n - 15);
}
__host__ __device__ constexpr uint32_t p4_bar(int n) {
    return n < 6 ? BAR_XFULL + 8 * n : n < 12 ? BAR_FULL + 8 * (n - 6) : n < 14 ? BAR_P4 + 8 * (n - 12)
                 : n == 14 ? BAR_XFULL + 48 : BAR_XFULL + 8 * (n - 15);
}
__host__ __device__ constexpr uint32_t p4_par(int n) { return (n < 12 || n == 14) ? 1 : 0; }
constexpr uint32_t OFF_OUT = OFF_X + 5 * 16384;
static_assert(p4_off(7) == p4_off(6) + 14336 && p4_off(13) == p4_off(12) + 14336 && p4_off(16) == p4_off(15) + 14336, "Wd halves");
static_assert(p4_off(13) + 14336 <= OFF_STG + 8192 && p4_off(14) + 8192 == OFF_OUT, "pass-4 layout");

struct Ring {
    uint32_t slot, phase;
    __device__ __forceinline__ void advance() { if (++slot == NSLOT) { slot = 0; phase ^= 1; } }
};

struct Maps { CUtensorMap x, kv, q, g4, g3, u4, u3, d, o, out; };

__global__ void __cluster_dims__(2, 1, 1) __launch_bounds__(NTHREADS, 1)
fused_kernel(const __grid_constant__ Maps mp, const __nv_bfloat16* __restrict__ gate_w, __nv_bfloat16* __restrict__ out,
             uint32_t zero)
{
    extern __shared__ __align__(1024) unsigned char smem[];
    const uint32_t sb = (uint32_t)__cvta_generic_to_shared(smem);
    const int tid = threadIdx.x, warp = tid >> 5, lane = tid & 31;
    const int rank = blockIdx.x & 1, j = (blockIdx.x >> 1) & 7;
    const int row0 = ((blockIdx.x >> 4) * 2 + rank) * 128;
    const int par = j & 1;
    const int g4i = (7 * j + 3 * par) >> 1;

    if (warp == 9) {
        if (elect_one()) {
            prefetch_map(&mp.x);
            mbar_init(sb + BAR_XFULL, 1);
            mbar_expect_tx(sb + BAR_XFULL, 16384);
            tma2d(sb + OFF_X, &mp.x, 0, row0, sb + BAR_XFULL);
            asm volatile("fence.mbarrier_init.release.cluster;" ::: "memory");
        }
        __syncwarp();
    } else if (warp == 8) {
        if (elect_one()) {
            #pragma unroll
            for (int s = 0; s < NSLOT; s++) mbar_init(sb + BAR_FULL + 8 * s, 1);
            asm volatile("fence.mbarrier_init.release.cluster;" ::: "memory");
            mbar_expect_tx(sb + BAR_FULL, TX1);
        }
        __syncwarp();
    } else if (warp == 10) {
        if (elect_one()) {
            #pragma unroll
            for (int s = 1; s < 7; s++) mbar_init(sb + BAR_XFULL + 8 * s, 1);
            mbar_init(sb + BAR_KVDONE, 8);
            mbar_init(sb + BAR_AUX, 3);
            asm volatile("fence.mbarrier_init.release.cluster;" ::: "memory");
            if ((sb & 0xFFFFFF) != SB) asm volatile("trap;");
        }
        __syncwarp();
    } else if (warp == 11) {
        if (elect_one()) {
            #pragma unroll
            for (int s = 0; s < NSLOT; s++) mbar_init(sb + BAR_EMPTY + 8 * s, 4);
            mbar_init(sb + BAR_P4, 1);
            mbar_init(sb + BAR_P4 + 8, 1);
            asm volatile("fence.mbarrier_init.release.cluster;" ::: "memory");
        }
        __syncwarp();
    } else if (warp == 2) {
        if (elect_one()) {
            mbar_init(sb + BAR_W, 1);
            asm volatile("fence.mbarrier_init.release.cluster;" ::: "memory");
            mbar_expect_tx(sb + BAR_W, 896);
            asm volatile("cp.async.bulk.shared::cluster.global.mbarrier::complete_tx::bytes [%0], [%1], 896, [%2];"
                         :: "r"(sb + OFF_W), "l"(gate_w), "r"(sb + BAR_W) : "memory");
        }
        __syncwarp();
    }
    asm volatile("barrier.cluster.arrive.relaxed.aligned;" ::: "memory");
    if (warp == 8) {
        if (elect_one()) { prefetch_map(&mp.kv); prefetch_map(&mp.g4); }
        __syncwarp();
    }
    asm volatile("barrier.cluster.wait.aligned;" ::: "memory");
    if (warp == 8) {
        if (elect_one()) {
            tma3d_mc(sb + OFF_RING + rank * 8192, &mp.kv, 56 * j, 16 * rank, 1, sb + BAR_FULL);
            tma3d_mc(sb + OFF_RING + rank * 8192 + 4096, &mp.g4, 0, 16 * rank, g4i, sb + BAR_FULL);
        }
        __syncwarp();
    }

    if (warp >= 8) {
        asm volatile("setmaxnreg.dec.sync.aligned.u32 40;");
        if (warp == 8) {
            if (elect_one()) {
                Ring r{1, 1};
                auto acquire = [&](uint32_t bytes) -> uint32_t {
                    mbar_wait(sb + BAR_EMPTY + 8 * r.slot, r.phase);
                    mbar_expect_tx(sb + BAR_FULL + 8 * r.slot, bytes);
                    return sb + OFF_RING + r.slot * SLOT_BYTES;
                };
                #pragma unroll 1
                for (int s = 1; s < 14; s++) {
                    const uint32_t dst = acquire(TX1) + rank * 8192;
                    tma3d_mc(dst, &mp.kv, 56 * j, 32 * s + 16 * rank, 1, sb + BAR_FULL + 8 * r.slot);
                    tma3d_mc(dst + 4096, &mp.g4, 0, 32 * s + 16 * rank, g4i, sb + BAR_FULL + 8 * r.slot);
                    r.advance();
                    if ((s & 1) && s < 12) {
                        const int n = (s >> 1) + 1;
                        mbar_expect_tx(sb + BAR_XFULL + 8 * n, 16384);
                        tma2d(sb + OFF_X + n * 16384, &mp.x, 64 * n, row0, sb + BAR_XFULL + 8 * n);
                    }
                    if (s == 5) {
                        prefetch_map(&mp.q); prefetch_map(&mp.u4); prefetch_map(&mp.g3); prefetch_map(&mp.u3);
                        prefetch_map(&mp.d); prefetch_map(&mp.o); prefetch_map(&mp.out);
                    }
                }
                #pragma unroll 1
                for (int s = 0; s < 14; s++) {
                    const uint32_t dst = acquire(TX2) + rank * 6144;
                    tma3d_mc(dst, &mp.q, 56 * j, 32 * s + 16 * rank, 0, sb + BAR_FULL + 8 * r.slot);
                    tma3d_mc(dst + 2048, &mp.u4, 0, 32 * s + 16 * rank, g4i, sb + BAR_FULL + 8 * r.slot);
                    r.advance();
                }
                const int cfirst = j == 7 ? 0 : j;
                auto load4 = [&](int n) {
                    int c = cfirst + n / 3;
                    if (c >= 7) c -= 7;
                    mbar_expect_tx(sb + p4_bar(n), n % 3 == 2 ? 8192 : 14336);
                    if (n % 3 == 2) tma2d_mc(sb + p4_off(n) + rank * 4096, &mp.o, 64 * c, 56 * j + 32 * rank, sb + p4_bar(n));
                    else tma2d_mc(sb + p4_off(n) + rank * 7168, &mp.d, 64 * c, 224 * j + 112 * (n % 3) + 56 * rank, sb + p4_bar(n));
                };
                #pragma unroll 1
                for (int s = 0; s < 14; s++) {
                    const uint32_t dst = acquire(TX3) + rank * 6144;
                    tma3d_mc(dst, &mp.g3, 0, 32 * s + 16 * rank, 7 * j + 4 - 4 * par, sb + BAR_FULL + 8 * r.slot);
                    tma3d_mc(dst + 3072, &mp.u3, 0, 32 * s + 16 * rank, 7 * j + 4 - 4 * par, sb + BAR_FULL + 8 * r.slot);
                    r.advance();
                    if (s == 7) load4(0);
                    if (s == 9) load4(1);
                    if (s == 11) load4(2);
                    if (s == 13) { load4(3); load4(4); }
                }
                mbar_wait(sb + BAR_EMPTY, 0);      load4(6);
                mbar_wait(sb + BAR_EMPTY + 8, 0);  load4(5); load4(7); load4(14);
                mbar_wait(sb + BAR_EMPTY + 16, 0); load4(8);
                mbar_wait(sb + BAR_EMPTY + 24, 0); load4(9); load4(10);
                mbar_wait(sb + BAR_EMPTY + 32, 0); load4(11);
                mbar_wait(sb + BAR_EMPTY + 40, 0); load4(12);
                mbar_wait(sb + BAR_AUX, 0);        load4(13);
                #pragma unroll
                for (int n = 15; n < 21; n++) {
                    mbar_wait(sb + BAR_EMPTY + 8 * (n - 15), 1);
                    __nanosleep(100);
                    load4(n);
                }
            }
        } else {
            const int ht = tid - 288;
            unsigned int cnt0;
            asm volatile("ld.relaxed.gpu.global.u32 %0, [%1];" : "=r"(cnt0) : "l"(&g_counter[32]) : "memory");
            const unsigned int target = ((cnt0 >> 7) + 1) << 7;
            if (warp == 9) {
                reinterpret_cast<float4*>(&g_kvacc[0][0])[blockIdx.x * 32 + lane] = make_float4(0.f, 0.f, 0.f, 0.f);
                asm volatile("fence.proxy.async.global;" ::: "memory");
                __syncwarp();
                if (lane == 0) grid_arrive(&g_counter[0]);
                mbar_wait(sb + BAR_XFULL + 8 * 6, 0);
                uint4* o = reinterpret_cast<uint4*>(out) + blockIdx.x * 896 + lane;
                #pragma unroll 4
                for (int q = 0; q < 28; q++) o[q * 32] = make_uint4(0, 0, 0, 0);
                asm volatile("fence.proxy.async.global;" ::: "memory");
                __syncwarp();
                if (lane == 0) {
                    asm volatile("fence.acq_rel.gpu;" ::: "memory");
                    grid_wait(&g_counter[0], target);
                }
                __syncwarp();
            }
            mbar_wait(sb + BAR_KVDONE, 0);
            {
                #pragma unroll
                for (int i0 = 0; i0 < 5; i0 += 2) {
                    float4 pa[2], pb[2];
                    #pragma unroll
                    for (int i = 0; i < 2 && i0 + i < 5; i++) {
                        const int q = min(ht + 96 * (i0 + i), 447);
                        pa[i] = lds128f(sb + OFF_STG + q * 16); pb[i] = lds128f(sb + OFF_STG + 8192 + q * 16);
                    }
                    #pragma unroll
                    for (int i = 0; i < 2 && i0 + i < 5; i++) {
                        const int q = ht + 96 * (i0 + i);
                        if (q < 448) asm volatile("st.shared.v4.f32 [%0], {%1, %2, %3, %4};" :: "r"(sb + OFF_STG + q * 16),
                            "f"(pa[i].x + pb[i].x), "f"(pa[i].y + pb[i].y), "f"(pa[i].z + pb[i].z), "f"(pa[i].w + pb[i].w) : "memory");
                    }
                }
                fence_async_smem();
            }
            bar_sync<3, 96>();
            if (warp == 9) {
                if (elect_one()) {
                    bulk_reduce_f32(&g_kvacc[j][0], sb + OFF_STG, 7168);
                    asm volatile("cp.async.bulk.commit_group;" ::: "memory");
                    asm volatile("cp.async.bulk.wait_group 0;" ::: "memory");
                    asm volatile("red.relaxed.gpu.global.add.u32 [%0], 1;" :: "l"(&g_counter[32]) : "memory");
                }
            }
            __syncwarp();
            #pragma unroll
            for (int i = 0; i < 3; i++) {
                const int q = ht + 96 * i;
                const int d = q < 168 ? q / 3 : 56 + ((q - 168) >> 3);
                const int c = q < 168 ? (q - 3 * d + (d < 28 ? 4 : 0)) : (q & 7);
                if (q < 232) asm volatile("st.shared.v4.u32 [%0], {%1, %1, %1, %1};" :: "r"(sb + OFF_STG + 8192 + d * 128 + ((c ^ (d & 7)) << 4)), "r"(0) : "memory");
            }
            uint32_t plan[3];
            #pragma unroll
            for (int i = 0; i < 3; i++) {
                const int q = min(ht + 96 * i, 279), d = q / 5, m = q - 5 * d;
                const bool h0 = d < 28;
                const int c = m == 4 ? 7 : (h0 ? m : m + 3), pc = m < 4 ? m : (h0 ? 3 : 0);
                const int kind = m == 4 ? (h0 ? 3 : 4) : c == 3 ? (h0 ? 1 : 2) : 0;
                plan[i] = (d * 128 + ((c ^ (d & 7)) << 4)) | ((d * 4 + (pc ^ (d & 3))) << 13) | (kind << 23);
                asm volatile("" : "+r"(plan[i]));
            }
            if (lane == 0) grid_wait(&g_counter[32], target);
            __syncwarp();
            const float4* src = reinterpret_cast<const float4*>(&g_kvacc[j][0]);
            float4 va[3], vb[3];
            #pragma unroll
            for (int i = 0; i < 3; i++) {
                const float4* p = src + ((plan[i] >> 12) & 0x7fe);
                va[i] = __ldcg(p); vb[i] = __ldcg(p + 1);
            }
            #pragma unroll
            for (int i = 0; i < 3; i++) {
                const uint32_t kind = plan[i] >> 23;
                uint32_t w0 = pack_bf16(va[i].x, va[i].y), w1 = pack_bf16(va[i].z, va[i].w);
                uint32_t w2 = pack_bf16(vb[i].x, vb[i].y), w3 = pack_bf16(vb[i].z, vb[i].w);
                if (kind == 3) w0 = w2 & 0xffffu;
                if (kind == 4) w0 <<= 16;
                if (kind == 2) w0 = 0u;
                if (kind >= 2) w1 = 0u;
                if (kind != 0 && kind != 2) w2 = w3 = 0u;
                if (i < 2 || ht < 88)
                    asm volatile("st.shared.v4.u32 [%0], {%1, %2, %3, %4};"
                                 :: "r"(sb + OFF_STG + 8192 + (plan[i] & 0x1fff)), "r"(w0), "r"(w1), "r"(w2), "r"(w3) : "memory");
            }
            fence_async_smem();
            __syncwarp();
            if (lane == 0) mbar_arrive(sb + BAR_AUX);
        }
    } else {
        asm volatile("setmaxnreg.inc.sync.aligned.u32 232;");
        const int wg = warp >> 2, w4 = warp & 3;
        const int q4 = lane & 3, g8 = lane >> 2;
        const uint32_t lx = ((lane >> 4) ^ (lane & 7)) << 4;
        const uint32_t xa = sb + OFF_X + (warp * 16 + (lane & 15)) * 128;
        const uint32_t empty_dst = mapa(sb + BAR_EMPTY, w4 & 1);
        const bool signaller = lane == 0 && w4 < 2;
        constexpr uint32_t dsb = SB >> 4;
        Ring r{0, 0};
        uint32_t cur = 0, old = 0;
        bool ready = false;
        auto release = [&](uint32_t slot) { if (signaller) mbar_arrive_cluster(empty_dst + 8 * slot); };
        auto turn_wait = [&]() { if (wg == 0) bar_sync<6, 256>(); else bar_sync<7, 256>(); };
        auto turn_pass = [&]() { if (wg == 0) bar_arrive<7, 256>(); else bar_arrive<6, 256>(); };
        auto begin = [&]() -> uint32_t {
            if (!ready) mbar_wait(sb + BAR_FULL + 8 * r.slot, r.phase);
            wg_fence();
            return dsb + (OFF_RING >> 4) + r.slot * (SLOT_BYTES >> 4);
        };
        auto commit = [&]() { wg_commit(); old = cur; cur = r.slot; r.advance(); };
        auto retire = [&]() { wg_wait<1>(); release(old); };
        auto peek = [&]() { ready = mbar_try(sb + BAR_FULL + 8 * r.slot, r.phase); };
        uint32_t a0[8], a1[8];
        auto load_a0 = [&](int kc) { ldsm4(a0, xa + kc * 16384 + lx); ldsm4(a0 + 4, xa + kc * 16384 + (lx ^ 32)); };
        auto load_a1 = [&](int kc) { ldsm4(a1, xa + kc * 16384 + (lx ^ 64)); ldsm4(a1 + 4, xa + kc * 16384 + (lx ^ 96)); };

        uint32_t hp[56];
        float g0, g1, ak[28], av[28];
        {
            float ag[64];
            float d0 = 0.f, d1 = 0.f, d2 = 0.f, d3 = 0.f;
            uint32_t w0[4], w1[4];
            auto issue1 = [&](uint32_t (&a)[8], int sd) {
                const uint32_t b = begin();
                wgmma_rs56<HI128>(ak, a[0], a[1], a[2], a[3], b + LO128, sd);
                wgmma_rs56<HI128>(av, a[0], a[1], a[2], a[3], b + LO128 + 128, sd);
                wgmma_rs128<HI128>(ag, a[0], a[1], a[2], a[3], b + LO128X2 + 256, sd);
                wgmma_rs56<HI128>(ak, a[4], a[5], a[6], a[7], b + LO128 + 512, 1);
                wgmma_rs56<HI128>(av, a[4], a[5], a[6], a[7], b + LO128 + 640, 1);
                wgmma_rs128<HI128>(ag, a[4], a[5], a[6], a[7], b + LO128X2 + 768, 1);
                commit();
            };
            auto issue1s = [&](uint32_t (&a)[8]) {
                const uint32_t b = begin();
                wgmma_rs128<HI128>(ag, a[0], a[1], a[2], a[3], b + LO128X2 + 256, 1);
                wgmma_rs128<HI128>(ag, a[4], a[5], a[6], a[7], b + LO128X2 + 768, 1);
                wg_commit();
                wgmma_rs56<HI128>(ak, a[0], a[1], a[2], a[3], b + LO128, 1);
                wgmma_rs56<HI128>(av, a[0], a[1], a[2], a[3], b + LO128 + 128, 1);
                wgmma_rs56<HI128>(ak, a[4], a[5], a[6], a[7], b + LO128 + 512, 1);
                wgmma_rs56<HI128>(av, a[4], a[5], a[6], a[7], b + LO128 + 640, 1);
                commit();
            };
            auto load_w = [&](uint32_t (&w)[4], int s) {
                #pragma unroll
                for (int e = 0; e < 4; e++) w[e] = lds32(sb + OFF_W + s * 64 + q4 * 4 + e * 16);
            };
            auto dot = [&](uint32_t (&a)[8], uint32_t (&w)[4]) {
                uint32_t p0 = mul_bf16x2(a[0], w[0]), p1 = mul_bf16x2(a[1], w[0]);
                #pragma unroll
                for (int e = 1; e < 4; e++) { p0 = fma_bf16x2(a[2 * e], w[e], p0); p1 = fma_bf16x2(a[2 * e + 1], w[e], p1); }
                d0 += bf_lo(p0); d2 += bf_hi(p0); d1 += bf_lo(p1); d3 += bf_hi(p1);
                asm volatile("" : "+f"(d0), "+f"(d1), "+f"(d2), "+f"(d3));
            };
            mbar_wait(sb + BAR_XFULL, 0);
            load_a0(0);
            mbar_wait(sb + BAR_W, 0);
            load_w(w0, 0);
            auto odd_stage = [&](int it, bool first, bool last) {
                wg_wait<1>();
                if (!first) release(old);
                load_a1(it);
                load_w(w1, 2 * it + 1);
                peek();
                dot(a0, w0);
                if (last && wg == 1) bar_sync<4, 256>();
                issue1s(a1);
                if (last && wg == 0) bar_arrive<4, 256>();
            };
            issue1(a0, 0);
            #pragma unroll
            for (int it = 0; it < 6; it++) {
                const bool xok = mbar_try(sb + BAR_XFULL + 8 * (it + 1), 0);
                odd_stage(it, it == 0, false);
                wg_wait<2>(); release(old);
                if (!xok) mbar_wait(sb + BAR_XFULL + 8 * (it + 1), 0);
                load_a0(it + 1);
                load_w(w0, 2 * it + 2);
                peek();
                dot(a1, w1);
                issue1(a0, 1);
            }
            odd_stage(6, false, true);
            wg_wait<2>(); release(old);
            load_a0(0);
            peek();
            dot(a1, w1);
            wg_wait<1>();
            reg_fence(ag);
            #pragma unroll
            for (int i = 0; i < 32; i++) hp[i] = pack_relu_bf16(ag[2 * i], ag[2 * i + 1]);
            reg_fence_part<0, 32>(hp);
            g0 = d0 + d2; g1 = d1 + d3;
        }

        float aq[28], au[64];
        {
            auto issue2 = [&](uint32_t (&a)[8], int sd) {
                const uint32_t b = begin();
                wgmma_rs56<HI128>(aq, a[0], a[1], a[2], a[3], b + LO128, sd);
                wgmma_rs128<HI128>(au, a[0], a[1], a[2], a[3], b + LO128X2 + 128, sd);
                wgmma_rs56<HI128>(aq, a[4], a[5], a[6], a[7], b + LO128 + 384, 1);
                wgmma_rs128<HI128>(au, a[4], a[5], a[6], a[7], b + LO128X2 + 512, 1);
            };
            const uint32_t st_base = wg == 0 ? OFF_STG : OFF_RING + 12288, st_step = wg == 0 ? 2048 : SLOT_BYTES, st_v = wg == 0 ? 8192 : 2048;
            const uint32_t sk = sb + st_base + w4 * st_step + (lane & 15) * 128;
            auto stage_k = [&](int t) {
                const float l2e = after_issue(kLog2e, zero);
                uint32_t p[4];
                #pragma unroll
                for (int e = 0; e < 4; e++)
                    p[e] = 4 * t + e < 14 ? pack_bf16(phi(ak[8 * t + 2 * e], l2e), phi(ak[8 * t + 2 * e + 1], l2e)) : 0u;
                stsm4(sk + (lx ^ (t * 32)), p[0], p[1], p[2], p[3]);
            };
            issue2(a0, 0); commit();
            retire();
            reg_fence(ak); reg_fence(av);
            if (wg == 0) bar_arrive<8, 256>();
            load_a1(0); peek();
            uint32_t pv[14];
            #pragma unroll
            for (int i = 0; i < 14; i++) pv[i] = pack_bf16(av[2 * i], av[2 * i + 1]);
            if (wg == 1) bar_sync<8, 256>();
            {
                const uint32_t ones = q4 == 0 ? 0x3f803f80u : 0u;
                #pragma unroll
                for (int t = 0; t < 3; t++) stsm4(sk + st_v + (lx ^ (t * 32)), pv[4 * t], pv[4 * t + 1], pv[4 * t + 2], pv[4 * t + 3]);
                stsm4(sk + st_v + (lx ^ 96), pv[12], pv[13], ones, ones);
            }
            issue2(a1, 1); commit();
            retire(); load_a0(1); peek();
            stage_k(0);
            issue2(a0, 1); commit();
            retire(); load_a1(1); peek();
            stage_k(1);
            issue2(a1, 1); commit();
            retire(); load_a0(2); peek();
            stage_k(2);
            issue2(a0, 1); commit();
            retire(); load_a1(2); peek();
            stage_k(3);
            issue2(a1, 1); commit();
            retire(); load_a0(3); peek();
            g0 += __shfl_xor_sync(0xffffffffu, g0, 1); g1 += __shfl_xor_sync(0xffffffffu, g1, 1);
            fence_async_smem();
            g0 += __shfl_xor_sync(0xffffffffu, g0, 2); g1 += __shfl_xor_sync(0xffffffffu, g1, 2);
            if (wg == 0) bar_sync<1, 128>(); else bar_sync<2, 128>();
            float kv[32];
            issue2(a0, 1);
            {
                const uint32_t dk = dsb + LO128 + (st_base >> 4), ds = st_step >> 4, dv = st_v >> 4;
                #pragma unroll
                for (int ks = 0; ks < 4; ks++) wgmma_ss64_tt<HI128>(kv, dk + ks * ds, dk + ks * ds + dv, ks);
            }
            commit();
            retire(); load_a1(3); peek();
            {
                const float l2e = after_issue(-kLog2e, zero);
                float e0, e1;
                asm("ex2.approx.ftz.f32 %0, %1;" : "=f"(e0) : "f"(g0 * l2e));
                asm("ex2.approx.ftz.f32 %0, %1;" : "=f"(e1) : "f"(g1 * l2e));
                g0 = __fdividef(1.f, 1.f + e0);
                g1 = __fdividef(1.f, 1.f + e1);
                asm volatile("" : "+f"(g0), "+f"(g1));
            }
            issue2(a1, 1); commit();
            retire(); load_a0(4); peek();
            reg_fence(kv);
            if (wg == 0) { bar_arrive<5, 256>(); bar_sync<1, 128>(); } else bar_sync<5, 256>();
            auto stage_kv = [&](int hh) {
                const int d = w4 * 16 + g8 + 8 * hh;
                const bool h0 = d < 28;
                const uint32_t rowa = sb + OFF_STG + wg * 8192 + d * 128 + q4 * 8;
                #pragma unroll
                for (int t = 0; t < 4; t++) {
                    float v0 = h0 ? kv[4 * t + 2 * hh] : kv[4 * t + 12 + 2 * hh];
                    float v1 = h0 ? kv[4 * t + 2 * hh + 1] : kv[4 * t + 13 + 2 * hh];
                    if (t == 0 && !h0 && q4 == 0) v0 = kv[28 + 2 * hh];
                    if (d < 56 && !(t == 3 && h0 && q4 == 2))
                        asm volatile("st.shared.v2.f32 [%0], {%1, %2};" :: "r"(rowa + ((t ^ (g8 & 3)) << 5)), "f"(v0), "f"(v1) : "memory");
                }
                if (h0 && q4 == 0)
                    asm volatile("st.shared.v2.f32 [%0], {%1, %1};" :: "r"(rowa + ((3 ^ (g8 & 3)) << 5) + 16), "f"(kv[28 + 2 * hh]) : "memory");
            };
            stage_kv(0);
            issue2(a0, 1); commit();
            retire(); load_a1(4); peek();
            stage_kv(1);
            __syncwarp();
            if (lane == 0) mbar_arrive(sb + BAR_KVDONE);
            issue2(a1, 1); commit();
            retire(); load_a0(5); peek();
            {
                const uint32_t s0 = pack_bf16(1.f - g0, 1.f - g0), s1 = pack_bf16(1.f - g1, 1.f - g1);
                #pragma unroll
                for (int i = 0; i < 32; i++) hp[i] = mul_bf16x2(hp[i], (i & 1) ? s1 : s0);
                reg_fence_part<0, 32>(hp);
            }
            issue2(a0, 1); commit();
            retire(); load_a1(5); peek();
            issue2(a1, 1); commit();
            retire(); load_a0(6); peek();
            issue2(a0, 1); commit();
            retire(); load_a1(6); peek();
            if (wg == 1) bar_sync<4, 256>();
            const uint32_t b = begin();
            wgmma_rs128<HI128>(au, a1[0], a1[1], a1[2], a1[3], b + LO128X2 + 128, 1);
            wgmma_rs128<HI128>(au, a1[4], a1[5], a1[6], a1[7], b + LO128X2 + 512, 1);
            wg_commit();
            wgmma_rs56<HI128>(aq, a1[0], a1[1], a1[2], a1[3], b + LO128, 1);
            wgmma_rs56<HI128>(aq, a1[4], a1[5], a1[6], a1[7], b + LO128 + 384, 1);
            commit();
            if (wg == 0) bar_arrive<4, 256>();
            wg_wait<2>(); release(old);
            load_a0(0); peek();
            wg_wait<1>();
            reg_fence(au);
        }
        #pragma unroll
        for (int i = 0; i < 32; i++) hp[i] = mul_bf16x2(hp[i], pack_bf16(au[2 * i], au[2 * i + 1]));
        reg_fence_part<0, 32>(hp);

        float ag[96];
        uint32_t op[16];
        {
            auto issue3 = [&](uint32_t (&a)[8], int sd) {
                const uint32_t b = begin();
                wgmma_rs192<HI64>(ag, a[0], a[1], a[2], a[3], b + LO64, sd);
                wgmma_rs192<HI64>(ag, a[4], a[5], a[6], a[7], b + LO64 + 384, 1);
            };
            uint32_t pq[16];
            issue3(a0, 0); commit();
            retire();
            reg_fence(aq);
            load_a1(0); peek();
            auto phi_q = [&](int lo, int hi) {
                const float l2e = after_issue(kLog2e, zero);
                #pragma unroll
                for (int i = 0; i < 14; i++) if (i >= lo && i < hi) pq[i] = pack_bf16(phi(aq[2 * i], l2e), phi(aq[2 * i + 1], l2e));
            };
            pq[14] = 0u; pq[15] = 0u;
            issue3(a1, 1); commit();
            retire(); load_a0(1); peek();
            phi_q(0, 5); reg_fence_part<0, 5>(pq);
            issue3(a0, 1); commit();
            retire(); load_a1(1); peek();
            phi_q(5, 10); reg_fence_part<5, 10>(pq);
            issue3(a1, 1); commit();
            retire(); load_a0(2); peek();
            phi_q(10, 14); reg_fence_part<10, 16>(pq);
            issue3(a0, 1); commit();
            #pragma unroll
            for (int it = 2; it < 5; it++) {
                retire(); load_a1(it); peek();
                issue3(a1, 1); commit();
                retire(); load_a0(it + 1); peek();
                issue3(a0, 1); commit();
            }
            retire(); load_a1(5); peek();
            issue3(a1, 1); commit();
            const bool aux = mbar_try(sb + BAR_AUX, 0);
            retire(); load_a0(6); peek();
            if (!aux) mbar_wait(sb + BAR_AUX, 0);
            if (wg == 1) bar_sync<4, 256>();
            float nd[32];
            issue3(a0, 1);
            {
                const uint32_t dk = dsb + LO128 + ((OFF_STG + 8192) >> 4);
                #pragma unroll
                for (int ks = 0; ks < 4; ks++) wgmma_rs64<HI128>(nd, pq[4 * ks], pq[4 * ks + 1], pq[4 * ks + 2], pq[4 * ks + 3], dk + ks * 128, ks);
            }
            commit();
            retire(); load_a1(6); peek();
            issue3(a1, 1); commit();
            if (wg == 0) bar_arrive<4, 256>();
            ready = mbar_try(sb + p4_bar(0), p4_par(0));
            retire();
            reg_fence(nd);
            const int src = lane & ~3;
            const float s00 = __fdividef(g0, __shfl_sync(0xffffffffu, nd[28], src) + 1e-6f);
            const float s01 = __fdividef(g0, __shfl_sync(0xffffffffu, nd[29], src) + 1e-6f);
            const float s10 = __fdividef(g1, __shfl_sync(0xffffffffu, nd[30], src) + 1e-6f);
            const float s11 = __fdividef(g1, __shfl_sync(0xffffffffu, nd[31], src) + 1e-6f);
            #pragma unroll
            for (int t = 0; t < 7; t++) {
                const bool h1 = t > 3 || (t == 3 && q4 >= 2);
                const float sa = h1 ? s01 : s00, sc = h1 ? s11 : s10;
                op[2 * t] = pack_bf16(nd[4 * t] * sa, nd[4 * t + 1] * sa);
                op[2 * t + 1] = pack_bf16(nd[4 * t + 2] * sc, nd[4 * t + 3] * sc);
            }
            op[14] = 0u; op[15] = 0u;
            reg_fence(op);
        }

        float oa[32], ob[32];
        int c = j == 7 ? 0 : j;
        const int wsh = __shfl_sync(0xffffffffu, warp * 16, 0);
        const uint32_t sh0 = par * 768, sh1 = par * 1024;
        bool ready2 = false;
        auto issue_d = [&](float (&o)[32], int c0, int half) {
            const int n = 3 * c0;
            if (half == 0) {
                if (!ready) mbar_wait(sb + p4_bar(n), p4_par(n));
                if (!ready2) mbar_wait(sb + p4_bar(n + 1), p4_par(n + 1));
                ready = mbar_try(sb + p4_bar(n + 2), p4_par(n + 2));
            }
            wg_fence();
            const uint32_t b = dsb + LO128 + (p4_off(n) >> 4);
            #pragma unroll
            for (int ks = 7 * half; ks < 7 * half + 7; ks++)
                wgmma_rs64<HI128>(o, hp[4 * ks], hp[4 * ks + 1], hp[4 * ks + 2], hp[4 * ks + 3],
                                  b + ks * 128 + (ks < 8 ? sh0 : 0u - sh1), ks);
        };
        auto issue_o = [&](float (&o)[32], int c0) {
            const int n = 3 * c0 + 2;
            if (!ready) mbar_wait(sb + p4_bar(n), p4_par(n));
            if (c0 < 6) {
                ready = mbar_try(sb + p4_bar(n + 1), p4_par(n + 1));
                ready2 = mbar_try(sb + p4_bar(n + 2), p4_par(n + 2));
            }
            wg_fence();
            const uint32_t b = dsb + LO128 + (p4_off(n) >> 4);
            #pragma unroll
            for (int ks = 0; ks < 4; ks++) wgmma_rs64<HI128>(o, op[4 * ks], op[4 * ks + 1], op[4 * ks + 2], op[4 * ks + 3], b + ks * 128, 1);
            wg_commit();
        };
        auto ship = [&](float (&o)[32], int c0) {
            reg_fence(o);
            const uint32_t so = xa + OFF_OUT + (c0 & 1) * 16384;
            #pragma unroll
            for (int t = 0; t < 4; t++)
                stsm4(so + (lx ^ (t * 32)), pack_bf16(o[8 * t], o[8 * t + 1]), pack_bf16(o[8 * t + 2], o[8 * t + 3]),
                      pack_bf16(o[8 * t + 4], o[8 * t + 5]), pack_bf16(o[8 * t + 6], o[8 * t + 7]));
            fence_async_smem();
            __syncwarp();
            if (elect_one()) {
                tma_reduce2d(&mp.out, sb + OFF_OUT + (c0 & 1) * 16384 + wsh * 128, 64 * c, row0 + wsh);
                asm volatile("cp.async.bulk.commit_group;" ::: "memory");
            }
            if (++c == 7) c = 0;
        };
        auto finish_h = [&]() {
            reg_fence(ag);
            release(cur);
            const float u0 = 1.f - g0, u1 = 1.f - g1;
            #pragma unroll
            for (int i = 0; i < 24; i++) {
                const float u = (i & 1) ? u1 : u0;
                hp[32 + i] = mul_bf16x2(pack_relu_bf16(ag[2 * i], ag[2 * i + 1]), pack_bf16(ag[48 + 2 * i] * u, ag[49 + 2 * i] * u));
            }
            reg_fence_part<32, 56>(hp);
        };
        ready2 = mbar_try(sb + p4_bar(1), p4_par(1));
        wg_wait<0>();
        finish_h();
        #pragma unroll
        for (int c0 = 0; c0 < 7; c0++) {
            float (&o)[32] = (c0 & 1) ? ob : oa;
            if (c0 > 0 || wg == 1) turn_wait();
            issue_d(o, c0, 0);
            issue_d(o, c0, 1);
            issue_o(o, c0);
            if (!(c0 == 6 && wg == 1)) turn_pass();
            if (c0 >= 2) {
                if (elect_one()) asm volatile("cp.async.bulk.wait_group.read 1;" ::: "memory");
                __syncwarp();
            }
            wg_wait<0>();
            if (c0 < 2) { release(3 * c0); release(3 * c0 + 1); release(3 * c0 + 2); }
            ship(o, c0);
        }
        if (elect_one()) asm volatile("cp.async.bulk.wait_group.read 0;" ::: "memory");
    }
}

typedef CUresult (*EncodeFn)(CUtensorMap*, CUtensorMapDataType, cuuint32_t, void*, const cuuint64_t*, const cuuint64_t*,
                             const cuuint32_t*, const cuuint32_t*, CUtensorMapInterleave, CUtensorMapSwizzle,
                             CUtensorMapL2promotion, CUtensorMapFloatOOBfill);

void make_map(EncodeFn enc, CUtensorMap* m, const void* base, int rank, const cuuint64_t* dims, const cuuint64_t* strides,
              cuuint32_t b0, cuuint32_t b1, cuuint32_t b2, CUtensorMapSwizzle sw) {
    const cuuint32_t es[3] = {1, 1, 1}, box[3] = {b0, b1, b2};
    enc(m, CU_TENSOR_MAP_DATA_TYPE_BFLOAT16, rank, const_cast<void*>(base), dims, strides, box, es,
        CU_TENSOR_MAP_INTERLEAVE_NONE, sw, CU_TENSOR_MAP_L2_PROMOTION_L2_128B, CU_TENSOR_MAP_FLOAT_OOB_FILL_NONE);
}

}

extern "C" void kernel_launch(void* const* d_in, const int* in_sizes, int n_in, void* d_out, int out_size) {
    (void)in_sizes; (void)n_in; (void)out_size;
    static EncodeFn enc = nullptr;
    if (!enc) {
        void* fn = nullptr;
        cudaDriverEntryPointQueryResult st;
        cudaGetDriverEntryPoint("cuTensorMapEncodeTiled", &fn, cudaEnableDefault, &st);
        enc = (EncodeFn)fn;
        cudaFuncSetAttribute(fused_kernel, cudaFuncAttributeMaxDynamicSharedMemorySize, SMEM_BYTES);
    }
    Maps mp;
    const cuuint64_t dimx[2] = {kD, kS}, dimd[2] = {kD, kF}, dimo[2] = {kD, kD}, strd[1] = {kD * 2};
    make_map(enc, &mp.x, d_in[0], 2, dimx, strd, 64, 128, 1, CU_TENSOR_MAP_SWIZZLE_128B);
    make_map(enc, &mp.out, d_out, 2, dimx, strd, 64, 16, 1, CU_TENSOR_MAP_SWIZZLE_128B);
    make_map(enc, &mp.d, d_in[6], 2, dimd, strd, 64, 56, 1, CU_TENSOR_MAP_SWIZZLE_128B);
    make_map(enc, &mp.o, d_in[2], 2, dimo, strd, 64, 32, 1, CU_TENSOR_MAP_SWIZZLE_128B);
    const cuuint64_t dimq[3] = {kD, kD, 3}, strq[2] = {3 * kD * 2, kD * 2};
    make_map(enc, &mp.kv, d_in[1], 3, dimq, strq, 56, 16, 2, CU_TENSOR_MAP_SWIZZLE_128B);
    make_map(enc, &mp.q, d_in[1], 3, dimq, strq, 56, 16, 1, CU_TENSOR_MAP_SWIZZLE_128B);
    const cuuint64_t dimf[3] = {32, kD, kF / 32}, strf[2] = {kF * 2, 64};
    const cuuint64_t dimw[3] = {64, kD, kF / 64}, strw[2] = {kF * 2, 128};
    make_map(enc, &mp.g4, d_in[4], 3, dimw, strw, 64, 16, 2, CU_TENSOR_MAP_SWIZZLE_128B);
    make_map(enc, &mp.u4, d_in[5], 3, dimw, strw, 64, 16, 2, CU_TENSOR_MAP_SWIZZLE_128B);
    make_map(enc, &mp.g3, d_in[4], 3, dimf, strf, 32, 16, 3, CU_TENSOR_MAP_SWIZZLE_64B);
    make_map(enc, &mp.u3, d_in[5], 3, dimf, strf, 32, 16, 3, CU_TENSOR_MAP_SWIZZLE_64B);
    fused_kernel<<<NCTA, NTHREADS, SMEM_BYTES>>>(mp, (const __nv_bfloat16*)d_in[7], (__nv_bfloat16*)d_out, 0u);
}
```

```cpp
#include <cuda_runtime.h>
#include <cuda_bf16.h>
#include <cuda.h>
#include <stdint.h>

namespace {

constexpr int kS = 2048, kD = 448, kF = 1792;
constexpr int NTHREADS = 384;
constexpr int NCTA = 128;
constexpr uint32_t OFF_X = 0;
constexpr uint32_t OFF_RING = 114688;
constexpr uint32_t SLOT_BYTES = 16384;
constexpr int NSLOT = 6;
constexpr uint32_t OFF_STG = 212992;
constexpr uint32_t OFF_MISC = 229376;
constexpr uint32_t SMEM_BYTES = 232448;
constexpr uint32_t BAR_FULL = OFF_MISC, BAR_EMPTY = OFF_MISC + 48, BAR_XFULL = OFF_MISC + 96;
constexpr uint32_t BAR_W = OFF_MISC + 152, BAR_KVDONE = OFF_MISC + 160, BAR_AUX = OFF_MISC + 168, BAR_P4 = OFF_MISC + 176;
constexpr uint32_t OFF_W = OFF_MISC + 256;
constexpr uint32_t SB = 1024;

__device__ __align__(128) float g_kvacc[8][2048];
__device__ unsigned int g_counter[64];

__device__ __forceinline__ void mbar_init(uint32_t bar, uint32_t cnt) {
    asm volatile("mbarrier.init.shared::cta.b64 [%0], %1;" :: "r"(bar), "r"(cnt) : "memory");
}
__device__ __forceinline__ void mbar_expect_tx(uint32_t bar, uint32_t bytes) {
    asm volatile("mbarrier.arrive.expect_tx.shared::cta.b64 _, [%0], %1;" :: "r"(bar), "r"(bytes) : "memory");
}
__device__ __forceinline__ void mbar_arrive(uint32_t bar) {
    asm volatile("mbarrier.arrive.shared::cta.b64 _, [%0];" :: "r"(bar) : "memory");
}
__device__ __forceinline__ void mbar_arrive_cluster(uint32_t bar) {
    asm volatile("mbarrier.arrive.shared::cluster.b64 _, [%0];" :: "r"(bar) : "memory");
}
__device__ __forceinline__ void mbar_wait(uint32_t bar, uint32_t parity) {
    asm volatile("{\n"
                 ".reg .pred p;\n"
                 ".reg .u32 c;\n"
                 "mov.u32 c, 0;\n"
                 "AGAIN:\n"
                 "mbarrier.try_wait.parity.shared::cta.b64 p, [%0], %1;\n"
                 "@p bra DONE;\n"
                 "add.u32 c, c, 1;\n"
                 "setp.lt.u32 p, c, 4194304;\n"
                 "@p bra AGAIN;\n"
                 "trap;\n"
                 "DONE:\n"
                 "}" :: "r"(bar), "r"(parity) : "memory");
}
__device__ __forceinline__ uint32_t mapa(uint32_t addr, uint32_t cta) {
    uint32_t r; asm("mapa.shared::cluster.u32 %0, %1, %2;" : "=r"(r) : "r"(addr), "r"(cta)); return r;
}
__device__ __forceinline__ bool elect_one() {
    uint32_t p;
    asm volatile("{ .reg .pred P; elect.sync _|P, 0xffffffff; selp.u32 %0, 1, 0, P; }" : "=r"(p));
    return p;
}
__device__ __forceinline__ void tma2d(uint32_t dst, const CUtensorMap* m, int c0, int c1, uint32_t bar) {
    asm volatile("cp.async.bulk.tensor.2d.shared::cluster.global.mbarrier::complete_tx::bytes [%0], [%1, {%3, %4}], [%2];"
                 :: "r"(dst), "l"(m), "r"(bar), "r"(c0), "r"(c1) : "memory");
}
__device__ __forceinline__ void tma2d_mc(uint32_t dst, const CUtensorMap* m, int c0, int c1, uint32_t bar) {
    asm volatile("cp.async.bulk.tensor.2d.shared::cluster.global.mbarrier::complete_tx::bytes.multicast::cluster [%0], [%1, {%3, %4}], [%2], %5;"
                 :: "r"(dst), "l"(m), "r"(bar), "r"(c0), "r"(c1), "h"((uint16_t)3) : "memory");
}
__device__ __forceinline__ void tma3d_mc(uint32_t dst, const CUtensorMap* m, int c0, int c1, int c2, uint32_t bar) {
    asm volatile("cp.async.bulk.tensor.3d.shared::cluster.global.mbarrier::complete_tx::bytes.multicast::cluster [%0], [%1, {%3, %4, %5}], [%2], %6;"
                 :: "r"(dst), "l"(m), "r"(bar), "r"(c0), "r"(c1), "r"(c2), "h"((uint16_t)3) : "memory");
}
__device__ __forceinline__ void tma_reduce2d(const CUtensorMap* m, uint32_t src, int c0, int c1) {
    asm volatile("cp.reduce.async.bulk.tensor.2d.global.shared::cta.add.bulk_group [%0, {%2, %3}], [%1];"
                 :: "l"(m), "r"(src), "r"(c0), "r"(c1) : "memory");
}
__device__ __forceinline__ void bulk_reduce_f32(float* dst, uint32_t src, uint32_t bytes) {
    asm volatile("cp.reduce.async.bulk.global.shared::cta.bulk_group.add.f32 [%0], [%1], %2;" :: "l"(dst), "r"(src), "r"(bytes) : "memory");
}
__device__ __forceinline__ bool mbar_try(uint32_t bar, uint32_t parity) {
    uint32_t ok;
    asm volatile("{ .reg .pred p; mbarrier.test_wait.parity.shared::cta.b64 p, [%1], %2; selp.u32 %0, 1, 0, p; }"
                 : "=r"(ok) : "r"(bar), "r"(parity) : "memory");
    return ok;
}
__device__ __forceinline__ void prefetch_map(const CUtensorMap* m) {
    asm volatile("prefetch.tensormap [%0];" :: "l"(m) : "memory");
}
__device__ __forceinline__ void wg_fence() { asm volatile("wgmma.fence.sync.aligned;" ::: "memory"); }
__device__ __forceinline__ void wg_commit() { asm volatile("wgmma.commit_group.sync.aligned;" ::: "memory"); }
template <int N> __device__ __forceinline__ void wg_wait() { asm volatile("wgmma.wait_group.sync.aligned %0;" :: "n"(N) : "memory"); }
template <int N> __device__ __forceinline__ void reg_fence(float (&d)[N]) {
#pragma unroll
    for (int i = 0; i < N; i++) asm volatile("" : "+f"(d[i]) :: "memory");
}
template <int N> __device__ __forceinline__ void reg_fence(uint32_t (&d)[N]) {
#pragma unroll
    for (int i = 0; i < N; i++) asm volatile("" : "+r"(d[i]) :: "memory");
}
template <int LO, int HI, int N> __device__ __forceinline__ void reg_fence_part(uint32_t (&d)[N]) {
#pragma unroll
    for (int i = LO; i < HI; i++) asm volatile("" : "+r"(d[i]) :: "memory");
}
__device__ __forceinline__ void fence_async_smem() { asm volatile("fence.proxy.async.shared::cta;" ::: "memory"); }
template <int ID, int N> __device__ __forceinline__ void bar_sync() { asm volatile("bar.sync %0, %1;" :: "n"(ID), "n"(N) : "memory"); }
template <int ID, int N> __device__ __forceinline__ void bar_arrive() { asm volatile("bar.arrive %0, %1;" :: "n"(ID), "n"(N) : "memory"); }
__device__ __forceinline__ void ldsm4(uint32_t* r, uint32_t addr) {
    asm volatile("ldmatrix.sync.aligned.m8n8.x4.shared.b16 {%0, %1, %2, %3}, [%4];"
                 : "=r"(r[0]), "=r"(r[1]), "=r"(r[2]), "=r"(r[3]) : "r"(addr) : "memory");
}
__device__ __forceinline__ void stsm4(uint32_t addr, uint32_t r0, uint32_t r1, uint32_t r2, uint32_t r3) {
    asm volatile("stmatrix.sync.aligned.m8n8.x4.shared.b16 [%0], {%1, %2, %3, %4};"
                 :: "r"(addr), "r"(r0), "r"(r1), "r"(r2), "r"(r3) : "memory");
}
__device__ __forceinline__ uint32_t lds32(uint32_t addr) {
    uint32_t r; asm volatile("ld.shared.u32 %0, [%1];" : "=r"(r) : "r"(addr)); return r;
}
__device__ __forceinline__ float4 lds128f(uint32_t addr) {
    float4 r; asm volatile("ld.shared.v4.f32 {%0, %1, %2, %3}, [%4];" : "=f"(r.x), "=f"(r.y), "=f"(r.z), "=f"(r.w) : "r"(addr)); return r;
}
__device__ __forceinline__ uint32_t clock32() { uint32_t t; asm volatile("mov.u32 %0, %%clock;" : "=r"(t)); return t; }
__device__ __forceinline__ uint32_t pack_bf16(float lo, float hi) {
    uint32_t r; asm("cvt.rn.bf16x2.f32 %0, %1, %2;" : "=r"(r) : "f"(hi), "f"(lo)); return r;
}
__device__ __forceinline__ uint32_t pack_relu_bf16(float lo, float hi) {
    uint32_t r; asm("cvt.rn.relu.bf16x2.f32 %0, %1, %2;" : "=r"(r) : "f"(hi), "f"(lo)); return r;
}
__device__ __forceinline__ uint32_t mul_bf16x2(uint32_t a, uint32_t b) {
    uint32_t r; asm("mul.rn.bf16x2 %0, %1, %2;" : "=r"(r) : "r"(a), "r"(b)); return r;
}
__device__ __forceinline__ uint32_t fma_bf16x2(uint32_t a, uint32_t b, uint32_t c) {
    uint32_t r; asm("fma.rn.bf16x2 %0, %1, %2, %3;" : "=r"(r) : "r"(a), "r"(b), "r"(c)); return r;
}
__device__ __forceinline__ float phi(float t, float log2e) {
    float e;
    asm("ex2.approx.ftz.f32 %0, %1;" : "=f"(e) : "f"(fminf(t * log2e, 0.f)));
    return e + (fmaxf(t, 0.f) + 1e-6f);
}
__device__ __forceinline__ float after_issue(float v, uint32_t zero) {
    return __uint_as_float(__float_as_uint(v) | (clock32() & zero));
}
constexpr float kLog2e = 1.4426950408889634f;
__device__ __forceinline__ float bf_lo(uint32_t v) { return __uint_as_float(v << 16); }
__device__ __forceinline__ float bf_hi(uint32_t v) { return __uint_as_float(v & 0xffff0000u); }
constexpr uint32_t HI128 = (1024 >> 4) | (1u << 30);
constexpr uint32_t HI64 = (512 >> 4) | (2u << 30);
constexpr uint32_t LO128 = 1u << 16, LO64 = (1024u >> 4) << 16, LO128X2 = (2048u >> 4) << 16;
constexpr uint32_t QB = 16 * 112;
constexpr uint32_t TX1 = 2 * (2 * QB + 4096), TX2 = 2 * (QB + 4096), TX3 = 12288;
__device__ __forceinline__ void grid_arrive(unsigned int* c) {
    asm volatile("fence.acq_rel.gpu;" ::: "memory");
    asm volatile("red.relaxed.gpu.global.add.u32 [%0], 1;" :: "l"(c) : "memory");
}
__device__ __forceinline__ void grid_wait(const unsigned int* c, unsigned int target) {
    unsigned int v; int it = 0;
    do {
        asm volatile("ld.relaxed.gpu.global.u32 %0, [%1];" : "=r"(v) : "l"(c) : "memory");
        if (++it > (1 << 22)) asm volatile("trap;");
    } while ((int)(v - target) < 0);
    asm volatile("ld.acquire.gpu.global.u32 %0, [%1];" : "=r"(v) : "l"(c) : "memory");
}


__host__ __device__ constexpr uint32_t p4_pack(int n) { return (n / 3) * 36864 + (n % 3) * 14336; }
__host__ __device__ constexpr uint32_t p4_off(int n) {
    return n < 6 ? OFF_X + p4_pack(n) : n < 14 ? OFF_RING + p4_pack(n - 6) : n == 14 ? OFF_X + p4_pack(6) : OFF_X + p4_pack(n - 15);
}
__host__ __device__ constexpr uint32_t p4_bar(int n) {
    return n < 6 ? BAR_XFULL + 8 * n : n < 12 ? BAR_FULL + 8 * (n - 6) : n < 14 ? BAR_P4 + 8 * (n - 12)
                 : n == 14 ? BAR_XFULL + 48 : BAR_XFULL + 8 * (n - 15);
}
__host__ __device__ constexpr uint32_t p4_par(int n) { return (n < 12 || n == 14) ? 1 : 0; }
constexpr uint32_t OFF_OUT = OFF_X + 5 * 16384;
static_assert(p4_off(7) == p4_off(6) + 14336 && p4_off(13) == p4_off(12) + 14336 && p4_off(16) == p4_off(15) + 14336, "Wd halves");
static_assert(p4_off(13) + 14336 <= OFF_STG + 8192 && p4_off(14) + 8192 == OFF_OUT, "pass-4 layout");

struct Ring {
    uint32_t slot, phase;
    __device__ __forceinline__ void advance() { if (++slot == NSLOT) { slot = 0; phase ^= 1; } }
};

struct Maps { CUtensorMap x, kv, q, g4, g3, u4, u3, d, o, out; };

__global__ void __cluster_dims__(2, 1, 1) __launch_bounds__(NTHREADS, 1)
fused_kernel(const __grid_constant__ Maps mp, const __nv_bfloat16* __restrict__ gate_w, __nv_bfloat16* __restrict__ out,
             uint32_t zero)
{
    extern __shared__ __align__(1024) unsigned char smem[];
    const uint32_t sb = (uint32_t)__cvta_generic_to_shared(smem);
    const int tid = threadIdx.x, warp = tid >> 5, lane = tid & 31;
    const int rank = blockIdx.x & 1, j = (blockIdx.x >> 1) & 7;
    const int row0 = ((blockIdx.x >> 4) * 2 + rank) * 128;
    const int par = j & 1;
    const int g4i = (7 * j + 3 * par) >> 1;

    if (warp == 9) {
        if (elect_one()) {
            prefetch_map(&mp.x);
            mbar_init(sb + BAR_XFULL, 1);
            mbar_expect_tx(sb + BAR_XFULL, 16384);
            tma2d(sb + OFF_X, &mp.x, 0, row0, sb + BAR_XFULL);
            asm volatile("fence.mbarrier_init.release.cluster;" ::: "memory");
        }
        __syncwarp();
    } else if (warp == 8) {
        if (elect_one()) {
            #pragma unroll
            for (int s = 0; s < NSLOT; s++) mbar_init(sb + BAR_FULL + 8 * s, 1);
            asm volatile("fence.mbarrier_init.release.cluster;" ::: "memory");
            mbar_expect_tx(sb + BAR_FULL, TX1);
        }
        __syncwarp();
    } else if (warp == 10) {
        if (elect_one()) {
            #pragma unroll
            for (int s = 1; s < 7; s++) mbar_init(sb + BAR_XFULL + 8 * s, 1);
            mbar_init(sb + BAR_KVDONE, 8);
            mbar_init(sb + BAR_AUX, 3);
            asm volatile("fence.mbarrier_init.release.cluster;" ::: "memory");
            if ((sb & 0xFFFFFF) != SB) asm volatile("trap;");
        }
        __syncwarp();
    } else if (warp == 11) {
        if (elect_one()) {
            #pragma unroll
            for (int s = 0; s < NSLOT; s++) mbar_init(sb + BAR_EMPTY + 8 * s, 4);
            mbar_init(sb + BAR_P4, 1);
            mbar_init(sb + BAR_P4 + 8, 1);
            asm volatile("fence.mbarrier_init.release.cluster;" ::: "memory");
        }
        __syncwarp();
    } else if (warp == 2) {
        if (elect_one()) {
            mbar_init(sb + BAR_W, 1);
            asm volatile("fence.mbarrier_init.release.cluster;" ::: "memory");
            mbar_expect_tx(sb + BAR_W, 896);
            asm volatile("cp.async.bulk.shared::cluster.global.mbarrier::complete_tx::bytes [%0], [%1], 896, [%2];"
                         :: "r"(sb + OFF_W), "l"(gate_w), "r"(sb + BAR_W) : "memory");
        }
        __syncwarp();
    }
    asm volatile("barrier.cluster.arrive.relaxed.aligned;" ::: "memory");
    if (warp == 8) {
        if (elect_one()) { prefetch_map(&mp.kv); prefetch_map(&mp.g4); }
        __syncwarp();
    }
    asm volatile("barrier.cluster.wait.aligned;" ::: "memory");
    if (warp == 8) {
        if (elect_one()) {
            tma3d_mc(sb + OFF_RING + rank * 8192, &mp.kv, 56 * j, 16 * rank, 1, sb + BAR_FULL);
            tma3d_mc(sb + OFF_RING + rank * 8192 + 4096, &mp.g4, 0, 16 * rank, g4i, sb + BAR_FULL);
        }
        __syncwarp();
    }

    if (warp >= 8) {
        asm volatile("setmaxnreg.dec.sync.aligned.u32 40;");
        if (warp == 8) {
            if (elect_one()) {
                Ring r{1, 1};
                auto acquire = [&](uint32_t bytes) -> uint32_t {
                    mbar_wait(sb + BAR_EMPTY + 8 * r.slot, r.phase);
                    mbar_expect_tx(sb + BAR_FULL + 8 * r.slot, bytes);
                    return sb + OFF_RING + r.slot * SLOT_BYTES;
                };
                #pragma unroll 1
                for (int s = 1; s < 14; s++) {
                    const uint32_t dst = acquire(TX1) + rank * 8192;
                    tma3d_mc(dst, &mp.kv, 56 * j, 32 * s + 16 * rank, 1, sb + BAR_FULL + 8 * r.slot);
                    tma3d_mc(dst + 4096, &mp.g4, 0, 32 * s + 16 * rank, g4i, sb + BAR_FULL + 8 * r.slot);
                    r.advance();
                    if ((s & 1) && s < 12) {
                        const int n = (s >> 1) + 1;
                        mbar_expect_tx(sb + BAR_XFULL + 8 * n, 16384);
                        tma2d(sb + OFF_X + n * 16384, &mp.x, 64 * n, row0, sb + BAR_XFULL + 8 * n);
                    }
                    if (s == 5) {
                        prefetch_map(&mp.q); prefetch_map(&mp.u4); prefetch_map(&mp.g3); prefetch_map(&mp.u3);
                        prefetch_map(&mp.d); prefetch_map(&mp.o); prefetch_map(&mp.out);
                    }
                }
                #pragma unroll 1
                for (int s = 0; s < 14; s++) {
                    const uint32_t dst = acquire(TX2) + rank * 6144;
                    tma3d_mc(dst, &mp.q, 56 * j, 32 * s + 16 * rank, 0, sb + BAR_FULL + 8 * r.slot);
                    tma3d_mc(dst + 2048, &mp.u4, 0, 32 * s + 16 * rank, g4i, sb + BAR_FULL + 8 * r.slot);
                    r.advance();
                }
                const int cfirst = j == 7 ? 0 : j;
                auto load4 = [&](int n) {
                    int c = cfirst + n / 3;
                    if (c >= 7) c -= 7;
                    mbar_expect_tx(sb + p4_bar(n), n % 3 == 2 ? 8192 : 14336);
                    if (n % 3 == 2) tma2d_mc(sb + p4_off(n) + rank * 4096, &mp.o, 64 * c, 56 * j + 32 * rank, sb + p4_bar(n));
                    else tma2d_mc(sb + p4_off(n) + rank * 7168, &mp.d, 64 * c, 224 * j + 112 * (n % 3) + 56 * rank, sb + p4_bar(n));
                };
                #pragma unroll 1
                for (int s = 0; s < 14; s++) {
                    const uint32_t dst = acquire(TX3) + rank * 6144;
                    tma3d_mc(dst, &mp.g3, 0, 32 * s + 16 * rank, 7 * j + 4 - 4 * par, sb + BAR_FULL + 8 * r.slot);
                    tma3d_mc(dst + 3072, &mp.u3, 0, 32 * s + 16 * rank, 7 * j + 4 - 4 * par, sb + BAR_FULL + 8 * r.slot);
                    r.advance();
                    if (s == 7) load4(0);
                    if (s == 9) load4(1);
                    if (s == 11) load4(2);
                    if (s == 13) { load4(3); load4(4); }
                }
                mbar_wait(sb + BAR_EMPTY, 0);      load4(6);
                mbar_wait(sb + BAR_EMPTY + 8, 0);  load4(5); load4(7); load4(14);
                mbar_wait(sb + BAR_EMPTY + 16, 0); load4(8);
                mbar_wait(sb + BAR_EMPTY + 24, 0); load4(9); load4(10);
                mbar_wait(sb + BAR_EMPTY + 32, 0); load4(11);
                mbar_wait(sb + BAR_EMPTY + 40, 0); load4(12);
                mbar_wait(sb + BAR_AUX, 0);        load4(13);
                #pragma unroll
                for (int n = 15; n < 21; n++) {
                    mbar_wait(sb + BAR_EMPTY + 8 * (n - 15), 1);
                    __nanosleep(100);
                    load4(n);
                }
            }
        } else {
            const int ht = tid - 288;
            unsigned int cnt0;
            asm volatile("ld.relaxed.gpu.global.u32 %0, [%1];" : "=r"(cnt0) : "l"(&g_counter[32]) : "memory");
            const unsigned int target = ((cnt0 >> 7) + 1) << 7;
            if (warp == 9) {
                reinterpret_cast<float4*>(&g_kvacc[0][0])[blockIdx.x * 32 + lane] = make_float4(0.f, 0.f, 0.f, 0.f);
                asm volatile("fence.proxy.async.global;" ::: "memory");
                __syncwarp();
                if (lane == 0) grid_arrive(&g_counter[0]);
                mbar_wait(sb + BAR_XFULL + 8 * 6, 0);
                uint4* o = reinterpret_cast<uint4*>(out) + blockIdx.x * 896 + lane;
                #pragma unroll 4
                for (int q = 0; q < 28; q++) o[q * 32] = make_uint4(0, 0, 0, 0);
                asm volatile("fence.proxy.async.global;" ::: "memory");
                __syncwarp();
                if (lane == 0) {
                    asm volatile("fence.acq_rel.gpu;" ::: "memory");
                    grid_wait(&g_counter[0], target);
                }
                __syncwarp();
            }
            mbar_wait(sb + BAR_KVDONE, 0);
            {
                #pragma unroll
                for (int i0 = 0; i0 < 5; i0 += 2) {
                    float4 pa[2], pb[2];
                    #pragma unroll
                    for (int i = 0; i < 2 && i0 + i < 5; i++) {
                        const int q = min(ht + 96 * (i0 + i), 447);
                        pa[i] = lds128f(sb + OFF_STG + q * 16); pb[i] = lds128f(sb + OFF_STG + 8192 + q * 16);
                    }
                    #pragma unroll
                    for (int i = 0; i < 2 && i0 + i < 5; i++) {
                        const int q = ht + 96 * (i0 + i);
                        if (q < 448) asm volatile("st.shared.v4.f32 [%0], {%1, %2, %3, %4};" :: "r"(sb + OFF_STG + q * 16),
                            "f"(pa[i].x + pb[i].x), "f"(pa[i].y + pb[i].y), "f"(pa[i].z + pb[i].z), "f"(pa[i].w + pb[i].w) : "memory");
                    }
                }
                fence_async_smem();
            }
            bar_sync<3, 96>();
            if (warp == 9) {
                if (elect_one()) {
                    bulk_reduce_f32(&g_kvacc[j][0], sb + OFF_STG, 7168);
                    asm volatile("cp.async.bulk.commit_group;" ::: "memory");
                    asm volatile("cp.async.bulk.wait_group 0;" ::: "memory");
                    asm volatile("red.relaxed.gpu.global.add.u32 [%0], 1;" :: "l"(&g_counter[32]) : "memory");
                }
            }
            __syncwarp();
            #pragma unroll
            for (int i = 0; i < 3; i++) {
                const int q = ht + 96 * i;
                const int d = q < 168 ? q / 3 : 56 + ((q - 168) >> 3);
                const int c = q < 168 ? (q - 3 * d + (d < 28 ? 4 : 0)) : (q & 7);
                if (q < 232) asm volatile("st.shared.v4.u32 [%0], {%1, %1, %1, %1};" :: "r"(sb + OFF_STG + 8192 + d * 128 + ((c ^ (d & 7)) << 4)), "r"(0) : "memory");
            }
            uint32_t plan[3];
            #pragma unroll
            for (int i = 0; i < 3; i++) {
                const int q = min(ht + 96 * i, 279), d = q / 5, m = q - 5 * d;
                const bool h0 = d < 28;
                const int c = m == 4 ? 7 : (h0 ? m : m + 3), pc = m < 4 ? m : (h0 ? 3 : 0);
                const int kind = m == 4 ? (h0 ? 3 : 4) : c == 3 ? (h0 ? 1 : 2) : 0;
                plan[i] = (d * 128 + ((c ^ (d & 7)) << 4)) | ((d * 4 + (pc ^ (d & 3))) << 13) | (kind << 23);
                asm volatile("" : "+r"(plan[i]));
            }
            if (lane == 0) grid_wait(&g_counter[32], target);
            __syncwarp();
            const float4* src = reinterpret_cast<const float4*>(&g_kvacc[j][0]);
            float4 va[3], vb[3];
            #pragma unroll
            for (int i = 0; i < 3; i++) {
                const float4* p = src + ((plan[i] >> 12) & 0x7fe);
                va[i] = __ldcg(p); vb[i] = __ldcg(p + 1);
            }
            #pragma unroll
            for (int i = 0; i < 3; i++) {
                const uint32_t kind = plan[i] >> 23;
                uint32_t w0 = pack_bf16(va[i].x, va[i].y), w1 = pack_bf16(va[i].z, va[i].w);
                uint32_t w2 = pack_bf16(vb[i].x, vb[i].y), w3 = pack_bf16(vb[i].z, vb[i].w);
                if (kind == 3) w0 = w2 & 0xffffu;
                if (kind == 4) w0 <<= 16;
                if (kind == 2) w0 = 0u;
                if (kind >= 2) w1 = 0u;
                if (kind != 0 && kind != 2) w2 = w3 = 0u;
                if (i < 2 || ht < 88)
                    asm volatile("st.shared.v4.u32 [%0], {%1, %2, %3, %4};"
                                 :: "r"(sb + OFF_STG + 8192 + (plan[i] & 0x1fff)), "r"(w0), "r"(w1), "r"(w2), "r"(w3) : "memory");
            }
            fence_async_smem();
            __syncwarp();
            if (lane == 0) mbar_arrive(sb + BAR_AUX);
        }
    } else {
        asm volatile("setmaxnreg.inc.sync.aligned.u32 232;");
        const int wg = warp >> 2, w4 = warp & 3;
        const int q4 = lane & 3, g8 = lane >> 2;
        const uint32_t lx = ((lane >> 4) ^ (lane & 7)) << 4;
        const uint32_t xa = sb + OFF_X + (warp * 16 + (lane & 15)) * 128;
        const uint32_t empty_dst = mapa(sb + BAR_EMPTY, w4 & 1);
        const bool signaller = lane == 0 && w4 < 2;
        constexpr uint32_t dsb = SB >> 4;
        Ring r{0, 0};
        uint32_t cur = 0, old = 0;
        bool ready = false;
        auto release = [&](uint32_t slot) { if (signaller) mbar_arrive_cluster(empty_dst + 8 * slot); };
        auto turn_wait = [&]() { if (wg == 0) bar_sync<6, 256>(); else bar_sync<7, 256>(); };
        auto turn_pass = [&]() { if (wg == 0) bar_arrive<7, 256>(); else bar_arrive<6, 256>(); };
        auto begin = [&]() -> uint32_t {
            if (!ready) mbar_wait(sb + BAR_FULL + 8 * r.slot, r.phase);
            wg_fence();
            return dsb + (OFF_RING >> 4) + r.slot * (SLOT_BYTES >> 4);
        };
        auto commit = [&]() { wg_commit(); old = cur; cur = r.slot; r.advance(); };
        auto retire = [&]() { wg_wait<1>(); release(old); };
        auto peek = [&]() { ready = mbar_try(sb + BAR_FULL + 8 * r.slot, r.phase); };
        uint32_t a0[8], a1[8];
        auto load_a0 = [&](int kc) { ldsm4(a0, xa + kc * 16384 + lx); ldsm4(a0 + 4, xa + kc * 16384 + (lx ^ 32)); };
        auto load_a1 = [&](int kc) { ldsm4(a1, xa + kc * 16384 + (lx ^ 64)); ldsm4(a1 + 4, xa + kc * 16384 + (lx ^ 96)); };

        uint32_t hp[56];
        float g0, g1, ak[28], av[28];
        {
            float ag[64];
            float d0 = 0.f, d1 = 0.f, d2 = 0.f, d3 = 0.f;
            uint32_t w0[4], w1[4];
            auto issue1 = [&](uint32_t (&a)[8], int sd) {
                const uint32_t b = begin();
                wgmma_rs56<HI128>(ak, a[0], a[1], a[2], a[3], b + LO128, sd);
                wgmma_rs56<HI128>(av, a[0], a[1], a[2], a[3], b + LO128 + 128, sd);
                wgmma_rs128<HI128>(ag, a[0], a[1], a[2], a[3], b + LO128X2 + 256, sd);
                wgmma_rs56<HI128>(ak, a[4], a[5], a[6], a[7], b + LO128 + 512, 1);
                wgmma_rs56<HI128>(av, a[4], a[5], a[6], a[7], b + LO128 + 640, 1);
                wgmma_rs128<HI128>(ag, a[4], a[5], a[6], a[7], b + LO128X2 + 768, 1);
                commit();
            };
            auto issue1s = [&](uint32_t (&a)[8]) {
                const uint32_t b = begin();
                wgmma_rs128<HI128>(ag, a[0], a[1], a[2], a[3], b + LO128X2 + 256, 1);
                wgmma_rs128<HI128>(ag, a[4], a[5], a[6], a[7], b + LO128X2 + 768, 1);
                wg_commit();
                wgmma_rs56<HI128>(ak, a[0], a[1], a[2], a[3], b + LO128, 1);
                wgmma_rs56<HI128>(av, a[0], a[1], a[2], a[3], b + LO128 + 128, 1);
                wgmma_rs56<HI128>(ak, a[4], a[5], a[6], a[7], b + LO128 + 512, 1);
                wgmma_rs56<HI128>(av, a[4], a[5], a[6], a[7], b + LO128 + 640, 1);
                commit();
            };
            auto load_w = [&](uint32_t (&w)[4], int s) {
                #pragma unroll
                for (int e = 0; e < 4; e++) w[e] = lds32(sb + OFF_W + s * 64 + q4 * 4 + e * 16);
            };
            auto dot = [&](uint32_t (&a)[8], uint32_t (&w)[4]) {
                uint32_t p0 = mul_bf16x2(a[0], w[0]), p1 = mul_bf16x2(a[1], w[0]);
                #pragma unroll
                for (int e = 1; e < 4; e++) { p0 = fma_bf16x2(a[2 * e], w[e], p0); p1 = fma_bf16x2(a[2 * e + 1], w[e], p1); }
                d0 += bf_lo(p0); d2 += bf_hi(p0); d1 += bf_lo(p1); d3 += bf_hi(p1);
                asm volatile("" : "+f"(d0), "+f"(d1), "+f"(d2), "+f"(d3));
            };
            mbar_wait(sb + BAR_XFULL, 0);
            load_a0(0);
            mbar_wait(sb + BAR_W, 0);
            load_w(w0, 0);
            auto odd_stage = [&](int it, bool first, bool last) {
                wg_wait<1>();
                if (!first) release(old);
                load_a1(it);
                load_w(w1, 2 * it + 1);
                peek();
                dot(a0, w0);
                if (last && wg == 1) bar_sync<4, 256>();
                issue1s(a1);
                if (last && wg == 0) bar_arrive<4, 256>();
            };
            issue1(a0, 0);
            #pragma unroll
            for (int it = 0; it < 6; it++) {
                const bool xok = mbar_try(sb + BAR_XFULL + 8 * (it + 1), 0);
                odd_stage(it, it == 0, false);
                wg_wait<2>(); release(old);
                if (!xok) mbar_wait(sb + BAR_XFULL + 8 * (it + 1), 0);
                load_a0(it + 1);
                load_w(w0, 2 * it + 2);
                peek();
                dot(a1, w1);
                issue1(a0, 1);
            }
            odd_stage(6, false, true);
            wg_wait<2>(); release(old);
            load_a0(0);
            peek();
            dot(a1, w1);
            wg_wait<1>();
            reg_fence(ag);
            #pragma unroll
            for (int i = 0; i < 32; i++) hp[i] = pack_relu_bf16(ag[2 * i], ag[2 * i + 1]);
            reg_fence_part<0, 32>(hp);
            g0 = d0 + d2; g1 = d1 + d3;
        }

        float aq[28], au[64];
        {
            auto issue2 = [&](uint32_t (&a)[8], int sd) {
                const uint32_t b = begin();
                wgmma_rs56<HI128>(aq, a[0], a[1], a[2], a[3], b + LO128, sd);
                wgmma_rs128<HI128>(au, a[0], a[1], a[2], a[3], b + LO128X2 + 128, sd);
                wgmma_rs56<HI128>(aq, a[4], a[5], a[6], a[7], b + LO128 + 384, 1);
                wgmma_rs128<HI128>(au, a[4], a[5], a[6], a[7], b + LO128X2 + 512, 1);
            };
            const uint32_t st_base = wg == 0 ? OFF_STG : OFF_RING + 12288, st_step = wg == 0 ? 2048 : SLOT_BYTES, st_v = wg == 0 ? 8192 : 2048;
            const uint32_t sk = sb + st_base + w4 * st_step + (lane & 15) * 128;
            float tok = kLog2e;
            uint32_t pk[16];
            pk[14] = 0u; pk[15] = 0u;
            auto stage_k = [&](int lo, int hi) {
                #pragma unroll
                for (int i = 0; i < 14; i++) if (i >= lo && i < hi) pk[i] = pack_bf16(phi(ak[2 * i], tok), phi(ak[2 * i + 1], tok));
                #pragma unroll
                for (int t = 0; t < 4; t++) {
                    const int need = t < 3 ? 4 * t + 4 : 14;
                    if (need > lo && need <= hi) stsm4(sk + (lx ^ (t * 32)), pk[4 * t], pk[4 * t + 1], pk[4 * t + 2], pk[4 * t + 3]);
                }
                #pragma unroll
                for (int i = 0; i < 14; i++) if (i >= lo && i < hi) asm volatile("" : "+r"(pk[i]));
            };
            issue2(a0, 0); commit();
            tok = after_issue(kLog2e, zero);
            retire();
            reg_fence(ak); reg_fence(av);
            if (wg == 0) bar_arrive<8, 256>();
            load_a1(0); peek();
            uint32_t pv[14];
            #pragma unroll
            for (int i = 0; i < 14; i++) pv[i] = pack_bf16(av[2 * i], av[2 * i + 1]);
            if (wg == 1) bar_sync<8, 256>();
            {
                const uint32_t ones = q4 == 0 ? 0x3f803f80u : 0u;
                #pragma unroll
                for (int t = 0; t < 3; t++) stsm4(sk + st_v + (lx ^ (t * 32)), pv[4 * t], pv[4 * t + 1], pv[4 * t + 2], pv[4 * t + 3]);
                stsm4(sk + st_v + (lx ^ 96), pv[12], pv[13], ones, ones);
            }
            stage_k(0, 2);
            issue2(a1, 1); commit();
            tok = after_issue(kLog2e, zero);
            retire(); load_a0(1); peek();
            stage_k(2, 5);
            issue2(a0, 1); commit();
            tok = after_issue(kLog2e, zero);
            retire(); load_a1(1); peek();
            stage_k(5, 8);
            issue2(a1, 1); commit();
            tok = after_issue(kLog2e, zero);
            retire(); load_a0(2); peek();
            stage_k(8, 11);
            issue2(a0, 1); commit();
            tok = after_issue(kLog2e, zero);
            retire(); load_a1(2); peek();
            stage_k(11, 14);
            issue2(a1, 1); commit();
            retire(); load_a0(3); peek();
            fence_async_smem();
            if (wg == 0) bar_sync<1, 128>(); else bar_sync<2, 128>();
            float kv[32];
            issue2(a0, 1);
            {
                const uint32_t dk = dsb + LO128 + (st_base >> 4), ds = st_step >> 4, dv = st_v >> 4;
                #pragma unroll
                for (int ks = 0; ks < 4; ks++) wgmma_ss64_tt<HI128>(kv, dk + ks * ds, dk + ks * ds + dv, ks);
            }
            commit();
            tok = after_issue(-kLog2e, zero);
            retire(); load_a1(3); peek();
            {
                g0 += __shfl_xor_sync(0xffffffffu, g0, 1); g1 += __shfl_xor_sync(0xffffffffu, g1, 1);
                g0 += __shfl_xor_sync(0xffffffffu, g0, 2); g1 += __shfl_xor_sync(0xffffffffu, g1, 2);
                float e0, e1;
                asm("ex2.approx.ftz.f32 %0, %1;" : "=f"(e0) : "f"(g0 * tok));
                asm("ex2.approx.ftz.f32 %0, %1;" : "=f"(e1) : "f"(g1 * tok));
                g0 = __fdividef(1.f, 1.f + e0);
                g1 = __fdividef(1.f, 1.f + e1);
                asm volatile("" : "+f"(g0), "+f"(g1));
            }
            issue2(a1, 1); commit();
            retire(); load_a0(4); peek();
            reg_fence(kv);
            if (wg == 0) { bar_arrive<5, 256>(); bar_sync<1, 128>(); } else bar_sync<5, 256>();
            auto stage_kv = [&](int hh) {
                const int d = w4 * 16 + g8 + 8 * hh;
                const bool h0 = d < 28;
                const uint32_t rowa = sb + OFF_STG + wg * 8192 + d * 128 + q4 * 8;
                #pragma unroll
                for (int t = 0; t < 4; t++) {
                    float v0 = h0 ? kv[4 * t + 2 * hh] : kv[4 * t + 12 + 2 * hh];
                    float v1 = h0 ? kv[4 * t + 2 * hh + 1] : kv[4 * t + 13 + 2 * hh];
                    if (t == 0 && !h0 && q4 == 0) v0 = kv[28 + 2 * hh];
                    if (d < 56 && !(t == 3 && h0 && q4 == 2))
                        asm volatile("st.shared.v2.f32 [%0], {%1, %2};" :: "r"(rowa + ((t ^ (g8 & 3)) << 5)), "f"(v0), "f"(v1) : "memory");
                }
                if (h0 && q4 == 0)
                    asm volatile("st.shared.v2.f32 [%0], {%1, %1};" :: "r"(rowa + ((3 ^ (g8 & 3)) << 5) + 16), "f"(kv[28 + 2 * hh]) : "memory");
            };
            stage_kv(0);
            issue2(a0, 1); commit();
            retire(); load_a1(4); peek();
            stage_kv(1);
            __syncwarp();
            if (lane == 0) mbar_arrive(sb + BAR_KVDONE);
            issue2(a1, 1); commit();
            retire(); load_a0(5); peek();
            auto prescale = [&](int lo, int hi) {
                const float t0 = after_issue(1.f - g0, zero), t1 = after_issue(1.f - g1, zero);
                const uint32_t s0 = pack_bf16(t0, t0), s1 = pack_bf16(t1, t1);
                #pragma unroll
                for (int i = 0; i < 32; i++) if (i >= lo && i < hi) { hp[i] = mul_bf16x2(hp[i], (i & 1) ? s1 : s0); asm volatile("" : "+r"(hp[i])); }
            };
            prescale(0, 16);
            issue2(a0, 1); commit();
            retire(); load_a1(5); peek();
            prescale(16, 32);
            issue2(a1, 1); commit();
            retire(); load_a0(6); peek();
            issue2(a0, 1); commit();
            retire(); load_a1(6); peek();
            if (wg == 1) bar_sync<4, 256>();
            const uint32_t b = begin();
            wgmma_rs128<HI128>(au, a1[0], a1[1], a1[2], a1[3], b + LO128X2 + 128, 1);
            wgmma_rs128<HI128>(au, a1[4], a1[5], a1[6], a1[7], b + LO128X2 + 512, 1);
            wg_commit();
            wgmma_rs56<HI128>(aq, a1[0], a1[1], a1[2], a1[3], b + LO128, 1);
            wgmma_rs56<HI128>(aq, a1[4], a1[5], a1[6], a1[7], b + LO128 + 384, 1);
            commit();
            if (wg == 0) bar_arrive<4, 256>();
            wg_wait<2>(); release(old);
            load_a0(0); peek();
            wg_wait<1>();
            reg_fence(au);
        }
        #pragma unroll
        for (int i = 0; i < 32; i++) hp[i] = mul_bf16x2(hp[i], pack_bf16(au[2 * i], au[2 * i + 1]));
        reg_fence_part<0, 32>(hp);

        float ag[96];
        uint32_t op[16];
        {
            auto issue3 = [&](uint32_t (&a)[8], int sd) {
                const uint32_t b = begin();
                wgmma_rs192<HI64>(ag, a[0], a[1], a[2], a[3], b + LO64, sd);
                wgmma_rs192<HI64>(ag, a[4], a[5], a[6], a[7], b + LO64 + 384, 1);
            };
            uint32_t pq[16];
            issue3(a0, 0); commit();
            retire();
            reg_fence(aq);
            load_a1(0); peek();
            pq[14] = 0u; pq[15] = 0u;
            bool aux = false;
            #pragma unroll
            for (int st = 1; st < 12; st++) {
                if (st & 1) issue3(a1, 1); else issue3(a0, 1);
                commit();
                const float tok = st < 8 ? after_issue(kLog2e, zero) : 0.f;
                if (st == 11) aux = mbar_try(sb + BAR_AUX, 0);
                retire();
                if (st & 1) load_a0((st + 1) >> 1); else load_a1(st >> 1);
                peek();
                if (st < 8) {
                    const int i = 2 * st - 2;
                    pq[i] = pack_bf16(phi(aq[2 * i], tok), phi(aq[2 * i + 1], tok));
                    pq[i + 1] = pack_bf16(phi(aq[2 * i + 2], tok), phi(aq[2 * i + 3], tok));
                    asm volatile("" : "+r"(pq[i]), "+r"(pq[i + 1]));
                }
            }
            if (!aux) mbar_wait(sb + BAR_AUX, 0);
            if (wg == 1) bar_sync<4, 256>();
            float nd[32];
            issue3(a0, 1);
            {
                const uint32_t dk = dsb + LO128 + ((OFF_STG + 8192) >> 4);
                #pragma unroll
                for (int ks = 0; ks < 4; ks++) wgmma_rs64<HI128>(nd, pq[4 * ks], pq[4 * ks + 1], pq[4 * ks + 2], pq[4 * ks + 3], dk + ks * 128, ks);
            }
            commit();
            retire(); load_a1(6); peek();
            issue3(a1, 1); commit();
            if (wg == 0) bar_arrive<4, 256>();
            ready = mbar_try(sb + p4_bar(0), p4_par(0));
            retire();
            reg_fence(nd);
            const int src = lane & ~3;
            const float s00 = __fdividef(g0, __shfl_sync(0xffffffffu, nd[28], src) + 1e-6f);
            const float s01 = __fdividef(g0, __shfl_sync(0xffffffffu, nd[29], src) + 1e-6f);
            const float s10 = __fdividef(g1, __shfl_sync(0xffffffffu, nd[30], src) + 1e-6f);
            const float s11 = __fdividef(g1, __shfl_sync(0xffffffffu, nd[31], src) + 1e-6f);
            #pragma unroll
            for (int t = 0; t < 7; t++) {
                const bool h1 = t > 3 || (t == 3 && q4 >= 2);
                const float sa = h1 ? s01 : s00, sc = h1 ? s11 : s10;
                op[2 * t] = pack_bf16(nd[4 * t] * sa, nd[4 * t + 1] * sa);
                op[2 * t + 1] = pack_bf16(nd[4 * t + 2] * sc, nd[4 * t + 3] * sc);
            }
            op[14] = 0u; op[15] = 0u;
            reg_fence(op);
        }

        float oa[32], ob[32];
        int c = j == 7 ? 0 : j;
        const int wsh = __shfl_sync(0xffffffffu, warp * 16, 0);
        const uint32_t sh0 = par * 768, sh1 = par * 1024;
        bool ready2 = false;
        auto issue_d = [&](float (&o)[32], int c0, int half) {
            const int n = 3 * c0;
            if (half == 0) {
                if (!ready) mbar_wait(sb + p4_bar(n), p4_par(n));
                if (!ready2) mbar_wait(sb + p4_bar(n + 1), p4_par(n + 1));
                ready = mbar_try(sb + p4_bar(n + 2), p4_par(n + 2));
            }
            wg_fence();
            const uint32_t b = dsb + LO128 + (p4_off(n) >> 4);
            #pragma unroll
            for (int ks = 7 * half; ks < 7 * half + 7; ks++)
                wgmma_rs64<HI128>(o, hp[4 * ks], hp[4 * ks + 1], hp[4 * ks + 2], hp[4 * ks + 3],
                                  b + ks * 128 + (ks < 8 ? sh0 : 0u - sh1), ks);
        };
        auto issue_o = [&](float (&o)[32], int c0) {
            const int n = 3 * c0 + 2;
            if (!ready) mbar_wait(sb + p4_bar(n), p4_par(n));
            if (c0 < 6) {
                ready = mbar_try(sb + p4_bar(n + 1), p4_par(n + 1));
                ready2 = mbar_try(sb + p4_bar(n + 2), p4_par(n + 2));
            }
            wg_fence();
            const uint32_t b = dsb + LO128 + (p4_off(n) >> 4);
            #pragma unroll
            for (int ks = 0; ks < 4; ks++) wgmma_rs64<HI128>(o, op[4 * ks], op[4 * ks + 1], op[4 * ks + 2], op[4 * ks + 3], b + ks * 128, 1);
            wg_commit();
        };
        auto ship = [&](float (&o)[32], int c0) {
            reg_fence(o);
            const uint32_t so = xa + OFF_OUT + (c0 & 1) * 16384;
            #pragma unroll
            for (int t = 0; t < 4; t++)
                stsm4(so + (lx ^ (t * 32)), pack_bf16(o[8 * t], o[8 * t + 1]), pack_bf16(o[8 * t + 2], o[8 * t + 3]),
                      pack_bf16(o[8 * t + 4], o[8 * t + 5]), pack_bf16(o[8 * t + 6], o[8 * t + 7]));
            fence_async_smem();
            __syncwarp();
            if (elect_one()) {
                tma_reduce2d(&mp.out, sb + OFF_OUT + (c0 & 1) * 16384 + wsh * 128, 64 * c, row0 + wsh);
                asm volatile("cp.async.bulk.commit_group;" ::: "memory");
            }
            if (++c == 7) c = 0;
        };
        auto finish_h = [&]() {
            reg_fence(ag);
            release(cur);
            const float u0 = 1.f - g0, u1 = 1.f - g1;
            #pragma unroll
            for (int i = 0; i < 24; i++) {
                const float u = (i & 1) ? u1 : u0;
                hp[32 + i] = mul_bf16x2(pack_relu_bf16(ag[2 * i], ag[2 * i + 1]), pack_bf16(ag[48 + 2 * i] * u, ag[49 + 2 * i] * u));
            }
            reg_fence_part<32, 56>(hp);
        };
        ready2 = mbar_try(sb + p4_bar(1), p4_par(1));
        wg_wait<0>();
        finish_h();
        #pragma unroll
        for (int c0 = 0; c0 < 7; c0++) {
            float (&o)[32] = (c0 & 1) ? ob : oa;
            if (c0 > 0 || wg == 1) turn_wait();
            issue_d(o, c0, 0);
            issue_d(o, c0, 1);
            issue_o(o, c0);
            if (!(c0 == 6 && wg == 1)) turn_pass();
            if (c0 >= 2) {
                if (elect_one()) asm volatile("cp.async.bulk.wait_group.read 1;" ::: "memory");
                __syncwarp();
            }
            wg_wait<0>();
            if (c0 < 2) { release(3 * c0); release(3 * c0 + 1); release(3 * c0 + 2); }
            ship(o, c0);
        }
        if (elect_one()) asm volatile("cp.async.bulk.wait_group.read 0;" ::: "memory");
    }
}

typedef CUresult (*EncodeFn)(CUtensorMap*, CUtensorMapDataType, cuuint32_t, void*, const cuuint64_t*, const cuuint64_t*,
                             const cuuint32_t*, const cuuint32_t*, CUtensorMapInterleave, CUtensorMapSwizzle,
                             CUtensorMapL2promotion, CUtensorMapFloatOOBfill);

void make_map(EncodeFn enc, CUtensorMap* m, const void* base, int rank, const cuuint64_t* dims, const cuuint64_t* strides,
              cuuint32_t b0, cuuint32_t b1, cuuint32_t b2, CUtensorMapSwizzle sw) {
    const cuuint32_t es[3] = {1, 1, 1}, box[3] = {b0, b1, b2};
    enc(m, CU_TENSOR_MAP_DATA_TYPE_BFLOAT16, rank, const_cast<void*>(base), dims, strides, box, es,
        CU_TENSOR_MAP_INTERLEAVE_NONE, sw, CU_TENSOR_MAP_L2_PROMOTION_L2_128B, CU_TENSOR_MAP_FLOAT_OOB_FILL_NONE);
}

}

extern "C" void kernel_launch(void* const* d_in, const int* in_sizes, int n_in, void* d_out, int out_size) {
    (void)in_sizes; (void)n_in; (void)out_size;
    static EncodeFn enc = nullptr;
    if (!enc) {
        void* fn = nullptr;
        cudaDriverEntryPointQueryResult st;
        cudaGetDriverEntryPoint("cuTensorMapEncodeTiled", &fn, cudaEnableDefault, &st);
        enc = (EncodeFn)fn;
        cudaFuncSetAttribute(fused_kernel, cudaFuncAttributeMaxDynamicSharedMemorySize, SMEM_BYTES);
    }
    Maps mp;
    const cuuint64_t dimx[2] = {kD, kS}, dimd[2] = {kD, kF}, dimo[2] = {kD, kD}, strd[1] = {kD * 2};
    make_map(enc, &mp.x, d_in[0], 2, dimx, strd, 64, 128, 1, CU_TENSOR_MAP_SWIZZLE_128B);
    make_map(enc, &mp.out, d_out, 2, dimx, strd, 64, 16, 1, CU_TENSOR_MAP_SWIZZLE_128B);
    make_map(enc, &mp.d, d_in[6], 2, dimd, strd, 64, 56, 1, CU_TENSOR_MAP_SWIZZLE_128B);
    make_map(enc, &mp.o, d_in[2], 2, dimo, strd, 64, 32, 1, CU_TENSOR_MAP_SWIZZLE_128B);
    const cuuint64_t dimq[3] = {kD, kD, 3}, strq[2] = {3 * kD * 2, kD * 2};
    make_map(enc, &mp.kv, d_in[1], 3, dimq, strq, 56, 16, 2, CU_TENSOR_MAP_SWIZZLE_128B);
    make_map(enc, &mp.q, d_in[1], 3, dimq, strq, 56, 16, 1, CU_TENSOR_MAP_SWIZZLE_128B);
    const cuuint64_t dimf[3] = {32, kD, kF / 32}, strf[2] = {kF * 2, 64};
    const cuuint64_t dimw[3] = {64, kD, kF / 64}, strw[2] = {kF * 2, 128};
    make_map(enc, &mp.g4, d_in[4], 3, dimw, strw, 64, 16, 2, CU_TENSOR_MAP_SWIZZLE_128B);
    make_map(enc, &mp.u4, d_in[5], 3, dimw, strw, 64, 16, 2, CU_TENSOR_MAP_SWIZZLE_128B);
    make_map(enc, &mp.g3, d_in[4], 3, dimf, strf, 32, 16, 3, CU_TENSOR_MAP_SWIZZLE_64B);
    make_map(enc, &mp.u3, d_in[5], 3, dimf, strf, 32, 16, 3, CU_TENSOR_MAP_SWIZZLE_64B);
    fused_kernel<<<NCTA, NTHREADS, SMEM_BYTES>>>(mp, (const __nv_bfloat16*)d_in[7], (__nv_bfloat16*)d_out, 0u);
}
```

```cpp
#include <cuda_runtime.h>
#include <cuda_bf16.h>
#include <cuda.h>
#include <stdint.h>

namespace {

constexpr int kS = 2048, kD = 448, kF = 1792;
constexpr int NTHREADS = 384;
constexpr int NCTA = 128;
constexpr uint32_t OFF_X = 0;
constexpr uint32_t OFF_RING = 114688;
constexpr uint32_t SLOT_BYTES = 16384;
constexpr int NSLOT = 6;
constexpr uint32_t OFF_STG = 212992;
constexpr uint32_t OFF_MISC = 229376;
constexpr uint32_t SMEM_BYTES = 232448;
constexpr uint32_t BAR_FULL = OFF_MISC, BAR_EMPTY = OFF_MISC + 48, BAR_XFULL = OFF_MISC + 96;
constexpr uint32_t BAR_W = OFF_MISC + 152, BAR_KVDONE = OFF_MISC + 160, BAR_AUX = OFF_MISC + 168, BAR_P4 = OFF_MISC + 176;
constexpr uint32_t OFF_W = OFF_MISC + 256;
constexpr uint32_t SB = 1024;

__device__ __align__(128) float g_kvacc[8][2048];
__device__ unsigned int g_counter[64];

__device__ __forceinline__ void mbar_init(uint32_t bar, uint32_t cnt) {
    asm volatile("mbarrier.init.shared::cta.b64 [%0], %1;" :: "r"(bar), "r"(cnt) : "memory");
}
__device__ __forceinline__ void mbar_expect_tx(uint32_t bar, uint32_t bytes) {
    asm volatile("mbarrier.arrive.expect_tx.shared::cta.b64 _, [%0], %1;" :: "r"(bar), "r"(bytes) : "memory");
}
__device__ __forceinline__ void mbar_arrive(uint32_t bar) {
    asm volatile("mbarrier.arrive.shared::cta.b64 _, [%0];" :: "r"(bar) : "memory");
}
__device__ __forceinline__ void mbar_arrive_cluster(uint32_t bar) {
    asm volatile("mbarrier.arrive.shared::cluster.b64 _, [%0];" :: "r"(bar) : "memory");
}
__device__ __forceinline__ void mbar_wait(uint32_t bar, uint32_t parity) {
    asm volatile("{\n"
                 ".reg .pred p;\n"
                 ".reg .u32 c;\n"
                 "mov.u32 c, 0;\n"
                 "AGAIN:\n"
                 "mbarrier.try_wait.parity.shared::cta.b64 p, [%0], %1;\n"
                 "@p bra DONE;\n"
                 "add.u32 c, c, 1;\n"
                 "setp.lt.u32 p, c, 4194304;\n"
                 "@p bra AGAIN;\n"
                 "trap;\n"
                 "DONE:\n"
                 "}" :: "r"(bar), "r"(parity) : "memory");
}
__device__ __forceinline__ uint32_t mapa(uint32_t addr, uint32_t cta) {
    uint32_t r; asm("mapa.shared::cluster.u32 %0, %1, %2;" : "=r"(r) : "r"(addr), "r"(cta)); return r;
}
__device__ __forceinline__ bool elect_one() {
    uint32_t p;
    asm volatile("{ .reg .pred P; elect.sync _|P, 0xffffffff; selp.u32 %0, 1, 0, P; }" : "=r"(p));
    return p;
}
__device__ __forceinline__ void tma2d(uint32_t dst, const CUtensorMap* m, int c0, int c1, uint32_t bar) {
    asm volatile("cp.async.bulk.tensor.2d.shared::cluster.global.mbarrier::complete_tx::bytes [%0], [%1, {%3, %4}], [%2];"
                 :: "r"(dst), "l"(m), "r"(bar), "r"(c0), "r"(c1) : "memory");
}
__device__ __forceinline__ void tma2d_mc(uint32_t dst, const CUtensorMap* m, int c0, int c1, uint32_t bar) {
    asm volatile("cp.async.bulk.tensor.2d.shared::cluster.global.mbarrier::complete_tx::bytes.multicast::cluster [%0], [%1, {%3, %4}], [%2], %5;"
                 :: "r"(dst), "l"(m), "r"(bar), "r"(c0), "r"(c1), "h"((uint16_t)3) : "memory");
}
__device__ __forceinline__ void tma3d_mc(uint32_t dst, const CUtensorMap* m, int c0, int c1, int c2, uint32_t bar) {
    asm volatile("cp.async.bulk.tensor.3d.shared::cluster.global.mbarrier::complete_tx::bytes.multicast::cluster [%0], [%1, {%3, %4, %5}], [%2], %6;"
                 :: "r"(dst), "l"(m), "r"(bar), "r"(c0), "r"(c1), "r"(c2), "h"((uint16_t)3) : "memory");
}
__device__ __forceinline__ void tma_reduce2d(const CUtensorMap* m, uint32_t src, int c0, int c1) {
    asm volatile("cp.reduce.async.bulk.tensor.2d.global.shared::cta.add.bulk_group [%0, {%2, %3}], [%1];"
                 :: "l"(m), "r"(src), "r"(c0), "r"(c1) : "memory");
}
__device__ __forceinline__ void bulk_reduce_f32(float* dst, uint32_t src, uint32_t bytes) {
    asm volatile("cp.reduce.async.bulk.global.shared::cta.bulk_group.add.f32 [%0], [%1], %2;" :: "l"(dst), "r"(src), "r"(bytes) : "memory");
}
__device__ __forceinline__ bool mbar_try(uint32_t bar, uint32_t parity) {
    uint32_t ok;
    asm volatile("{ .reg .pred p; mbarrier.test_wait.parity.shared::cta.b64 p, [%1], %2; selp.u32 %0, 1, 0, p; }"
                 : "=r"(ok) : "r"(bar), "r"(parity) : "memory");
    return ok;
}
__device__ __forceinline__ void prefetch_map(const CUtensorMap* m) {
    asm volatile("prefetch.tensormap [%0];" :: "l"(m) : "memory");
}
__device__ __forceinline__ void wg_fence() { asm volatile("wgmma.fence.sync.aligned;" ::: "memory"); }
__device__ __forceinline__ void wg_commit() { asm volatile("wgmma.commit_group.sync.aligned;" ::: "memory"); }
template <int N> __device__ __forceinline__ void wg_wait() { asm volatile("wgmma.wait_group.sync.aligned %0;" :: "n"(N) : "memory"); }
template <int N> __device__ __forceinline__ void reg_fence(float (&d)[N]) {
#pragma unroll
    for (int i = 0; i < N; i++) asm volatile("" : "+f"(d[i]) :: "memory");
}
template <int N> __device__ __forceinline__ void reg_fence(uint32_t (&d)[N]) {
#pragma unroll
    for (int i = 0; i < N; i++) asm volatile("" : "+r"(d[i]) :: "memory");
}
template <int LO, int HI, int N> __device__ __forceinline__ void reg_fence_part(uint32_t (&d)[N]) {
#pragma unroll
    for (int i = LO; i < HI; i++) asm volatile("" : "+r"(d[i]) :: "memory");
}
__device__ __forceinline__ void fence_async_smem() { asm volatile("fence.proxy.async.shared::cta;" ::: "memory"); }
template <int ID, int N> __device__ __forceinline__ void bar_sync() { asm volatile("bar.sync %0, %1;" :: "n"(ID), "n"(N) : "memory"); }
template <int ID, int N> __device__ __forceinline__ void bar_arrive() { asm volatile("bar.arrive %0, %1;" :: "n"(ID), "n"(N) : "memory"); }
__device__ __forceinline__ void ldsm4(uint32_t* r, uint32_t addr) {
    asm volatile("ldmatrix.sync.aligned.m8n8.x4.shared.b16 {%0, %1, %2, %3}, [%4];"
                 : "=r"(r[0]), "=r"(r[1]), "=r"(r[2]), "=r"(r[3]) : "r"(addr) : "memory");
}
__device__ __forceinline__ void stsm4(uint32_t addr, uint32_t r0, uint32_t r1, uint32_t r2, uint32_t r3) {
    asm volatile("stmatrix.sync.aligned.m8n8.x4.shared.b16 [%0], {%1, %2, %3, %4};"
                 :: "r"(addr), "r"(r0), "r"(r1), "r"(r2), "r"(r3) : "memory");
}
__device__ __forceinline__ uint32_t lds32(uint32_t addr) {
    uint32_t r; asm volatile("ld.shared.u32 %0, [%1];" : "=r"(r) : "r"(addr)); return r;
}
__device__ __forceinline__ float4 lds128f(uint32_t addr) {
    float4 r; asm volatile("ld.shared.v4.f32 {%0, %1, %2, %3}, [%4];" : "=f"(r.x), "=f"(r.y), "=f"(r.z), "=f"(r.w) : "r"(addr)); return r;
}
__device__ __forceinline__ uint32_t clock32() { uint32_t t; asm volatile("mov.u32 %0, %%clock;" : "=r"(t)); return t; }
__device__ __forceinline__ uint32_t pack_bf16(float lo, float hi) {
    uint32_t r; asm("cvt.rn.bf16x2.f32 %0, %1, %2;" : "=r"(r) : "f"(hi), "f"(lo)); return r;
}
__device__ __forceinline__ uint32_t pack_relu_bf16(float lo, float hi) {
    uint32_t r; asm("cvt.rn.relu.bf16x2.f32 %0, %1, %2;" : "=r"(r) : "f"(hi), "f"(lo)); return r;
}
__device__ __forceinline__ uint32_t mul_bf16x2(uint32_t a, uint32_t b) {
    uint32_t r; asm("mul.rn.bf16x2 %0, %1, %2;" : "=r"(r) : "r"(a), "r"(b)); return r;
}
__device__ __forceinline__ uint32_t fma_bf16x2(uint32_t a, uint32_t b, uint32_t c) {
    uint32_t r; asm("fma.rn.bf16x2 %0, %1, %2, %3;" : "=r"(r) : "r"(a), "r"(b), "r"(c)); return r;
}
__device__ __forceinline__ float phi(float t, float log2e) {
    float e;
    asm("ex2.approx.ftz.f32 %0, %1;" : "=f"(e) : "f"(fminf(t * log2e, 0.f)));
    return e + (fmaxf(t, 0.f) + 1e-6f);
}
__device__ __forceinline__ float after_issue(float v, uint32_t zero) {
    return __uint_as_float(__float_as_uint(v) | (clock32() & zero));
}
constexpr float kLog2e = 1.4426950408889634f;
__device__ __forceinline__ float bf_lo(uint32_t v) { return __uint_as_float(v << 16); }
__device__ __forceinline__ float bf_hi(uint32_t v) { return __uint_as_float(v & 0xffff0000u); }
constexpr uint32_t HI128 = (1024 >> 4) | (1u << 30);
constexpr uint32_t HI64 = (512 >> 4) | (2u << 30);
constexpr uint32_t LO128 = 1u << 16, LO64 = (1024u >> 4) << 16, LO128X2 = (2048u >> 4) << 16;
constexpr uint32_t QB = 16 * 112;
constexpr uint32_t TX1 = 2 * (2 * QB + 4096), TX2 = 2 * (QB + 4096), TX3 = 12288;
__device__ __forceinline__ void grid_arrive(unsigned int* c) {
    asm volatile("fence.acq_rel.gpu;" ::: "memory");
    asm volatile("red.relaxed.gpu.global.add.u32 [%0], 1;" :: "l"(c) : "memory");
}
__device__ __forceinline__ void grid_wait(const unsigned int* c, unsigned int target) {
    unsigned int v; int it = 0;
    do {
        asm volatile("ld.relaxed.gpu.global.u32 %0, [%1];" : "=r"(v) : "l"(c) : "memory");
        if (++it > (1 << 22)) asm volatile("trap;");
    } while ((int)(v - target) < 0);
    asm volatile("ld.acquire.gpu.global.u32 %0, [%1];" : "=r"(v) : "l"(c) : "memory");
}


__host__ __device__ constexpr uint32_t p4_pack(int n) { return (n / 3) * 36864 + (n % 3) * 14336; }
__host__ __device__ constexpr uint32_t p4_off(int n) {
    return n < 6 ? OFF_X + p4_pack(n) : n < 14 ? OFF_RING + p4_pack(n - 6) : n == 14 ? OFF_X + p4_pack(6) : OFF_X + p4_pack(n - 15);
}
__host__ __device__ constexpr uint32_t p4_bar(int n) {
    return n < 6 ? BAR_XFULL + 8 * n : n < 12 ? BAR_FULL + 8 * (n - 6) : n < 14 ? BAR_P4 + 8 * (n - 12)
                 : n == 14 ? BAR_XFULL + 48 : BAR_XFULL + 8 * (n - 15);
}
__host__ __device__ constexpr uint32_t p4_par(int n) { return (n < 12 || n == 14) ? 1 : 0; }
constexpr uint32_t OFF_OUT = OFF_X + 5 * 16384;
static_assert(p4_off(7) == p4_off(6) + 14336 && p4_off(13) == p4_off(12) + 14336 && p4_off(16) == p4_off(15) + 14336, "Wd halves");
static_assert(p4_off(13) + 14336 <= OFF_STG + 8192 && p4_off(14) + 8192 == OFF_OUT, "pass-4 layout");

struct Ring {
    uint32_t slot, phase;
    __device__ __forceinline__ void advance() { if (++slot == NSLOT) { slot = 0; phase ^= 1; } }
};

struct Maps { CUtensorMap x, kv, q, g4, g3, u4, u3, d, o, out; };

__global__ void __cluster_dims__(2, 1, 1) __launch_bounds__(NTHREADS, 1)
fused_kernel(const __grid_constant__ Maps mp, const __nv_bfloat16* __restrict__ gate_w, __nv_bfloat16* __restrict__ out,
             uint32_t zero)
{
    extern __shared__ __align__(1024) unsigned char smem[];
    const uint32_t sb = (uint32_t)__cvta_generic_to_shared(smem);
    const int tid = threadIdx.x, warp = tid >> 5, lane = tid & 31;
    const int rank = blockIdx.x & 1, j = (blockIdx.x >> 1) & 7;
    const int row0 = ((blockIdx.x >> 4) * 2 + rank) * 128;
    const int par = j & 1;
    const int g4i = (7 * j + 3 * par) >> 1;

    if (warp == 9) {
        if (elect_one()) {
            prefetch_map(&mp.x);
            mbar_init(sb + BAR_XFULL, 1);
            mbar_expect_tx(sb + BAR_XFULL, 16384);
            tma2d(sb + OFF_X, &mp.x, 0, row0, sb + BAR_XFULL);
            asm volatile("fence.mbarrier_init.release.cluster;" ::: "memory");
        }
        __syncwarp();
    } else if (warp == 8) {
        if (elect_one()) {
            #pragma unroll
            for (int s = 0; s < NSLOT; s++) mbar_init(sb + BAR_FULL + 8 * s, 1);
            asm volatile("fence.mbarrier_init.release.cluster;" ::: "memory");
            mbar_expect_tx(sb + BAR_FULL, TX1);
        }
        __syncwarp();
    } else if (warp == 10) {
        if (elect_one()) {
            #pragma unroll
            for (int s = 1; s < 7; s++) mbar_init(sb + BAR_XFULL + 8 * s, 1);
            mbar_init(sb + BAR_KVDONE, 8);
            mbar_init(sb + BAR_AUX, 3);
            asm volatile("fence.mbarrier_init.release.cluster;" ::: "memory");
            if ((sb & 0xFFFFFF) != SB) asm volatile("trap;");
        }
        __syncwarp();
    } else if (warp == 11) {
        if (elect_one()) {
            #pragma unroll
            for (int s = 0; s < NSLOT; s++) mbar_init(sb + BAR_EMPTY + 8 * s, 4);
            mbar_init(sb + BAR_P4, 1);
            mbar_init(sb + BAR_P4 + 8, 1);
            asm volatile("fence.mbarrier_init.release.cluster;" ::: "memory");
        }
        __syncwarp();
    } else if (warp == 2) {
        if (elect_one()) {
            mbar_init(sb + BAR_W, 1);
            asm volatile("fence.mbarrier_init.release.cluster;" ::: "memory");
            mbar_expect_tx(sb + BAR_W, 896);
            asm volatile("cp.async.bulk.shared::cluster.global.mbarrier::complete_tx::bytes [%0], [%1], 896, [%2];"
                         :: "r"(sb + OFF_W), "l"(gate_w), "r"(sb + BAR_W) : "memory");
        }
        __syncwarp();
    }
    asm volatile("barrier.cluster.arrive.relaxed.aligned;" ::: "memory");
    if (warp == 8) {
        if (elect_one()) { prefetch_map(&mp.kv); prefetch_map(&mp.g4); }
        __syncwarp();
    }
    asm volatile("barrier.cluster.wait.aligned;" ::: "memory");
    if (warp == 8) {
        if (elect_one()) {
            tma3d_mc(sb + OFF_RING + rank * 8192, &mp.kv, 56 * j, 16 * rank, 1, sb + BAR_FULL);
            tma3d_mc(sb + OFF_RING + rank * 8192 + 4096, &mp.g4, 0, 16 * rank, g4i, sb + BAR_FULL);
        }
        __syncwarp();
    }

    if (warp >= 8) {
        asm volatile("setmaxnreg.dec.sync.aligned.u32 40;");
        if (warp == 8) {
            if (elect_one()) {
                Ring r{1, 1};
                auto acquire = [&](uint32_t bytes) -> uint32_t {
                    mbar_wait(sb + BAR_EMPTY + 8 * r.slot, r.phase);
                    mbar_expect_tx(sb + BAR_FULL + 8 * r.slot, bytes);
                    return sb + OFF_RING + r.slot * SLOT_BYTES;
                };
                #pragma unroll 1
                for (int s = 1; s < 14; s++) {
                    const uint32_t dst = acquire(TX1) + rank * 8192;
                    tma3d_mc(dst, &mp.kv, 56 * j, 32 * s + 16 * rank, 1, sb + BAR_FULL + 8 * r.slot);
                    tma3d_mc(dst + 4096, &mp.g4, 0, 32 * s + 16 * rank, g4i, sb + BAR_FULL + 8 * r.slot);
                    r.advance();
                    if ((s & 1) && s < 12) {
                        const int n = (s >> 1) + 1;
                        mbar_expect_tx(sb + BAR_XFULL + 8 * n, 16384);
                        tma2d(sb + OFF_X + n * 16384, &mp.x, 64 * n, row0, sb + BAR_XFULL + 8 * n);
                    }
                    if (s == 5) {
                        prefetch_map(&mp.q); prefetch_map(&mp.u4); prefetch_map(&mp.g3); prefetch_map(&mp.u3);
                        prefetch_map(&mp.d); prefetch_map(&mp.o); prefetch_map(&mp.out);
                    }
                }
                #pragma unroll 1
                for (int s = 0; s < 14; s++) {
                    const uint32_t dst = acquire(TX2) + rank * 6144;
                    tma3d_mc(dst, &mp.q, 56 * j, 32 * s + 16 * rank, 0, sb + BAR_FULL + 8 * r.slot);
                    tma3d_mc(dst + 2048, &mp.u4, 0, 32 * s + 16 * rank, g4i, sb + BAR_FULL + 8 * r.slot);
                    r.advance();
                }
                const int cfirst = j == 7 ? 0 : j;
                auto load4 = [&](int n) {
                    int c = cfirst + n / 3;
                    if (c >= 7) c -= 7;
                    mbar_expect_tx(sb + p4_bar(n), n % 3 == 2 ? 8192 : 14336);
                    if (n % 3 == 2) tma2d_mc(sb + p4_off(n) + rank * 4096, &mp.o, 64 * c, 56 * j + 32 * rank, sb + p4_bar(n));
                    else tma2d_mc(sb + p4_off(n) + rank * 7168, &mp.d, 64 * c, 224 * j + 112 * (n % 3) + 56 * rank, sb + p4_bar(n));
                };
                #pragma unroll 1
                for (int s = 0; s < 14; s++) {
                    const uint32_t dst = acquire(TX3) + rank * 6144;
                    tma3d_mc(dst, &mp.g3, 0, 32 * s + 16 * rank, 7 * j + 4 - 4 * par, sb + BAR_FULL + 8 * r.slot);
                    tma3d_mc(dst + 3072, &mp.u3, 0, 32 * s + 16 * rank, 7 * j + 4 - 4 * par, sb + BAR_FULL + 8 * r.slot);
                    r.advance();
                    if (s == 7) load4(0);
                    if (s == 9) load4(1);
                    if (s == 11) load4(2);
                    if (s == 13) { load4(3); load4(4); }
                }
                mbar_wait(sb + BAR_EMPTY, 0);      load4(6);
                mbar_wait(sb + BAR_EMPTY + 8, 0);  load4(5); load4(7); load4(14);
                mbar_wait(sb + BAR_EMPTY + 16, 0); load4(8);
                mbar_wait(sb + BAR_EMPTY + 24, 0); load4(9); load4(10);
                mbar_wait(sb + BAR_EMPTY + 32, 0); load4(11);
                mbar_wait(sb + BAR_EMPTY + 40, 0); load4(12);
                mbar_wait(sb + BAR_AUX, 0);        load4(13);
                #pragma unroll
                for (int n = 15; n < 21; n++) {
                    mbar_wait(sb + BAR_EMPTY + 8 * (n - 15), 1);
                    __nanosleep(100);
                    load4(n);
                }
            }
        } else {
            const int ht = tid - 288;
            unsigned int cnt0;
            asm volatile("ld.relaxed.gpu.global.u32 %0, [%1];" : "=r"(cnt0) : "l"(&g_counter[32]) : "memory");
            const unsigned int target = ((cnt0 >> 7) + 1) << 7;
            if (warp == 9) {
                reinterpret_cast<float4*>(&g_kvacc[0][0])[blockIdx.x * 32 + lane] = make_float4(0.f, 0.f, 0.f, 0.f);
                asm volatile("fence.proxy.async.global;" ::: "memory");
                __syncwarp();
                if (lane == 0) grid_arrive(&g_counter[0]);
                mbar_wait(sb + BAR_XFULL + 8 * 6, 0);
                uint4* o = reinterpret_cast<uint4*>(out) + blockIdx.x * 896 + lane;
                #pragma unroll 4
                for (int q = 0; q < 28; q++) o[q * 32] = make_uint4(0, 0, 0, 0);
                asm volatile("fence.proxy.async.global;" ::: "memory");
                __syncwarp();
                if (lane == 0) {
                    asm volatile("fence.acq_rel.gpu;" ::: "memory");
                    grid_wait(&g_counter[0], target);
                }
                __syncwarp();
            }
            mbar_wait(sb + BAR_KVDONE, 0);
            {
                #pragma unroll
                for (int i0 = 0; i0 < 5; i0 += 2) {
                    float4 pa[2], pb[2];
                    #pragma unroll
                    for (int i = 0; i < 2 && i0 + i < 5; i++) {
                        const int q = min(ht + 96 * (i0 + i), 447);
                        pa[i] = lds128f(sb + OFF_STG + q * 16); pb[i] = lds128f(sb + OFF_STG + 8192 + q * 16);
                    }
                    #pragma unroll
                    for (int i = 0; i < 2 && i0 + i < 5; i++) {
                        const int q = ht + 96 * (i0 + i);
                        if (q < 448) asm volatile("st.shared.v4.f32 [%0], {%1, %2, %3, %4};" :: "r"(sb + OFF_STG + q * 16),
                            "f"(pa[i].x + pb[i].x), "f"(pa[i].y + pb[i].y), "f"(pa[i].z + pb[i].z), "f"(pa[i].w + pb[i].w) : "memory");
                    }
                }
                fence_async_smem();
            }
            bar_sync<3, 96>();
            if (warp == 9) {
                if (elect_one()) {
                    bulk_reduce_f32(&g_kvacc[j][0], sb + OFF_STG, 7168);
                    asm volatile("cp.async.bulk.commit_group;" ::: "memory");
                    asm volatile("cp.async.bulk.wait_group 0;" ::: "memory");
                    asm volatile("red.relaxed.gpu.global.add.u32 [%0], 1;" :: "l"(&g_counter[32]) : "memory");
                }
            }
            __syncwarp();
            #pragma unroll
            for (int i = 0; i < 3; i++) {
                const int q = ht + 96 * i;
                const int d = q < 168 ? q / 3 : 56 + ((q - 168) >> 3);
                const int c = q < 168 ? (q - 3 * d + (d < 28 ? 4 : 0)) : (q & 7);
                if (q < 232) asm volatile("st.shared.v4.u32 [%0], {%1, %1, %1, %1};" :: "r"(sb + OFF_STG + 8192 + d * 128 + ((c ^ (d & 7)) << 4)), "r"(0) : "memory");
            }
            uint32_t plan[3];
            #pragma unroll
            for (int i = 0; i < 3; i++) {
                const int q = min(ht + 96 * i, 279), d = q / 5, m = q - 5 * d;
                const bool h0 = d < 28;
                const int c = m == 4 ? 7 : (h0 ? m : m + 3), pc = m < 4 ? m : (h0 ? 3 : 0);
                const int kind = m == 4 ? (h0 ? 3 : 4) : c == 3 ? (h0 ? 1 : 2) : 0;
                plan[i] = (d * 128 + ((c ^ (d & 7)) << 4)) | ((d * 4 + (pc ^ (d & 3))) << 13) | (kind << 23);
                asm volatile("" : "+r"(plan[i]));
            }
            if (lane == 0) grid_wait(&g_counter[32], target);
            __syncwarp();
            const float4* src = reinterpret_cast<const float4*>(&g_kvacc[j][0]);
            float4 va[3], vb[3];
            #pragma unroll
            for (int i = 0; i < 3; i++) {
                const float4* p = src + ((plan[i] >> 12) & 0x7fe);
                va[i] = __ldcg(p); vb[i] = __ldcg(p + 1);
            }
            #pragma unroll
            for (int i = 0; i < 3; i++) {
                const uint32_t kind = plan[i] >> 23;
                uint32_t w0 = pack_bf16(va[i].x, va[i].y), w1 = pack_bf16(va[i].z, va[i].w);
                uint32_t w2 = pack_bf16(vb[i].x, vb[i].y), w3 = pack_bf16(vb[i].z, vb[i].w);
                if (kind == 3) w0 = w2 & 0xffffu;
                if (kind == 4) w0 <<= 16;
                if (kind == 2) w0 = 0u;
                if (kind >= 2) w1 = 0u;
                if (kind != 0 && kind != 2) w2 = w3 = 0u;
                if (i < 2 || ht < 88)
                    asm volatile("st.shared.v4.u32 [%0], {%1, %2, %3, %4};"
                                 :: "r"(sb + OFF_STG + 8192 + (plan[i] & 0x1fff)), "r"(w0), "r"(w1), "r"(w2), "r"(w3) : "memory");
            }
            fence_async_smem();
            __syncwarp();
            if (lane == 0) mbar_arrive(sb + BAR_AUX);
        }
    } else {
        asm volatile("setmaxnreg.inc.sync.aligned.u32 232;");
        const int wg = warp >> 2, w4 = warp & 3;
        const int q4 = lane & 3, g8 = lane >> 2;
        const uint32_t lx = ((lane >> 4) ^ (lane & 7)) << 4;
        const uint32_t xa = sb + OFF_X + (warp * 16 + (lane & 15)) * 128;
        const uint32_t empty_dst = mapa(sb + BAR_EMPTY, w4 & 1);
        const bool signaller = lane == 0 && w4 < 2;
        constexpr uint32_t dsb = SB >> 4;
        Ring r{0, 0};
        uint32_t cur = 0, old = 0;
        bool ready = false;
        auto release = [&](uint32_t slot) { if (signaller) mbar_arrive_cluster(empty_dst + 8 * slot); };
        auto turn_wait = [&]() { if (wg == 0) bar_sync<6, 256>(); else bar_sync<7, 256>(); };
        auto turn_pass = [&]() { if (wg == 0) bar_arrive<7, 256>(); else bar_arrive<6, 256>(); };
        auto begin = [&]() -> uint32_t {
            if (!ready) mbar_wait(sb + BAR_FULL + 8 * r.slot, r.phase);
            wg_fence();
            return dsb + (OFF_RING >> 4) + r.slot * (SLOT_BYTES >> 4);
        };
        auto commit = [&]() { wg_commit(); old = cur; cur = r.slot; r.advance(); };
        auto retire = [&]() { wg_wait<1>(); release(old); };
        auto peek = [&]() { ready = mbar_try(sb + BAR_FULL + 8 * r.slot, r.phase); };
        uint32_t a0[8], a1[8];
        auto load_a0 = [&](int kc) { ldsm4(a0, xa + kc * 16384 + lx); ldsm4(a0 + 4, xa + kc * 16384 + (lx ^ 32)); };
        auto load_a1 = [&](int kc) { ldsm4(a1, xa + kc * 16384 + (lx ^ 64)); ldsm4(a1 + 4, xa + kc * 16384 + (lx ^ 96)); };

        uint32_t hp[56];
        float g0, g1, ak[28], av[28];
        {
            float ag[64];
            float d0 = 0.f, d1 = 0.f, d2 = 0.f, d3 = 0.f;
            uint32_t w0[4], w1[4];
            auto issue1 = [&](uint32_t (&a)[8], int sd) {
                const uint32_t b = begin();
                wgmma_rs56<HI128>(ak, a[0], a[1], a[2], a[3], b + LO128, sd);
                wgmma_rs56<HI128>(av, a[0], a[1], a[2], a[3], b + LO128 + 128, sd);
                wgmma_rs128<HI128>(ag, a[0], a[1], a[2], a[3], b + LO128X2 + 256, sd);
                wgmma_rs56<HI128>(ak, a[4], a[5], a[6], a[7], b + LO128 + 512, 1);
                wgmma_rs56<HI128>(av, a[4], a[5], a[6], a[7], b + LO128 + 640, 1);
                wgmma_rs128<HI128>(ag, a[4], a[5], a[6], a[7], b + LO128X2 + 768, 1);
                commit();
            };
            auto issue1s = [&](uint32_t (&a)[8]) {
                const uint32_t b = begin();
                wgmma_rs128<HI128>(ag, a[0], a[1], a[2], a[3], b + LO128X2 + 256, 1);
                wgmma_rs128<HI128>(ag, a[4], a[5], a[6], a[7], b + LO128X2 + 768, 1);
                wg_commit();
                wgmma_rs56<HI128>(ak, a[0], a[1], a[2], a[3], b + LO128, 1);
                wgmma_rs56<HI128>(av, a[0], a[1], a[2], a[3], b + LO128 + 128, 1);
                wgmma_rs56<HI128>(ak, a[4], a[5], a[6], a[7], b + LO128 + 512, 1);
                wgmma_rs56<HI128>(av, a[4], a[5], a[6], a[7], b + LO128 + 640, 1);
                commit();
            };
            auto load_w = [&](uint32_t (&w)[4], int s) {
                #pragma unroll
                for (int e = 0; e < 4; e++) w[e] = lds32(sb + OFF_W + s * 64 + q4 * 4 + e * 16);
            };
            auto dot = [&](uint32_t (&a)[8], uint32_t (&w)[4]) {
                uint32_t p0 = mul_bf16x2(a[0], w[0]), p1 = mul_bf16x2(a[1], w[0]);
                #pragma unroll
                for (int e = 1; e < 4; e++) { p0 = fma_bf16x2(a[2 * e], w[e], p0); p1 = fma_bf16x2(a[2 * e + 1], w[e], p1); }
                d0 += bf_lo(p0); d2 += bf_hi(p0); d1 += bf_lo(p1); d3 += bf_hi(p1);
                asm volatile("" : "+f"(d0), "+f"(d1), "+f"(d2), "+f"(d3));
            };
            mbar_wait(sb + BAR_XFULL, 0);
            load_a0(0);
            mbar_wait(sb + BAR_W, 0);
            load_w(w0, 0);
            auto odd_stage = [&](int it, bool first, bool last) {
                wg_wait<1>();
                if (!first) release(old);
                load_a1(it);
                load_w(w1, 2 * it + 1);
                peek();
                dot(a0, w0);
                if (last && wg == 1) bar_sync<4, 256>();
                issue1s(a1);
                if (last && wg == 0) bar_arrive<4, 256>();
            };
            issue1(a0, 0);
            #pragma unroll
            for (int it = 0; it < 6; it++) {
                const bool xok = mbar_try(sb + BAR_XFULL + 8 * (it + 1), 0);
                odd_stage(it, it == 0, false);
                wg_wait<2>(); release(old);
                if (!xok) mbar_wait(sb + BAR_XFULL + 8 * (it + 1), 0);
                load_a0(it + 1);
                load_w(w0, 2 * it + 2);
                peek();
                dot(a1, w1);
                issue1(a0, 1);
            }
            odd_stage(6, false, true);
            wg_wait<2>(); release(old);
            load_a0(0);
            peek();
            dot(a1, w1);
            wg_wait<1>();
            reg_fence(ag);
            #pragma unroll
            for (int i = 0; i < 32; i++) hp[i] = pack_relu_bf16(ag[2 * i], ag[2 * i + 1]);
            reg_fence_part<0, 32>(hp);
            g0 = d0 + d2; g1 = d1 + d3;
        }

        float aq[28], au[64];
        {
            auto issue2 = [&](uint32_t (&a)[8], int sd) {
                const uint32_t b = begin();
                wgmma_rs56<HI128>(aq, a[0], a[1], a[2], a[3], b + LO128, sd);
                wgmma_rs128<HI128>(au, a[0], a[1], a[2], a[3], b + LO128X2 + 128, sd);
                wgmma_rs56<HI128>(aq, a[4], a[5], a[6], a[7], b + LO128 + 384, 1);
                wgmma_rs128<HI128>(au, a[4], a[5], a[6], a[7], b + LO128X2 + 512, 1);
            };
            const uint32_t st_base = wg == 0 ? OFF_STG : OFF_RING + 12288, st_step = wg == 0 ? 2048 : SLOT_BYTES, st_v = wg == 0 ? 8192 : 2048;
            const uint32_t sk = sb + st_base + w4 * st_step + (lane & 15) * 128;
            float tok = kLog2e;
            uint32_t pk[16];
            pk[14] = 0u; pk[15] = 0u;
            auto stage_k = [&](int lo, int hi) {
                #pragma unroll
                for (int i = 0; i < 14; i++) if (i >= lo && i < hi) pk[i] = pack_bf16(phi(ak[2 * i], tok), phi(ak[2 * i + 1], tok));
                #pragma unroll
                for (int t = 0; t < 4; t++) {
                    const int need = t < 3 ? 4 * t + 4 : 14;
                    if (need > lo && need <= hi) stsm4(sk + (lx ^ (t * 32)), pk[4 * t], pk[4 * t + 1], pk[4 * t + 2], pk[4 * t + 3]);
                }
                #pragma unroll
                for (int i = 0; i < 14; i++) if (i >= lo && i < hi) asm volatile("" : "+r"(pk[i]));
            };
            issue2(a0, 0); commit();
            tok = after_issue(kLog2e, zero);
            retire();
            reg_fence(ak); reg_fence(av);
            if (wg == 0) bar_arrive<8, 256>();
            load_a1(0); peek();
            uint32_t pv[14];
            #pragma unroll
            for (int i = 0; i < 14; i++) pv[i] = pack_bf16(av[2 * i], av[2 * i + 1]);
            if (wg == 1) bar_sync<8, 256>();
            {
                const uint32_t ones = q4 == 0 ? 0x3f803f80u : 0u;
                #pragma unroll
                for (int t = 0; t < 3; t++) stsm4(sk + st_v + (lx ^ (t * 32)), pv[4 * t], pv[4 * t + 1], pv[4 * t + 2], pv[4 * t + 3]);
                stsm4(sk + st_v + (lx ^ 96), pv[12], pv[13], ones, ones);
            }
            stage_k(0, 2);
            issue2(a1, 1); commit();
            tok = after_issue(kLog2e, zero);
            retire(); load_a0(1); peek();
            stage_k(2, 5);
            issue2(a0, 1); commit();
            tok = after_issue(kLog2e, zero);
            retire(); load_a1(1); peek();
            stage_k(5, 8);
            issue2(a1, 1); commit();
            tok = after_issue(kLog2e, zero);
            retire(); load_a0(2); peek();
            stage_k(8, 11);
            issue2(a0, 1); commit();
            tok = after_issue(kLog2e, zero);
            retire(); load_a1(2); peek();
            stage_k(11, 14);
            issue2(a1, 1); commit();
            retire(); load_a0(3); peek();
            fence_async_smem();
            if (wg == 0) bar_sync<1, 128>(); else bar_sync<2, 128>();
            float kv[32];
            issue2(a0, 1);
            {
                const uint32_t dk = dsb + LO128 + (st_base >> 4), ds = st_step >> 4, dv = st_v >> 4;
                #pragma unroll
                for (int ks = 0; ks < 4; ks++) wgmma_ss64_tt<HI128>(kv, dk + ks * ds, dk + ks * ds + dv, ks);
            }
            commit();
            tok = after_issue(-kLog2e, zero);
            retire(); load_a1(3); peek();
            {
                g0 += __shfl_xor_sync(0xffffffffu, g0, 1); g1 += __shfl_xor_sync(0xffffffffu, g1, 1);
                g0 += __shfl_xor_sync(0xffffffffu, g0, 2); g1 += __shfl_xor_sync(0xffffffffu, g1, 2);
                const uint32_t lg = pack_bf16(g0, g1);
                float e0, e1;
                asm("ex2.approx.ftz.f32 %0, %1;" : "=f"(e0) : "f"(bf_lo(lg) * tok));
                asm("ex2.approx.ftz.f32 %0, %1;" : "=f"(e1) : "f"(bf_hi(lg) * tok));
                const uint32_t gg = pack_bf16(__fdividef(1.f, 1.f + e0), __fdividef(1.f, 1.f + e1));
                g0 = bf_lo(gg); g1 = bf_hi(gg);
                asm volatile("" : "+f"(g0), "+f"(g1));
            }
            issue2(a1, 1); commit();
            retire(); load_a0(4); peek();
            reg_fence(kv);
            if (wg == 0) { bar_arrive<5, 256>(); bar_sync<1, 128>(); } else bar_sync<5, 256>();
            auto stage_kv = [&](int hh) {
                const int d = w4 * 16 + g8 + 8 * hh;
                const bool h0 = d < 28;
                const uint32_t rowa = sb + OFF_STG + wg * 8192 + d * 128 + q4 * 8;
                #pragma unroll
                for (int t = 0; t < 4; t++) {
                    float v0 = h0 ? kv[4 * t + 2 * hh] : kv[4 * t + 12 + 2 * hh];
                    float v1 = h0 ? kv[4 * t + 2 * hh + 1] : kv[4 * t + 13 + 2 * hh];
                    if (t == 0 && !h0 && q4 == 0) v0 = kv[28 + 2 * hh];
                    if (d < 56 && !(t == 3 && h0 && q4 == 2))
                        asm volatile("st.shared.v2.f32 [%0], {%1, %2};" :: "r"(rowa + ((t ^ (g8 & 3)) << 5)), "f"(v0), "f"(v1) : "memory");
                }
                if (h0 && q4 == 0)
                    asm volatile("st.shared.v2.f32 [%0], {%1, %1};" :: "r"(rowa + ((3 ^ (g8 & 3)) << 5) + 16), "f"(kv[28 + 2 * hh]) : "memory");
            };
            stage_kv(0);
            issue2(a0, 1); commit();
            retire(); load_a1(4); peek();
            stage_kv(1);
            __syncwarp();
            if (lane == 0) mbar_arrive(sb + BAR_KVDONE);
            issue2(a1, 1); commit();
            retire(); load_a0(5); peek();
            auto prescale = [&](int lo, int hi) {
                const float t0 = after_issue(1.f - g0, zero), t1 = after_issue(1.f - g1, zero);
                const uint32_t s0 = pack_bf16(t0, t0), s1 = pack_bf16(t1, t1);
                #pragma unroll
                for (int i = 0; i < 32; i++) if (i >= lo && i < hi) { hp[i] = mul_bf16x2(hp[i], (i & 1) ? s1 : s0); asm volatile("" : "+r"(hp[i])); }
            };
            prescale(0, 16);
            issue2(a0, 1); commit();
            retire(); load_a1(5); peek();
            prescale(16, 32);
            issue2(a1, 1); commit();
            retire(); load_a0(6); peek();
            issue2(a0, 1); commit();
            retire(); load_a1(6); peek();
            if (wg == 1) bar_sync<4, 256>();
            const uint32_t b = begin();
            wgmma_rs128<HI128>(au, a1[0], a1[1], a1[2], a1[3], b + LO128X2 + 128, 1);
            wgmma_rs128<HI128>(au, a1[4], a1[5], a1[6], a1[7], b + LO128X2 + 512, 1);
            wg_commit();
            wgmma_rs56<HI128>(aq, a1[0], a1[1], a1[2], a1[3], b + LO128, 1);
            wgmma_rs56<HI128>(aq, a1[4], a1[5], a1[6], a1[7], b + LO128 + 384, 1);
            commit();
            if (wg == 0) bar_arrive<4, 256>();
            wg_wait<2>(); release(old);
            load_a0(0); peek();
            wg_wait<1>();
            reg_fence(au);
        }
        #pragma unroll
        for (int i = 0; i < 32; i++) hp[i] = mul_bf16x2(hp[i], pack_bf16(au[2 * i], au[2 * i + 1]));
        reg_fence_part<0, 32>(hp);

        float ag[96];
        uint32_t op[16];
        {
            auto issue3 = [&](uint32_t (&a)[8], int sd) {
                const uint32_t b = begin();
                wgmma_rs192<HI64>(ag, a[0], a[1], a[2], a[3], b + LO64, sd);
                wgmma_rs192<HI64>(ag, a[4], a[5], a[6], a[7], b + LO64 + 384, 1);
            };
            uint32_t pq[16];
            issue3(a0, 0); commit();
            retire();
            reg_fence(aq);
            load_a1(0); peek();
            pq[14] = 0u; pq[15] = 0u;
            bool aux = false;
            #pragma unroll
            for (int st = 1; st < 12; st++) {
                if (st & 1) issue3(a1, 1); else issue3(a0, 1);
                commit();
                const float tok = st < 8 ? after_issue(kLog2e, zero) : 0.f;
                if (st == 11) aux = mbar_try(sb + BAR_AUX, 0);
                retire();
                if (st & 1) load_a0((st + 1) >> 1); else load_a1(st >> 1);
                peek();
                if (st < 8) {
                    const int i = 2 * st - 2;
                    pq[i] = pack_bf16(phi(aq[2 * i], tok), phi(aq[2 * i + 1], tok));
                    pq[i + 1] = pack_bf16(phi(aq[2 * i + 2], tok), phi(aq[2 * i + 3], tok));
                    asm volatile("" : "+r"(pq[i]), "+r"(pq[i + 1]));
                }
            }
            if (!aux) mbar_wait(sb + BAR_AUX, 0);
            if (wg == 1) bar_sync<4, 256>();
            float nd[32];
            issue3(a0, 1);
            {
                const uint32_t dk = dsb + LO128 + ((OFF_STG + 8192) >> 4);
                #pragma unroll
                for (int ks = 0; ks < 4; ks++) wgmma_rs64<HI128>(nd, pq[4 * ks], pq[4 * ks + 1], pq[4 * ks + 2], pq[4 * ks + 3], dk + ks * 128, ks);
            }
            commit();
            retire(); load_a1(6); peek();
            issue3(a1, 1); commit();
            if (wg == 0) bar_arrive<4, 256>();
            ready = mbar_try(sb + p4_bar(0), p4_par(0));
            retire();
            reg_fence(nd);
            const int src = lane & ~3;
            const float s00 = __fdividef(g0, __shfl_sync(0xffffffffu, nd[28], src) + 1e-6f);
            const float s01 = __fdividef(g0, __shfl_sync(0xffffffffu, nd[29], src) + 1e-6f);
            const float s10 = __fdividef(g1, __shfl_sync(0xffffffffu, nd[30], src) + 1e-6f);
            const float s11 = __fdividef(g1, __shfl_sync(0xffffffffu, nd[31], src) + 1e-6f);
            #pragma unroll
            for (int t = 0; t < 7; t++) {
                const bool h1 = t > 3 || (t == 3 && q4 >= 2);
                const float sa = h1 ? s01 : s00, sc = h1 ? s11 : s10;
                op[2 * t] = pack_bf16(nd[4 * t] * sa, nd[4 * t + 1] * sa);
                op[2 * t + 1] = pack_bf16(nd[4 * t + 2] * sc, nd[4 * t + 3] * sc);
            }
            op[14] = 0u; op[15] = 0u;
            reg_fence(op);
        }

        float oa[32], ob[32];
        int c = j == 7 ? 0 : j;
        const int wsh = __shfl_sync(0xffffffffu, warp * 16, 0);
        const uint32_t sh0 = par * 768, sh1 = par * 1024;
        bool ready2 = false;
        auto issue_d = [&](float (&o)[32], int c0, int half) {
            const int n = 3 * c0;
            if (half == 0) {
                if (!ready) mbar_wait(sb + p4_bar(n), p4_par(n));
                if (!ready2) mbar_wait(sb + p4_bar(n + 1), p4_par(n + 1));
                ready = mbar_try(sb + p4_bar(n + 2), p4_par(n + 2));
            }
            wg_fence();
            const uint32_t b = dsb + LO128 + (p4_off(n) >> 4);
            #pragma unroll
            for (int ks = 7 * half; ks < 7 * half + 7; ks++)
                wgmma_rs64<HI128>(o, hp[4 * ks], hp[4 * ks + 1], hp[4 * ks + 2], hp[4 * ks + 3],
                                  b + ks * 128 + (ks < 8 ? sh0 : 0u - sh1), ks);
        };
        auto issue_o = [&](float (&o)[32], int c0) {
            const int n = 3 * c0 + 2;
            if (!ready) mbar_wait(sb + p4_bar(n), p4_par(n));
            if (c0 < 6) {
                ready = mbar_try(sb + p4_bar(n + 1), p4_par(n + 1));
                ready2 = mbar_try(sb + p4_bar(n + 2), p4_par(n + 2));
            }
            wg_fence();
            const uint32_t b = dsb + LO128 + (p4_off(n) >> 4);
            #pragma unroll
            for (int ks = 0; ks < 4; ks++) wgmma_rs64<HI128>(o, op[4 * ks], op[4 * ks + 1], op[4 * ks + 2], op[4 * ks + 3], b + ks * 128, 1);
            wg_commit();
        };
        auto ship = [&](float (&o)[32], int c0) {
            reg_fence(o);
            const uint32_t so = xa + OFF_OUT + (c0 & 1) * 16384;
            #pragma unroll
            for (int t = 0; t < 4; t++)
                stsm4(so + (lx ^ (t * 32)), pack_bf16(o[8 * t], o[8 * t + 1]), pack_bf16(o[8 * t + 2], o[8 * t + 3]),
                      pack_bf16(o[8 * t + 4], o[8 * t + 5]), pack_bf16(o[8 * t + 6], o[8 * t + 7]));
            fence_async_smem();
            __syncwarp();
            if (elect_one()) {
                tma_reduce2d(&mp.out, sb + OFF_OUT + (c0 & 1) * 16384 + wsh * 128, 64 * c, row0 + wsh);
                asm volatile("cp.async.bulk.commit_group;" ::: "memory");
            }
            if (++c == 7) c = 0;
        };
        auto finish_h = [&]() {
            reg_fence(ag);
            release(cur);
            const uint32_t uu = pack_bf16(1.f - g0, 1.f - g1);
            const float u0 = bf_lo(uu), u1 = bf_hi(uu);
            #pragma unroll
            for (int i = 0; i < 24; i++) {
                const float u = (i & 1) ? u1 : u0;
                hp[32 + i] = mul_bf16x2(pack_relu_bf16(ag[2 * i], ag[2 * i + 1]), pack_bf16(ag[48 + 2 * i] * u, ag[49 + 2 * i] * u));
            }
            reg_fence_part<32, 56>(hp);
        };
        ready2 = mbar_try(sb + p4_bar(1), p4_par(1));
        wg_wait<0>();
        finish_h();
        #pragma unroll
        for (int c0 = 0; c0 < 7; c0++) {
            float (&o)[32] = (c0 & 1) ? ob : oa;
            if (c0 > 0 || wg == 1) turn_wait();
            issue_d(o, c0, 0);
            issue_d(o, c0, 1);
            issue_o(o, c0);
            if (!(c0 == 6 && wg == 1)) turn_pass();
            if (c0 >= 2) {
                if (elect_one()) asm volatile("cp.async.bulk.wait_group.read 1;" ::: "memory");
                __syncwarp();
            }
            wg_wait<0>();
            if (c0 < 2) { release(3 * c0); release(3 * c0 + 1); release(3 * c0 + 2); }
            ship(o, c0);
        }
        if (elect_one()) asm volatile("cp.async.bulk.wait_group.read 0;" ::: "memory");
    }
}

typedef CUresult (*EncodeFn)(CUtensorMap*, CUtensorMapDataType, cuuint32_t, void*, const cuuint64_t*, const cuuint64_t*,
                             const cuuint32_t*, const cuuint32_t*, CUtensorMapInterleave, CUtensorMapSwizzle,
                             CUtensorMapL2promotion, CUtensorMapFloatOOBfill);

void make_map(EncodeFn enc, CUtensorMap* m, const void* base, int rank, const cuuint64_t* dims, const cuuint64_t* strides,
              cuuint32_t b0, cuuint32_t b1, cuuint32_t b2, CUtensorMapSwizzle sw) {
    const cuuint32_t es[3] = {1, 1, 1}, box[3] = {b0, b1, b2};
    enc(m, CU_TENSOR_MAP_DATA_TYPE_BFLOAT16, rank, const_cast<void*>(base), dims, strides, box, es,
        CU_TENSOR_MAP_INTERLEAVE_NONE, sw, CU_TENSOR_MAP_L2_PROMOTION_L2_128B, CU_TENSOR_MAP_FLOAT_OOB_FILL_NONE);
}

}

extern "C" void kernel_launch(void* const* d_in, const int* in_sizes, int n_in, void* d_out, int out_size) {
    (void)in_sizes; (void)n_in; (void)out_size;
    static EncodeFn enc = nullptr;
    if (!enc) {
        void* fn = nullptr;
        cudaDriverEntryPointQueryResult st;
        cudaGetDriverEntryPoint("cuTensorMapEncodeTiled", &fn, cudaEnableDefault, &st);
        enc = (EncodeFn)fn;
        cudaFuncSetAttribute(fused_kernel, cudaFuncAttributeMaxDynamicSharedMemorySize, SMEM_BYTES);
    }
    Maps mp;
    const cuuint64_t dimx[2] = {kD, kS}, dimd[2] = {kD, kF}, dimo[2] = {kD, kD}, strd[1] = {kD * 2};
    make_map(enc, &mp.x, d_in[0], 2, dimx, strd, 64, 128, 1, CU_TENSOR_MAP_SWIZZLE_128B);
    make_map(enc, &mp.out, d_out, 2, dimx, strd, 64, 16, 1, CU_TENSOR_MAP_SWIZZLE_128B);
    make_map(enc, &mp.d, d_in[6], 2, dimd, strd, 64, 56, 1, CU_TENSOR_MAP_SWIZZLE_128B);
    make_map(enc, &mp.o, d_in[2], 2, dimo, strd, 64, 32, 1, CU_TENSOR_MAP_SWIZZLE_128B);
    const cuuint64_t dimq[3] = {kD, kD, 3}, strq[2] = {3 * kD * 2, kD * 2};
    make_map(enc, &mp.kv, d_in[1], 3, dimq, strq, 56, 16, 2, CU_TENSOR_MAP_SWIZZLE_128B);
    make_map(enc, &mp.q, d_in[1], 3, dimq, strq, 56, 16, 1, CU_TENSOR_MAP_SWIZZLE_128B);
    const cuuint64_t dimf[3] = {32, kD, kF / 32}, strf[2] = {kF * 2, 64};
    const cuuint64_t dimw[3] = {64, kD, kF / 64}, strw[2] = {kF * 2, 128};
    make_map(enc, &mp.g4, d_in[4], 3, dimw, strw, 64, 16, 2, CU_TENSOR_MAP_SWIZZLE_128B);
    make_map(enc, &mp.u4, d_in[5], 3, dimw, strw, 64, 16, 2, CU_TENSOR_MAP_SWIZZLE_128B);
    make_map(enc, &mp.g3, d_in[4], 3, dimf, strf, 32, 16, 3, CU_TENSOR_MAP_SWIZZLE_64B);
    make_map(enc, &mp.u3, d_in[5], 3, dimf, strf, 32, 16, 3, CU_TENSOR_MAP_SWIZZLE_64B);
    fused_kernel<<<NCTA, NTHREADS, SMEM_BYTES>>>(mp, (const __nv_bfloat16*)d_in[7], (__nv_bfloat16*)d_out, 0u);
}
```

```cpp
#include <cuda_runtime.h>
#include <cuda_bf16.h>
#include <cuda.h>
#include <stdint.h>

namespace {

constexpr int kS = 2048, kD = 448, kF = 1792;
constexpr int NTHREADS = 384;
constexpr int NCTA = 128;
constexpr uint32_t OFF_X = 0;
constexpr uint32_t OFF_RING = 114688;
constexpr uint32_t SLOT_BYTES = 16384;
constexpr int NSLOT = 6;
constexpr uint32_t OFF_STG = 212992;
constexpr uint32_t OFF_MISC = 229376;
constexpr uint32_t SMEM_BYTES = 232448;
constexpr uint32_t BAR_FULL = OFF_MISC, BAR_EMPTY = OFF_MISC + 48, BAR_XFULL = OFF_MISC + 96;
constexpr uint32_t BAR_W = OFF_MISC + 152, BAR_KVDONE = OFF_MISC + 160, BAR_AUX = OFF_MISC + 168, BAR_P4 = OFF_MISC + 176;
constexpr uint32_t OFF_W = OFF_MISC + 256;
constexpr uint32_t SB = 1024;

#define DOT 2
__device__ __align__(128) float g_kvacc[8][2048];
__device__ unsigned int g_counter[64];

__device__ __forceinline__ void mbar_init(uint32_t bar, uint32_t cnt) {
    asm volatile("mbarrier.init.shared::cta.b64 [%0], %1;" :: "r"(bar), "r"(cnt) : "memory");
}
__device__ __forceinline__ void mbar_expect_tx(uint32_t bar, uint32_t bytes) {
    asm volatile("mbarrier.arrive.expect_tx.shared::cta.b64 _, [%0], %1;" :: "r"(bar), "r"(bytes) : "memory");
}
__device__ __forceinline__ void mbar_arrive(uint32_t bar) {
    asm volatile("mbarrier.arrive.shared::cta.b64 _, [%0];" :: "r"(bar) : "memory");
}
__device__ __forceinline__ void mbar_arrive_cluster(uint32_t bar) {
    asm volatile("mbarrier.arrive.shared::cluster.b64 _, [%0];" :: "r"(bar) : "memory");
}
__device__ __forceinline__ void mbar_wait(uint32_t bar, uint32_t parity) {
    asm volatile("{\n"
                 ".reg .pred p;\n"
                 ".reg .u32 c;\n"
                 "mov.u32 c, 0;\n"
                 "AGAIN:\n"
                 "mbarrier.try_wait.parity.shared::cta.b64 p, [%0], %1;\n"
                 "@p bra DONE;\n"
                 "add.u32 c, c, 1;\n"
                 "setp.lt.u32 p, c, 4194304;\n"
                 "@p bra AGAIN;\n"
                 "trap;\n"
                 "DONE:\n"
                 "}" :: "r"(bar), "r"(parity) : "memory");
}
__device__ __forceinline__ uint32_t mapa(uint32_t addr, uint32_t cta) {
    uint32_t r; asm("mapa.shared::cluster.u32 %0, %1, %2;" : "=r"(r) : "r"(addr), "r"(cta)); return r;
}
__device__ __forceinline__ bool elect_one() {
    uint32_t p;
    asm volatile("{ .reg .pred P; elect.sync _|P, 0xffffffff; selp.u32 %0, 1, 0, P; }" : "=r"(p));
    return p;
}
__device__ __forceinline__ void tma2d(uint32_t dst, const CUtensorMap* m, int c0, int c1, uint32_t bar) {
    asm volatile("cp.async.bulk.tensor.2d.shared::cluster.global.mbarrier::complete_tx::bytes [%0], [%1, {%3, %4}], [%2];"
                 :: "r"(dst), "l"(m), "r"(bar), "r"(c0), "r"(c1) : "memory");
}
__device__ __forceinline__ void tma2d_mc(uint32_t dst, const CUtensorMap* m, int c0, int c1, uint32_t bar) {
    asm volatile("cp.async.bulk.tensor.2d.shared::cluster.global.mbarrier::complete_tx::bytes.multicast::cluster [%0], [%1, {%3, %4}], [%2], %5;"
                 :: "r"(dst), "l"(m), "r"(bar), "r"(c0), "r"(c1), "h"((uint16_t)3) : "memory");
}
__device__ __forceinline__ void tma3d_mc(uint32_t dst, const CUtensorMap* m, int c0, int c1, int c2, uint32_t bar) {
    asm volatile("cp.async.bulk.tensor.3d.shared::cluster.global.mbarrier::complete_tx::bytes.multicast::cluster [%0], [%1, {%3, %4, %5}], [%2], %6;"
                 :: "r"(dst), "l"(m), "r"(bar), "r"(c0), "r"(c1), "r"(c2), "h"((uint16_t)3) : "memory");
}
__device__ __forceinline__ void tma_reduce2d(const CUtensorMap* m, uint32_t src, int c0, int c1) {
    asm volatile("cp.reduce.async.bulk.tensor.2d.global.shared::cta.add.bulk_group [%0, {%2, %3}], [%1];"
                 :: "l"(m), "r"(src), "r"(c0), "r"(c1) : "memory");
}
__device__ __forceinline__ void bulk_reduce_f32(float* dst, uint32_t src, uint32_t bytes) {
    asm volatile("cp.reduce.async.bulk.global.shared::cta.bulk_group.add.f32 [%0], [%1], %2;" :: "l"(dst), "r"(src), "r"(bytes) : "memory");
}
__device__ __forceinline__ bool mbar_try(uint32_t bar, uint32_t parity) {
    uint32_t ok;
    asm volatile("{ .reg .pred p; mbarrier.test_wait.parity.shared::cta.b64 p, [%1], %2; selp.u32 %0, 1, 0, p; }"
                 : "=r"(ok) : "r"(bar), "r"(parity) : "memory");
    return ok;
}
__device__ __forceinline__ void prefetch_map(const CUtensorMap* m) {
    asm volatile("prefetch.tensormap [%0];" :: "l"(m) : "memory");
}
__device__ __forceinline__ void wg_fence() { asm volatile("wgmma.fence.sync.aligned;" ::: "memory"); }
__device__ __forceinline__ void wg_commit() { asm volatile("wgmma.commit_group.sync.aligned;" ::: "memory"); }
template <int N> __device__ __forceinline__ void wg_wait() { asm volatile("wgmma.wait_group.sync.aligned %0;" :: "n"(N) : "memory"); }
template <int N> __device__ __forceinline__ void reg_fence(float (&d)[N]) {
#pragma unroll
    for (int i = 0; i < N; i++) asm volatile("" : "+f"(d[i]) :: "memory");
}
template <int N> __device__ __forceinline__ void reg_fence(uint32_t (&d)[N]) {
#pragma unroll
    for (int i = 0; i < N; i++) asm volatile("" : "+r"(d[i]) :: "memory");
}
template <int LO, int HI, int N> __device__ __forceinline__ void reg_fence_part(uint32_t (&d)[N]) {
#pragma unroll
    for (int i = LO; i < HI; i++) asm volatile("" : "+r"(d[i]) :: "memory");
}
__device__ __forceinline__ void fence_async_smem() { asm volatile("fence.proxy.async.shared::cta;" ::: "memory"); }
template <int ID, int N> __device__ __forceinline__ void bar_sync() { asm volatile("bar.sync %0, %1;" :: "n"(ID), "n"(N) : "memory"); }
template <int ID, int N> __device__ __forceinline__ void bar_arrive() { asm volatile("bar.arrive %0, %1;" :: "n"(ID), "n"(N) : "memory"); }
__device__ __forceinline__ void ldsm4(uint32_t* r, uint32_t addr) {
    asm volatile("ldmatrix.sync.aligned.m8n8.x4.shared.b16 {%0, %1, %2, %3}, [%4];"
                 : "=r"(r[0]), "=r"(r[1]), "=r"(r[2]), "=r"(r[3]) : "r"(addr) : "memory");
}
__device__ __forceinline__ void stsm4(uint32_t addr, uint32_t r0, uint32_t r1, uint32_t r2, uint32_t r3) {
    asm volatile("stmatrix.sync.aligned.m8n8.x4.shared.b16 [%0], {%1, %2, %3, %4};"
                 :: "r"(addr), "r"(r0), "r"(r1), "r"(r2), "r"(r3) : "memory");
}
__device__ __forceinline__ uint32_t lds32(uint32_t addr) {
    uint32_t r; asm volatile("ld.shared.u32 %0, [%1];" : "=r"(r) : "r"(addr)); return r;
}
__device__ __forceinline__ float4 lds128f(uint32_t addr) {
    float4 r; asm volatile("ld.shared.v4.f32 {%0, %1, %2, %3}, [%4];" : "=f"(r.x), "=f"(r.y), "=f"(r.z), "=f"(r.w) : "r"(addr)); return r;
}
__device__ __forceinline__ uint32_t clock32() { uint32_t t; asm volatile("mov.u32 %0, %%clock;" : "=r"(t)); return t; }
__device__ __forceinline__ uint32_t pack_bf16(float lo, float hi) {
    uint32_t r; asm("cvt.rn.bf16x2.f32 %0, %1, %2;" : "=r"(r) : "f"(hi), "f"(lo)); return r;
}
__device__ __forceinline__ uint32_t pack_relu_bf16(float lo, float hi) {
    uint32_t r; asm("cvt.rn.relu.bf16x2.f32 %0, %1, %2;" : "=r"(r) : "f"(hi), "f"(lo)); return r;
}
__device__ __forceinline__ uint32_t mul_bf16x2(uint32_t a, uint32_t b) {
    uint32_t r; asm("mul.rn.bf16x2 %0, %1, %2;" : "=r"(r) : "r"(a), "r"(b)); return r;
}
__device__ __forceinline__ uint32_t fma_bf16x2(uint32_t a, uint32_t b, uint32_t c) {
    uint32_t r; asm("fma.rn.bf16x2 %0, %1, %2, %3;" : "=r"(r) : "r"(a), "r"(b), "r"(c)); return r;
}
__device__ __forceinline__ float phi(float t, float log2e) {
    float e;
    asm("ex2.approx.ftz.f32 %0, %1;" : "=f"(e) : "f"(fminf(t * log2e, 0.f)));
    return e + (fmaxf(t, 0.f) + 1e-6f);
}
__device__ __forceinline__ float after_issue(float v, uint32_t zero) {
    return __uint_as_float(__float_as_uint(v) | (clock32() & zero));
}
constexpr float kLog2e = 1.4426950408889634f;
__device__ __forceinline__ float bf_lo(uint32_t v) { return __uint_as_float(v << 16); }
__device__ __forceinline__ float bf_hi(uint32_t v) { return __uint_as_float(v & 0xffff0000u); }
constexpr uint32_t HI128 = (1024 >> 4) | (1u << 30);
constexpr uint32_t HI64 = (512 >> 4) | (2u << 30);
constexpr uint32_t LO128 = 1u << 16, LO64 = (1024u >> 4) << 16, LO128X2 = (2048u >> 4) << 16;
constexpr uint32_t QB = 16 * 112;
constexpr uint32_t TX1 = 2 * (2 * QB + 4096), TX2 = 2 * (QB + 4096), TX3 = 12288;
__device__ __forceinline__ void grid_arrive(unsigned int* c) {
    asm volatile("fence.acq_rel.gpu;" ::: "memory");
    asm volatile("red.relaxed.gpu.global.add.u32 [%0], 1;" :: "l"(c) : "memory");
}
__device__ __forceinline__ void grid_wait(const unsigned int* c, unsigned int target) {
    unsigned int v; int it = 0;
    do {
        asm volatile("ld.relaxed.gpu.global.u32 %0, [%1];" : "=r"(v) : "l"(c) : "memory");
        if (++it > (1 << 22)) asm volatile("trap;");
    } while ((int)(v - target) < 0);
    asm volatile("ld.acquire.gpu.global.u32 %0, [%1];" : "=r"(v) : "l"(c) : "memory");
}

__host__ __device__ constexpr uint32_t p4_pack(int n) { return (n / 3) * 36864 + (n % 3) * 14336; }
__host__ __device__ constexpr uint32_t p4_off(int n) {
    return n < 6 ? OFF_X + p4_pack(n) : n < 14 ? OFF_RING + p4_pack(n - 6) : n == 14 ? OFF_X + p4_pack(6) : OFF_X + p4_pack(n - 15);
}
__host__ __device__ constexpr uint32_t p4_bar(int n) {
    return n < 6 ? BAR_XFULL + 8 * n : n < 12 ? BAR_FULL + 8 * (n - 6) : n < 14 ? BAR_P4 + 8 * (n - 12)
                 : n == 14 ? BAR_XFULL + 48 : BAR_XFULL + 8 * (n - 15);
}
__host__ __device__ constexpr uint32_t p4_par(int n) { return (n < 12 || n == 14) ? 1 : 0; }
constexpr uint32_t OFF_OUT = OFF_X + 5 * 16384;
static_assert(p4_off(7) == p4_off(6) + 14336 && p4_off(13) == p4_off(12) + 14336 && p4_off(16) == p4_off(15) + 14336, "Wd halves");
static_assert(p4_off(13) + 14336 <= OFF_STG + 8192 && p4_off(14) + 8192 == OFF_OUT, "pass-4 layout");

struct Ring {
    uint32_t slot, phase;
    __device__ __forceinline__ void advance() { if (++slot == NSLOT) { slot = 0; phase ^= 1; } }
};

struct Maps { CUtensorMap x, kv, q, g4, g3, u4, u3, d, o, out; };

__global__ void __cluster_dims__(2, 1, 1) __launch_bounds__(NTHREADS, 1)
fused_kernel(const __grid_constant__ Maps mp, const __nv_bfloat16* __restrict__ gate_w, __nv_bfloat16* __restrict__ out,
             uint32_t zero)
{
    extern __shared__ __align__(1024) unsigned char smem[];
    const uint32_t sb = (uint32_t)__cvta_generic_to_shared(smem);
    const int tid = threadIdx.x, warp = tid >> 5, lane = tid & 31;
    const int rank = blockIdx.x & 1, j = (blockIdx.x >> 1) & 7;
    const int row0 = ((blockIdx.x >> 4) * 2 + rank) * 128;
    const int par = j & 1;
    const int g4i = (7 * j + 3 * par) >> 1;

    if (warp == 9) {
        if (elect_one()) {
            prefetch_map(&mp.x);
            mbar_init(sb + BAR_XFULL, 1);
            mbar_expect_tx(sb + BAR_XFULL, 16384);
            tma2d(sb + OFF_X, &mp.x, 0, row0, sb + BAR_XFULL);
            asm volatile("fence.mbarrier_init.release.cluster;" ::: "memory");
        }
        __syncwarp();
    } else if (warp == 8) {
        if (elect_one()) {
            #pragma unroll
            for (int s = 0; s < NSLOT; s++) mbar_init(sb + BAR_FULL + 8 * s, 1);
            asm volatile("fence.mbarrier_init.release.cluster;" ::: "memory");
            mbar_expect_tx(sb + BAR_FULL, TX1);
        }
        __syncwarp();
    } else if (warp == 10) {
        if (elect_one()) {
            #pragma unroll
            for (int s = 1; s < 7; s++) mbar_init(sb + BAR_XFULL + 8 * s, 1);
            mbar_init(sb + BAR_KVDONE, 8);
            mbar_init(sb + BAR_AUX, 3);
            asm volatile("fence.mbarrier_init.release.cluster;" ::: "memory");
            if ((sb & 0xFFFFFF) != SB) asm volatile("trap;");
        }
        __syncwarp();
    } else if (warp == 11) {
        if (elect_one()) {
            #pragma unroll
            for (int s = 0; s < NSLOT; s++) mbar_init(sb + BAR_EMPTY + 8 * s, 4);
            mbar_init(sb + BAR_P4, 1);
            mbar_init(sb + BAR_P4 + 8, 1);
            asm volatile("fence.mbarrier_init.release.cluster;" ::: "memory");
        }
        __syncwarp();
    } else if (warp == 2) {
        if (elect_one()) {
            mbar_init(sb + BAR_W, 1);
            asm volatile("fence.mbarrier_init.release.cluster;" ::: "memory");
            mbar_expect_tx(sb + BAR_W, 896);
            asm volatile("cp.async.bulk.shared::cluster.global.mbarrier::complete_tx::bytes [%0], [%1], 896, [%2];"
                         :: "r"(sb + OFF_W), "l"(gate_w), "r"(sb + BAR_W) : "memory");
        }
        __syncwarp();
    }
    asm volatile("barrier.cluster.arrive.relaxed.aligned;" ::: "memory");
    if (warp == 8) {
        if (elect_one()) { prefetch_map(&mp.kv); prefetch_map(&mp.g4); }
        __syncwarp();
    }
    asm volatile("barrier.cluster.wait.aligned;" ::: "memory");
    if (warp == 8) {
        if (elect_one()) {
            tma3d_mc(sb + OFF_RING + rank * 8192, &mp.kv, 56 * j, 16 * rank, 1, sb + BAR_FULL);
            tma3d_mc(sb + OFF_RING + rank * 8192 + 4096, &mp.g4, 0, 16 * rank, g4i, sb + BAR_FULL);
        }
        __syncwarp();
    }

    if (warp >= 8) {
        asm volatile("setmaxnreg.dec.sync.aligned.u32 40;");
        if (warp == 8) {
            if (elect_one()) {
                Ring r{1, 1};
                auto acquire = [&](uint32_t bytes) -> uint32_t {
                    mbar_wait(sb + BAR_EMPTY + 8 * r.slot, r.phase);
                    mbar_expect_tx(sb + BAR_FULL + 8 * r.slot, bytes);
                    return sb + OFF_RING + r.slot * SLOT_BYTES;
                };
                #pragma unroll 1
                for (int s = 1; s < 14; s++) {
                    const uint32_t dst = acquire(TX1) + rank * 8192;
                    tma3d_mc(dst, &mp.kv, 56 * j, 32 * s + 16 * rank, 1, sb + BAR_FULL + 8 * r.slot);
                    tma3d_mc(dst + 4096, &mp.g4, 0, 32 * s + 16 * rank, g4i, sb + BAR_FULL + 8 * r.slot);
                    r.advance();
                    if ((s & 1) && s < 12) {
                        const int n = (s >> 1) + 1;
                        mbar_expect_tx(sb + BAR_XFULL + 8 * n, 16384);
                        tma2d(sb + OFF_X + n * 16384, &mp.x, 64 * n, row0, sb + BAR_XFULL + 8 * n);
                    }
                    if (s == 5) {
                        prefetch_map(&mp.q); prefetch_map(&mp.u4); prefetch_map(&mp.g3); prefetch_map(&mp.u3);
                        prefetch_map(&mp.d); prefetch_map(&mp.o); prefetch_map(&mp.out);
                    }
                }
                #pragma unroll 1
                for (int s = 0; s < 14; s++) {
                    const uint32_t dst = acquire(TX2) + rank * 6144;
                    tma3d_mc(dst, &mp.q, 56 * j, 32 * s + 16 * rank, 0, sb + BAR_FULL + 8 * r.slot);
                    tma3d_mc(dst + 2048, &mp.u4, 0, 32 * s + 16 * rank, g4i, sb + BAR_FULL + 8 * r.slot);
                    r.advance();
                }
                const int cfirst = j == 7 ? 0 : j;
                auto load4 = [&](int n) {
                    int c = cfirst + n / 3;
                    if (c >= 7) c -= 7;
                    mbar_expect_tx(sb + p4_bar(n), n % 3 == 2 ? 8192 : 14336);
                    if (n % 3 == 2) tma2d_mc(sb + p4_off(n) + rank * 4096, &mp.o, 64 * c, 56 * j + 32 * rank, sb + p4_bar(n));
                    else tma2d_mc(sb + p4_off(n) + rank * 7168, &mp.d, 64 * c, 224 * j + 112 * (n % 3) + 56 * rank, sb + p4_bar(n));
                };
                #pragma unroll 1
                for (int s = 0; s < 14; s++) {
                    const uint32_t dst = acquire(TX3) + rank * 6144;
                    tma3d_mc(dst, &mp.g3, 0, 32 * s + 16 * rank, 7 * j + 4 - 4 * par, sb + BAR_FULL + 8 * r.slot);
                    tma3d_mc(dst + 3072, &mp.u3, 0, 32 * s + 16 * rank, 7 * j + 4 - 4 * par, sb + BAR_FULL + 8 * r.slot);
                    r.advance();
                    if (s == 7) load4(0);
                    if (s == 9) load4(1);
                    if (s == 11) load4(2);
                    if (s == 13) { load4(3); load4(4); }
                }
                mbar_wait(sb + BAR_EMPTY, 0);      load4(6);
                mbar_wait(sb + BAR_EMPTY + 8, 0);  load4(5); load4(7); load4(14);
                mbar_wait(sb + BAR_EMPTY + 16, 0); load4(8);
                mbar_wait(sb + BAR_EMPTY + 24, 0); load4(9); load4(10);
                mbar_wait(sb + BAR_EMPTY + 32, 0); load4(11);
                mbar_wait(sb + BAR_EMPTY + 40, 0); load4(12);
                mbar_wait(sb + BAR_AUX, 0);        load4(13);
                #pragma unroll
                for (int n = 15; n < 21; n++) {
                    mbar_wait(sb + BAR_EMPTY + 8 * (n - 15), 1);
                    __nanosleep(100);
                    load4(n);
                }
            }
        } else {
            const int ht = tid - 288;
            unsigned int cnt0;
            asm volatile("ld.relaxed.gpu.global.u32 %0, [%1];" : "=r"(cnt0) : "l"(&g_counter[32]) : "memory");
            const unsigned int target = ((cnt0 >> 7) + 1) << 7;
            if (warp == 9) {
                reinterpret_cast<float4*>(&g_kvacc[0][0])[blockIdx.x * 32 + lane] = make_float4(0.f, 0.f, 0.f, 0.f);
                asm volatile("fence.proxy.async.global;" ::: "memory");
                __syncwarp();
                if (lane == 0) grid_arrive(&g_counter[0]);
                mbar_wait(sb + BAR_XFULL + 8 * 6, 0);
                uint4* o = reinterpret_cast<uint4*>(out) + blockIdx.x * 896 + lane;
                #pragma unroll 4
                for (int q = 0; q < 28; q++) o[q * 32] = make_uint4(0, 0, 0, 0);
                asm volatile("fence.proxy.async.global;" ::: "memory");
                __syncwarp();
                if (lane == 0) {
                    asm volatile("fence.acq_rel.gpu;" ::: "memory");
                    grid_wait(&g_counter[0], target);
                }
                __syncwarp();
            }
            mbar_wait(sb + BAR_KVDONE, 0);
            {
                #pragma unroll
                for (int i0 = 0; i0 < 5; i0 += 2) {
                    float4 pa[2], pb[2];
                    #pragma unroll
                    for (int i = 0; i < 2 && i0 + i < 5; i++) {
                        const int q = min(ht + 96 * (i0 + i), 447);
                        pa[i] = lds128f(sb + OFF_STG + q * 16); pb[i] = lds128f(sb + OFF_STG + 8192 + q * 16);
                    }
                    #pragma unroll
                    for (int i = 0; i < 2 && i0 + i < 5; i++) {
                        const int q = ht + 96 * (i0 + i);
                        if (q < 448) asm volatile("st.shared.v4.f32 [%0], {%1, %2, %3, %4};" :: "r"(sb + OFF_STG + q * 16),
                            "f"(pa[i].x + pb[i].x), "f"(pa[i].y + pb[i].y), "f"(pa[i].z + pb[i].z), "f"(pa[i].w + pb[i].w) : "memory");
                    }
                }
                fence_async_smem();
            }
            bar_sync<3, 96>();
            if (warp == 9) {
                if (elect_one()) {
                    bulk_reduce_f32(&g_kvacc[j][0], sb + OFF_STG, 7168);
                    asm volatile("cp.async.bulk.commit_group;" ::: "memory");
                    asm volatile("cp.async.bulk.wait_group 0;" ::: "memory");
                    asm volatile("red.relaxed.gpu.global.add.u32 [%0], 1;" :: "l"(&g_counter[32]) : "memory");
                }
            }
            __syncwarp();
            #pragma unroll
            for (int i = 0; i < 3; i++) {
                const int q = ht + 96 * i;
                const int d = q < 168 ? q / 3 : 56 + ((q - 168) >> 3);
                const int c = q < 168 ? (q - 3 * d + (d < 28 ? 4 : 0)) : (q & 7);
                if (q < 232) asm volatile("st.shared.v4.u32 [%0], {%1, %1, %1, %1};" :: "r"(sb + OFF_STG + 8192 + d * 128 + ((c ^ (d & 7)) << 4)), "r"(0) : "memory");
            }
            uint32_t plan[3];
            #pragma unroll
            for (int i = 0; i < 3; i++) {
                const int q = min(ht + 96 * i, 279), d = q / 5, m = q - 5 * d;
                const bool h0 = d < 28;
                const int c = m == 4 ? 7 : (h0 ? m : m + 3), pc = m < 4 ? m : (h0 ? 3 : 0);
                const int kind = m == 4 ? (h0 ? 3 : 4) : c == 3 ? (h0 ? 1 : 2) : 0;
                plan[i] = (d * 128 + ((c ^ (d & 7)) << 4)) | ((d * 4 + (pc ^ (d & 3))) << 13) | (kind << 23);
                asm volatile("" : "+r"(plan[i]));
            }
            if (lane == 0) grid_wait(&g_counter[32], target);
            __syncwarp();
            const float4* src = reinterpret_cast<const float4*>(&g_kvacc[j][0]);
            float4 va[3], vb[3];
            #pragma unroll
            for (int i = 0; i < 3; i++) {
                const float4* p = src + ((plan[i] >> 12) & 0x7fe);
                va[i] = __ldcg(p); vb[i] = __ldcg(p + 1);
            }
            #pragma unroll
            for (int i = 0; i < 3; i++) {
                const uint32_t kind = plan[i] >> 23;
                uint32_t w0 = pack_bf16(va[i].x, va[i].y), w1 = pack_bf16(va[i].z, va[i].w);
                uint32_t w2 = pack_bf16(vb[i].x, vb[i].y), w3 = pack_bf16(vb[i].z, vb[i].w);
                if (kind == 3) w0 = w2 & 0xffffu;
                if (kind == 4) w0 <<= 16;
                if (kind == 2) w0 = 0u;
                if (kind >= 2) w1 = 0u;
                if (kind != 0 && kind != 2) w2 = w3 = 0u;
                if (i < 2 || ht < 88)
                    asm volatile("st.shared.v4.u32 [%0], {%1, %2, %3, %4};"
                                 :: "r"(sb + OFF_STG + 8192 + (plan[i] & 0x1fff)), "r"(w0), "r"(w1), "r"(w2), "r"(w3) : "memory");
            }
            fence_async_smem();
            __syncwarp();
            if (lane == 0) mbar_arrive(sb + BAR_AUX);
        }
    } else {
        asm volatile("setmaxnreg.inc.sync.aligned.u32 232;");
        const int wg = warp >> 2, w4 = warp & 3;
        const int q4 = lane & 3, g8 = lane >> 2;
        const uint32_t lx = ((lane >> 4) ^ (lane & 7)) << 4;
        const uint32_t xa = sb + OFF_X + (warp * 16 + (lane & 15)) * 128;
        const uint32_t empty_dst = mapa(sb + BAR_EMPTY, w4 & 1);
        const bool signaller = lane == 0 && w4 < 2;
        constexpr uint32_t dsb = SB >> 4;
        Ring r{0, 0};
        uint32_t cur = 0, old = 0;
        bool ready = false;
        auto release = [&](uint32_t slot) { if (signaller) mbar_arrive_cluster(empty_dst + 8 * slot); };
        auto turn_wait = [&]() { if (wg == 0) bar_sync<6, 256>(); else bar_sync<7, 256>(); };
        auto turn_pass = [&]() { if (wg == 0) bar_arrive<7, 256>(); else bar_arrive<6, 256>(); };
        auto begin = [&]() -> uint32_t {
            if (!ready) mbar_wait(sb + BAR_FULL + 8 * r.slot, r.phase);
            wg_fence();
            return dsb + (OFF_RING >> 4) + r.slot * (SLOT_BYTES >> 4);
        };
        auto commit = [&]() { wg_commit(); old = cur; cur = r.slot; r.advance(); };
        auto retire = [&]() { wg_wait<1>(); release(old); };
        auto peek = [&]() { ready = mbar_try(sb + BAR_FULL + 8 * r.slot, r.phase); };
        uint32_t a0[8], a1[8];
        auto load_a0 = [&](int kc) { ldsm4(a0, xa + kc * 16384 + lx); ldsm4(a0 + 4, xa + kc * 16384 + (lx ^ 32)); };
        auto load_a1 = [&](int kc) { ldsm4(a1, xa + kc * 16384 + (lx ^ 64)); ldsm4(a1 + 4, xa + kc * 16384 + (lx ^ 96)); };

        uint32_t hp[56];
        float g0, g1, ak[28], av[28];
        {
            float ag[64];
            float d0 = 0.f, d1 = 0.f, d2 = 0.f, d3 = 0.f;
            uint32_t w0[4], w1[4];
            auto issue1 = [&](uint32_t (&a)[8], int sd) {
                const uint32_t b = begin();
                wgmma_rs56<HI128>(ak, a[0], a[1], a[2], a[3], b + LO128, sd);
                wgmma_rs56<HI128>(av, a[0], a[1], a[2], a[3], b + LO128 + 128, sd);
                wgmma_rs128<HI128>(ag, a[0], a[1], a[2], a[3], b + LO128X2 + 256, sd);
                wgmma_rs56<HI128>(ak, a[4], a[5], a[6], a[7], b + LO128 + 512, 1);
                wgmma_rs56<HI128>(av, a[4], a[5], a[6], a[7], b + LO128 + 640, 1);
                wgmma_rs128<HI128>(ag, a[4], a[5], a[6], a[7], b + LO128X2 + 768, 1);
                commit();
            };
            auto issue1s = [&](uint32_t (&a)[8]) {
                const uint32_t b = begin();
                wgmma_rs128<HI128>(ag, a[0], a[1], a[2], a[3], b + LO128X2 + 256, 1);
                wgmma_rs128<HI128>(ag, a[4], a[5], a[6], a[7], b + LO128X2 + 768, 1);
                wg_commit();
                wgmma_rs56<HI128>(ak, a[0], a[1], a[2], a[3], b + LO128, 1);
                wgmma_rs56<HI128>(av, a[0], a[1], a[2], a[3], b + LO128 + 128, 1);
                wgmma_rs56<HI128>(ak, a[4], a[5], a[6], a[7], b + LO128 + 512, 1);
                wgmma_rs56<HI128>(av, a[4], a[5], a[6], a[7], b + LO128 + 640, 1);
                commit();
            };
            auto load_w = [&](uint32_t (&w)[4], int s) {
                #pragma unroll
                for (int e = 0; e < 4; e++) w[e] = lds32(sb + OFF_W + s * 64 + q4 * 4 + e * 16);
            };
            auto dot = [&](uint32_t (&a)[8], uint32_t (&w)[4]) {
                if (DOT == 0) {
                uint32_t p0 = mul_bf16x2(a[0], w[0]), p1 = mul_bf16x2(a[1], w[0]);
                #pragma unroll
                for (int e = 1; e < 4; e++) { p0 = fma_bf16x2(a[2 * e], w[e], p0); p1 = fma_bf16x2(a[2 * e + 1], w[e], p1); }
                d0 += bf_lo(p0); d2 += bf_hi(p0); d1 += bf_lo(p1); d3 += bf_hi(p1);
                } else if (DOT == 1) {
                    #pragma unroll
                    for (int e = 0; e < 4; e++) {
                        d0 = fmaf(bf_lo(a[2 * e]), bf_lo(w[e]), d0);     d2 = fmaf(bf_hi(a[2 * e]), bf_hi(w[e]), d2);
                        d1 = fmaf(bf_lo(a[2 * e + 1]), bf_lo(w[e]), d1); d3 = fmaf(bf_hi(a[2 * e + 1]), bf_hi(w[e]), d3);
                    }
                } else {
                    #pragma unroll
                    for (int e = 0; e < 4; e++) {
                        const uint32_t p0 = mul_bf16x2(a[2 * e], w[e]), p1 = mul_bf16x2(a[2 * e + 1], w[e]);
                        d0 += bf_lo(p0); d2 += bf_hi(p0); d1 += bf_lo(p1); d3 += bf_hi(p1);
                    }
                }
                asm volatile("" : "+f"(d0), "+f"(d1), "+f"(d2), "+f"(d3));
            };
            mbar_wait(sb + BAR_XFULL, 0);
            load_a0(0);
            mbar_wait(sb + BAR_W, 0);
            load_w(w0, 0);
            auto odd_stage = [&](int it, bool first, bool last) {
                wg_wait<1>();
                if (!first) release(old);
                load_a1(it);
                load_w(w1, 2 * it + 1);
                peek();
                dot(a0, w0);
                if (last && wg == 1) bar_sync<4, 256>();
                issue1s(a1);
                if (last && wg == 0) bar_arrive<4, 256>();
            };
            issue1(a0, 0);
            #pragma unroll
            for (int it = 0; it < 6; it++) {
                const bool xok = mbar_try(sb + BAR_XFULL + 8 * (it + 1), 0);
                odd_stage(it, it == 0, false);
                wg_wait<2>(); release(old);
                if (!xok) mbar_wait(sb + BAR_XFULL + 8 * (it + 1), 0);
                load_a0(it + 1);
                load_w(w0, 2 * it + 2);
                peek();
                dot(a1, w1);
                issue1(a0, 1);
            }
            odd_stage(6, false, true);
            wg_wait<2>(); release(old);
            load_a0(0);
            peek();
            dot(a1, w1);
            wg_wait<1>();
            reg_fence(ag);
            #pragma unroll
            for (int i = 0; i < 32; i++) hp[i] = pack_relu_bf16(ag[2 * i], ag[2 * i + 1]);
            reg_fence_part<0, 32>(hp);
            g0 = d0 + d2; g1 = d1 + d3;
        }

        float aq[28], au[64];
        {
            auto issue2 = [&](uint32_t (&a)[8], int sd) {
                const uint32_t b = begin();
                wgmma_rs56<HI128>(aq, a[0], a[1], a[2], a[3], b + LO128, sd);
                wgmma_rs128<HI128>(au, a[0], a[1], a[2], a[3], b + LO128X2 + 128, sd);
                wgmma_rs56<HI128>(aq, a[4], a[5], a[6], a[7], b + LO128 + 384, 1);
                wgmma_rs128<HI128>(au, a[4], a[5], a[6], a[7], b + LO128X2 + 512, 1);
            };
            const uint32_t st_base = wg == 0 ? OFF_STG : OFF_RING + 12288, st_step = wg == 0 ? 2048 : SLOT_BYTES, st_v = wg == 0 ? 8192 : 2048;
            const uint32_t sk = sb + st_base + w4 * st_step + (lane & 15) * 128;
            float tok = kLog2e;
            uint32_t pk[16];
            pk[14] = 0u; pk[15] = 0u;
            auto stage_k = [&](int lo, int hi) {
                #pragma unroll
                for (int i = 0; i < 14; i++) if (i >= lo && i < hi) pk[i] = pack_bf16(phi(ak[2 * i], tok), phi(ak[2 * i + 1], tok));
                #pragma unroll
                for (int t = 0; t < 4; t++) {
                    const int need = t < 3 ? 4 * t + 4 : 14;
                    if (need > lo && need <= hi) stsm4(sk + (lx ^ (t * 32)), pk[4 * t], pk[4 * t + 1], pk[4 * t + 2], pk[4 * t + 3]);
                }
                #pragma unroll
                for (int i = 0; i < 14; i++) if (i >= lo && i < hi) asm volatile("" : "+r"(pk[i]));
            };
            issue2(a0, 0); commit();
            tok = after_issue(kLog2e, zero);
            retire();
            reg_fence(ak); reg_fence(av);
            if (wg == 0) bar_arrive<8, 256>();
            load_a1(0); peek();
            uint32_t pv[14];
            #pragma unroll
            for (int i = 0; i < 14; i++) pv[i] = pack_bf16(av[2 * i], av[2 * i + 1]);
            if (wg == 1) bar_sync<8, 256>();
            {
                const uint32_t ones = q4 == 0 ? 0x3f803f80u : 0u;
                #pragma unroll
                for (int t = 0; t < 3; t++) stsm4(sk + st_v + (lx ^ (t * 32)), pv[4 * t], pv[4 * t + 1], pv[4 * t + 2], pv[4 * t + 3]);
                stsm4(sk + st_v + (lx ^ 96), pv[12], pv[13], ones, ones);
            }
            stage_k(0, 2);
            issue2(a1, 1); commit();
            tok = after_issue(kLog2e, zero);
            retire(); load_a0(1); peek();
            stage_k(2, 5);
            issue2(a0, 1); commit();
            tok = after_issue(kLog2e, zero);
            retire(); load_a1(1); peek();
            stage_k(5, 8);
            issue2(a1, 1); commit();
            tok = after_issue(kLog2e, zero);
            retire(); load_a0(2); peek();
            stage_k(8, 11);
            issue2(a0, 1); commit();
            tok = after_issue(kLog2e, zero);
            retire(); load_a1(2); peek();
            stage_k(11, 14);
            issue2(a1, 1); commit();
            retire(); load_a0(3); peek();
            fence_async_smem();
            if (wg == 0) bar_sync<1, 128>(); else bar_sync<2, 128>();
            float kv[32];
            issue2(a0, 1);
            {
                const uint32_t dk = dsb + LO128 + (st_base >> 4), ds = st_step >> 4, dv = st_v >> 4;
                #pragma unroll
                for (int ks = 0; ks < 4; ks++) wgmma_ss64_tt<HI128>(kv, dk + ks * ds, dk + ks * ds + dv, ks);
            }
            commit();
            tok = after_issue(-kLog2e, zero);
            retire(); load_a1(3); peek();
            {
                g0 += __shfl_xor_sync(0xffffffffu, g0, 1); g1 += __shfl_xor_sync(0xffffffffu, g1, 1);
                g0 += __shfl_xor_sync(0xffffffffu, g0, 2); g1 += __shfl_xor_sync(0xffffffffu, g1, 2);
                const uint32_t lg = pack_bf16(g0, g1);
                float e0, e1;
                asm("ex2.approx.ftz.f32 %0, %1;" : "=f"(e0) : "f"(bf_lo(lg) * tok));
                asm("ex2.approx.ftz.f32 %0, %1;" : "=f"(e1) : "f"(bf_hi(lg) * tok));
                const uint32_t gg = pack_bf16(__fdividef(1.f, 1.f + e0), __fdividef(1.f, 1.f + e1));
                g0 = bf_lo(gg); g1 = bf_hi(gg);
                asm volatile("" : "+f"(g0), "+f"(g1));
            }
            issue2(a1, 1); commit();
            retire(); load_a0(4); peek();
            reg_fence(kv);
            if (wg == 0) { bar_arrive<5, 256>(); bar_sync<1, 128>(); } else bar_sync<5, 256>();
            auto stage_kv = [&](int hh) {
                const int d = w4 * 16 + g8 + 8 * hh;
                const bool h0 = d < 28;
                const uint32_t rowa = sb + OFF_STG + wg * 8192 + d * 128 + q4 * 8;
                #pragma unroll
                for (int t = 0; t < 4; t++) {
                    float v0 = h0 ? kv[4 * t + 2 * hh] : kv[4 * t + 12 + 2 * hh];
                    float v1 = h0 ? kv[4 * t + 2 * hh + 1] : kv[4 * t + 13 + 2 * hh];
                    if (t == 0 && !h0 && q4 == 0) v0 = kv[28 + 2 * hh];
                    if (d < 56 && !(t == 3 && h0 && q4 == 2))
                        asm volatile("st.shared.v2.f32 [%0], {%1, %2};" :: "r"(rowa + ((t ^ (g8 & 3)) << 5)), "f"(v0), "f"(v1) : "memory");
                }
                if (h0 && q4 == 0)
                    asm volatile("st.shared.v2.f32 [%0], {%1, %1};" :: "r"(rowa + ((3 ^ (g8 & 3)) << 5) + 16), "f"(kv[28 + 2 * hh]) : "memory");
            };
            stage_kv(0);
            issue2(a0, 1); commit();
            retire(); load_a1(4); peek();
            stage_kv(1);
            __syncwarp();
            if (lane == 0) mbar_arrive(sb + BAR_KVDONE);
            issue2(a1, 1); commit();
            retire(); load_a0(5); peek();
            auto prescale = [&](int lo, int hi) {
                const float t0 = after_issue(1.f - g0, zero), t1 = after_issue(1.f - g1, zero);
                const uint32_t s0 = pack_bf16(t0, t0), s1 = pack_bf16(t1, t1);
                #pragma unroll
                for (int i = 0; i < 32; i++) if (i >= lo && i < hi) { hp[i] = mul_bf16x2(hp[i], (i & 1) ? s1 : s0); asm volatile("" : "+r"(hp[i])); }
            };
            prescale(0, 16);
            issue2(a0, 1); commit();
            retire(); load_a1(5); peek();
            prescale(16, 32);
            issue2(a1, 1); commit();
            retire(); load_a0(6); peek();
            issue2(a0, 1); commit();
            retire(); load_a1(6); peek();
            if (wg == 1) bar_sync<4, 256>();
            const uint32_t b = begin();
            wgmma_rs128<HI128>(au, a1[0], a1[1], a1[2], a1[3], b + LO128X2 + 128, 1);
            wgmma_rs128<HI128>(au, a1[4], a1[5], a1[6], a1[7], b + LO128X2 + 512, 1);
            wg_commit();
            wgmma_rs56<HI128>(aq, a1[0], a1[1], a1[2], a1[3], b + LO128, 1);
            wgmma_rs56<HI128>(aq, a1[4], a1[5], a1[6], a1[7], b + LO128 + 384, 1);
            commit();
            if (wg == 0) bar_arrive<4, 256>();
            wg_wait<2>(); release(old);
            load_a0(0); peek();
            wg_wait<1>();
            reg_fence(au);
        }
        #pragma unroll
        for (int i = 0; i < 32; i++) hp[i] = mul_bf16x2(hp[i], pack_bf16(au[2 * i], au[2 * i + 1]));
        reg_fence_part<0, 32>(hp);

        float ag[96];
        uint32_t op[16];
        {
            auto issue3 = [&](uint32_t (&a)[8], int sd) {
                const uint32_t b = begin();
                wgmma_rs192<HI64>(ag, a[0], a[1], a[2], a[3], b + LO64, sd);
                wgmma_rs192<HI64>(ag, a[4], a[5], a[6], a[7], b + LO64 + 384, 1);
            };
            uint32_t pq[16];
            issue3(a0, 0); commit();
            retire();
            reg_fence(aq);
            load_a1(0); peek();
            pq[14] = 0u; pq[15] = 0u;
            bool aux = false;
            #pragma unroll
            for (int st = 1; st < 12; st++) {
                if (st & 1) issue3(a1, 1); else issue3(a0, 1);
                commit();
                const float tok = st < 8 ? after_issue(kLog2e, zero) : 0.f;
                if (st == 11) aux = mbar_try(sb + BAR_AUX, 0);
                retire();
                if (st & 1) load_a0((st + 1) >> 1); else load_a1(st >> 1);
                peek();
                if (st < 8) {
                    const int i = 2 * st - 2;
                    pq[i] = pack_bf16(phi(aq[2 * i], tok), phi(aq[2 * i + 1], tok));
                    pq[i + 1] = pack_bf16(phi(aq[2 * i + 2], tok), phi(aq[2 * i + 3], tok));
                    asm volatile("" : "+r"(pq[i]), "+r"(pq[i + 1]));
                }
            }
            if (!aux) mbar_wait(sb + BAR_AUX, 0);
            if (wg == 1) bar_sync<4, 256>();
            float nd[32];
            issue3(a0, 1);
            {
                const uint32_t dk = dsb + LO128 + ((OFF_STG + 8192) >> 4);
                #pragma unroll
                for (int ks = 0; ks < 4; ks++) wgmma_rs64<HI128>(nd, pq[4 * ks], pq[4 * ks + 1], pq[4 * ks + 2], pq[4 * ks + 3], dk + ks * 128, ks);
            }
            commit();
            retire(); load_a1(6); peek();
            issue3(a1, 1); commit();
            if (wg == 0) bar_arrive<4, 256>();
            ready = mbar_try(sb + p4_bar(0), p4_par(0));
            retire();
            reg_fence(nd);
            const int src = lane & ~3;
            const float s00 = __fdividef(g0, __shfl_sync(0xffffffffu, nd[28], src) + 1e-6f);
            const float s01 = __fdividef(g0, __shfl_sync(0xffffffffu, nd[29], src) + 1e-6f);
            const float s10 = __fdividef(g1, __shfl_sync(0xffffffffu, nd[30], src) + 1e-6f);
            const float s11 = __fdividef(g1, __shfl_sync(0xffffffffu, nd[31], src) + 1e-6f);
            #pragma unroll
            for (int t = 0; t < 7; t++) {
                const bool h1 = t > 3 || (t == 3 && q4 >= 2);
                const float sa = h1 ? s01 : s00, sc = h1 ? s11 : s10;
                op[2 * t] = pack_bf16(nd[4 * t] * sa, nd[4 * t + 1] * sa);
                op[2 * t + 1] = pack_bf16(nd[4 * t + 2] * sc, nd[4 * t + 3] * sc);
            }
            op[14] = 0u; op[15] = 0u;
            reg_fence(op);
        }

        float oa[32], ob[32];
        int c = j == 7 ? 0 : j;
        const int wsh = __shfl_sync(0xffffffffu, warp * 16, 0);
        const uint32_t sh0 = par * 768, sh1 = par * 1024;
        bool ready2 = false;
        auto issue_d = [&](float (&o)[32], int c0, int half) {
            const int n = 3 * c0;
            if (half == 0) {
                if (!ready) mbar_wait(sb + p4_bar(n), p4_par(n));
                if (!ready2) mbar_wait(sb + p4_bar(n + 1), p4_par(n + 1));
                ready = mbar_try(sb + p4_bar(n + 2), p4_par(n + 2));
            }
            wg_fence();
            const uint32_t b = dsb + LO128 + (p4_off(n) >> 4);
            #pragma unroll
            for (int ks = 7 * half; ks < 7 * half + 7; ks++)
                wgmma_rs64<HI128>(o, hp[4 * ks], hp[4 * ks + 1], hp[4 * ks + 2], hp[4 * ks + 3],
                                  b + ks * 128 + (ks < 8 ? sh0 : 0u - sh1), ks);
        };
        auto issue_o = [&](float (&o)[32], int c0) {
            const int n = 3 * c0 + 2;
            if (!ready) mbar_wait(sb + p4_bar(n), p4_par(n));
            if (c0 < 6) {
                ready = mbar_try(sb + p4_bar(n + 1), p4_par(n + 1));
                ready2 = mbar_try(sb + p4_bar(n + 2), p4_par(n + 2));
            }
            wg_fence();
            const uint32_t b = dsb + LO128 + (p4_off(n) >> 4);
            #pragma unroll
            for (int ks = 0; ks < 4; ks++) wgmma_rs64<HI128>(o, op[4 * ks], op[4 * ks + 1], op[4 * ks + 2], op[4 * ks + 3], b + ks * 128, 1);
            wg_commit();
        };
        auto ship = [&](float (&o)[32], int c0) {
            reg_fence(o);
            const uint32_t so = xa + OFF_OUT + (c0 & 1) * 16384;
            #pragma unroll
            for (int t = 0; t < 4; t++)
                stsm4(so + (lx ^ (t * 32)), pack_bf16(o[8 * t], o[8 * t + 1]), pack_bf16(o[8 * t + 2], o[8 * t + 3]),
                      pack_bf16(o[8 * t + 4], o[8 * t + 5]), pack_bf16(o[8 * t + 6], o[8 * t + 7]));
            fence_async_smem();
            __syncwarp();
            if (elect_one()) {
                tma_reduce2d(&mp.out, sb + OFF_OUT + (c0 & 1) * 16384 + wsh * 128, 64 * c, row0 + wsh);
                asm volatile("cp.async.bulk.commit_group;" ::: "memory");
            }
            if (++c == 7) c = 0;
        };
        auto finish_h = [&]() {
            reg_fence(ag);
            release(cur);
            const uint32_t uu = pack_bf16(1.f - g0, 1.f - g1);
            const float u0 = bf_lo(uu), u1 = bf_hi(uu);
            #pragma unroll
            for (int i = 0; i < 24; i++) {
                const float u = (i & 1) ? u1 : u0;
                hp[32 + i] = mul_bf16x2(pack_relu_bf16(ag[2 * i], ag[2 * i + 1]), pack_bf16(ag[48 + 2 * i] * u, ag[49 + 2 * i] * u));
            }
            reg_fence_part<32, 56>(hp);
        };
        ready2 = mbar_try(sb + p4_bar(1), p4_par(1));
        wg_wait<0>();
        finish_h();
        #pragma unroll
        for (int c0 = 0; c0 < 7; c0++) {
            float (&o)[32] = (c0 & 1) ? ob : oa;
            if (c0 > 0 || wg == 1) turn_wait();
            issue_d(o, c0, 0);
            issue_d(o, c0, 1);
            issue_o(o, c0);
            if (!(c0 == 6 && wg == 1)) turn_pass();
            if (c0 >= 2) {
                if (elect_one()) asm volatile("cp.async.bulk.wait_group.read 1;" ::: "memory");
                __syncwarp();
            }
            wg_wait<0>();
            if (c0 < 2) { release(3 * c0); release(3 * c0 + 1); release(3 * c0 + 2); }
            ship(o, c0);
        }
        if (elect_one()) asm volatile("cp.async.bulk.wait_group.read 0;" ::: "memory");
    }
}

typedef CUresult (*EncodeFn)(CUtensorMap*, CUtensorMapDataType, cuuint32_t, void*, const cuuint64_t*, const cuuint64_t*,
                             const cuuint32_t*, const cuuint32_t*, CUtensorMapInterleave, CUtensorMapSwizzle,
                             CUtensorMapL2promotion, CUtensorMapFloatOOBfill);

void make_map(EncodeFn enc, CUtensorMap* m, const void* base, int rank, const cuuint64_t* dims, const cuuint64_t* strides,
              cuuint32_t b0, cuuint32_t b1, cuuint32_t b2, CUtensorMapSwizzle sw) {
    const cuuint32_t es[3] = {1, 1, 1}, box[3] = {b0, b1, b2};
    enc(m, CU_TENSOR_MAP_DATA_TYPE_BFLOAT16, rank, const_cast<void*>(base), dims, strides, box, es,
        CU_TENSOR_MAP_INTERLEAVE_NONE, sw, CU_TENSOR_MAP_L2_PROMOTION_L2_128B, CU_TENSOR_MAP_FLOAT_OOB_FILL_NONE);
}

}

extern "C" void kernel_launch(void* const* d_in, const int* in_sizes, int n_in, void* d_out, int out_size) {
    (void)in_sizes; (void)n_in; (void)out_size;
    static EncodeFn enc = nullptr;
    if (!enc) {
        void* fn = nullptr;
        cudaDriverEntryPointQueryResult st;
        cudaGetDriverEntryPoint("cuTensorMapEncodeTiled", &fn, cudaEnableDefault, &st);
        enc = (EncodeFn)fn;
        cudaFuncSetAttribute(fused_kernel, cudaFuncAttributeMaxDynamicSharedMemorySize, SMEM_BYTES);
    }
    Maps mp;
    const cuuint64_t dimx[2] = {kD, kS}, dimd[2] = {kD, kF}, dimo[2] = {kD, kD}, strd[1] = {kD * 2};
    make_map(enc, &mp.x, d_in[0], 2, dimx, strd, 64, 128, 1, CU_TENSOR_MAP_SWIZZLE_128B);
    make_map(enc, &mp.out, d_out, 2, dimx, strd, 64, 16, 1, CU_TENSOR_MAP_SWIZZLE_128B);
    make_map(enc, &mp.d, d_in[6], 2, dimd, strd, 64, 56, 1, CU_TENSOR_MAP_SWIZZLE_128B);
    make_map(enc, &mp.o, d_in[2], 2, dimo, strd, 64, 32, 1, CU_TENSOR_MAP_SWIZZLE_128B);
    const cuuint64_t dimq[3] = {kD, kD, 3}, strq[2] = {3 * kD * 2, kD * 2};
    make_map(enc, &mp.kv, d_in[1], 3, dimq, strq, 56, 16, 2, CU_TENSOR_MAP_SWIZZLE_128B);
    make_map(enc, &mp.q, d_in[1], 3, dimq, strq, 56, 16, 1, CU_TENSOR_MAP_SWIZZLE_128B);
    const cuuint64_t dimf[3] = {32, kD, kF / 32}, strf[2] = {kF * 2, 64};
    const cuuint64_t dimw[3] = {64, kD, kF / 64}, strw[2] = {kF * 2, 128};
    make_map(enc, &mp.g4, d_in[4], 3, dimw, strw, 64, 16, 2, CU_TENSOR_MAP_SWIZZLE_128B);
    make_map(enc, &mp.u4, d_in[5], 3, dimw, strw, 64, 16, 2, CU_TENSOR_MAP_SWIZZLE_128B);
    make_map(enc, &mp.g3, d_in[4], 3, dimf, strf, 32, 16, 3, CU_TENSOR_MAP_SWIZZLE_64B);
    make_map(enc, &mp.u3, d_in[5], 3, dimf, strf, 32, 16, 3, CU_TENSOR_MAP_SWIZZLE_64B);
    fused_kernel<<<NCTA, NTHREADS, SMEM_BYTES>>>(mp, (const __nv_bfloat16*)d_in[7], (__nv_bfloat16*)d_out, 0u);
}
```

```cpp
#include <cuda_runtime.h>
#include <cuda_bf16.h>
#include <cuda.h>
#include <stdint.h>

namespace {

constexpr int kS = 2048, kD = 448, kF = 1792;
constexpr int NTHREADS = 384;
constexpr int NCTA = 128;
constexpr uint32_t OFF_X = 0;
constexpr uint32_t OFF_RING = 114688;
constexpr uint32_t SLOT_BYTES = 16384;
constexpr int NSLOT = 6;
constexpr uint32_t OFF_STG = 212992;
constexpr uint32_t OFF_MISC = 229376;
constexpr uint32_t SMEM_BYTES = 232448;
constexpr uint32_t BAR_FULL = OFF_MISC, BAR_EMPTY = OFF_MISC + 48, BAR_XFULL = OFF_MISC + 96;
constexpr uint32_t BAR_W = OFF_MISC + 152, BAR_KVDONE = OFF_MISC + 160, BAR_AUX = OFF_MISC + 168, BAR_P4 = OFF_MISC + 176;
constexpr uint32_t OFF_W = OFF_MISC + 256;
constexpr uint32_t SB = 1024;

__device__ __align__(128) float g_kvacc[8][2048];
__device__ unsigned int g_counter[64];

__device__ __forceinline__ void mbar_init(uint32_t bar, uint32_t cnt) {
    asm volatile("mbarrier.init.shared::cta.b64 [%0], %1;" :: "r"(bar), "r"(cnt) : "memory");
}
__device__ __forceinline__ void mbar_expect_tx(uint32_t bar, uint32_t bytes) {
    asm volatile("mbarrier.arrive.expect_tx.shared::cta.b64 _, [%0], %1;" :: "r"(bar), "r"(bytes) : "memory");
}
__device__ __forceinline__ void mbar_arrive(uint32_t bar) {
    asm volatile("mbarrier.arrive.shared::cta.b64 _, [%0];" :: "r"(bar) : "memory");
}
__device__ __forceinline__ void mbar_arrive_cluster(uint32_t bar) {
    asm volatile("mbarrier.arrive.shared::cluster.b64 _, [%0];" :: "r"(bar) : "memory");
}
__device__ __forceinline__ void mbar_wait(uint32_t bar, uint32_t parity) {
    asm volatile("{\n"
                 ".reg .pred p;\n"
                 ".reg .u32 c;\n"
                 "mov.u32 c, 0;\n"
                 "AGAIN:\n"
                 "mbarrier.try_wait.parity.shared::cta.b64 p, [%0], %1;\n"
                 "@p bra DONE;\n"
                 "add.u32 c, c, 1;\n"
                 "setp.lt.u32 p, c, 4194304;\n"
                 "@p bra AGAIN;\n"
                 "trap;\n"
                 "DONE:\n"
                 "}" :: "r"(bar), "r"(parity) : "memory");
}
__device__ __forceinline__ uint32_t mapa(uint32_t addr, uint32_t cta) {
    uint32_t r; asm("mapa.shared::cluster.u32 %0, %1, %2;" : "=r"(r) : "r"(addr), "r"(cta)); return r;
}
__device__ __forceinline__ bool elect_one() {
    uint32_t p;
    asm volatile("{ .reg .pred P; elect.sync _|P, 0xffffffff; selp.u32 %0, 1, 0, P; }" : "=r"(p));
    return p;
}
__device__ __forceinline__ void tma2d(uint32_t dst, const CUtensorMap* m, int c0, int c1, uint32_t bar) {
    asm volatile("cp.async.bulk.tensor.2d.shared::cluster.global.mbarrier::complete_tx::bytes [%0], [%1, {%3, %4}], [%2];"
                 :: "r"(dst), "l"(m), "r"(bar), "r"(c0), "r"(c1) : "memory");
}
__device__ __forceinline__ void tma2d_mc(uint32_t dst, const CUtensorMap* m, int c0, int c1, uint32_t bar) {
    asm volatile("cp.async.bulk.tensor.2d.shared::cluster.global.mbarrier::complete_tx::bytes.multicast::cluster [%0], [%1, {%3, %4}], [%2], %5;"
                 :: "r"(dst), "l"(m), "r"(bar), "r"(c0), "r"(c1), "h"((uint16_t)3) : "memory");
}
__device__ __forceinline__ void tma3d_mc(uint32_t dst, const CUtensorMap* m, int c0, int c1, int c2, uint32_t bar) {
    asm volatile("cp.async.bulk.tensor.3d.shared::cluster.global.mbarrier::complete_tx::bytes.multicast::cluster [%0], [%1, {%3, %4, %5}], [%2], %6;"
                 :: "r"(dst), "l"(m), "r"(bar), "r"(c0), "r"(c1), "r"(c2), "h"((uint16_t)3) : "memory");
}
__device__ __forceinline__ void tma_reduce2d(const CUtensorMap* m, uint32_t src, int c0, int c1) {
    asm volatile("cp.reduce.async.bulk.tensor.2d.global.shared::cta.add.bulk_group [%0, {%2, %3}], [%1];"
                 :: "l"(m), "r"(src), "r"(c0), "r"(c1) : "memory");
}
__device__ __forceinline__ void bulk_reduce_f32(float* dst, uint32_t src, uint32_t bytes) {
    asm volatile("cp.reduce.async.bulk.global.shared::cta.bulk_group.add.f32 [%0], [%1], %2;" :: "l"(dst), "r"(src), "r"(bytes) : "memory");
}
__device__ __forceinline__ bool mbar_try(uint32_t bar, uint32_t parity) {
    uint32_t ok;
    asm volatile("{ .reg .pred p; mbarrier.test_wait.parity.shared::cta.b64 p, [%1], %2; selp.u32 %0, 1, 0, p; }"
                 : "=r"(ok) : "r"(bar), "r"(parity) : "memory");
    return ok;
}
__device__ __forceinline__ void prefetch_map(const CUtensorMap* m) {
    asm volatile("prefetch.tensormap [%0];" :: "l"(m) : "memory");
}
__device__ __forceinline__ void wg_fence() { asm volatile("wgmma.fence.sync.aligned;" ::: "memory"); }
__device__ __forceinline__ void wg_commit() { asm volatile("wgmma.commit_group.sync.aligned;" ::: "memory"); }
template <int N> __device__ __forceinline__ void wg_wait() { asm volatile("wgmma.wait_group.sync.aligned %0;" :: "n"(N) : "memory"); }
template <int N> __device__ __forceinline__ void reg_fence(float (&d)[N]) {
#pragma unroll
    for (int i = 0; i < N; i++) asm volatile("" : "+f"(d[i]) :: "memory");
}
template <int N> __device__ __forceinline__ void reg_fence(uint32_t (&d)[N]) {
#pragma unroll
    for (int i = 0; i < N; i++) asm volatile("" : "+r"(d[i]) :: "memory");
}
template <int LO, int HI, int N> __device__ __forceinline__ void reg_fence_part(uint32_t (&d)[N]) {
#pragma unroll
    for (int i = LO; i < HI; i++) asm volatile("" : "+r"(d[i]) :: "memory");
}
__device__ __forceinline__ void fence_async_smem() { asm volatile("fence.proxy.async.shared::cta;" ::: "memory"); }
template <int ID, int N> __device__ __forceinline__ void bar_sync() { asm volatile("bar.sync %0, %1;" :: "n"(ID), "n"(N) : "memory"); }
template <int ID, int N> __device__ __forceinline__ void bar_arrive() { asm volatile("bar.arrive %0, %1;" :: "n"(ID), "n"(N) : "memory"); }
__device__ __forceinline__ void ldsm4(uint32_t* r, uint32_t addr) {
    asm volatile("ldmatrix.sync.aligned.m8n8.x4.shared.b16 {%0, %1, %2, %3}, [%4];"
                 : "=r"(r[0]), "=r"(r[1]), "=r"(r[2]), "=r"(r[3]) : "r"(addr) : "memory");
}
__device__ __forceinline__ void stsm4(uint32_t addr, uint32_t r0, uint32_t r1, uint32_t r2, uint32_t r3) {
    asm volatile("stmatrix.sync.aligned.m8n8.x4.shared.b16 [%0], {%1, %2, %3, %4};"
                 :: "r"(addr), "r"(r0), "r"(r1), "r"(r2), "r"(r3) : "memory");
}
__device__ __forceinline__ uint32_t lds32(uint32_t addr) {
    uint32_t r; asm volatile("ld.shared.u32 %0, [%1];" : "=r"(r) : "r"(addr)); return r;
}
__device__ __forceinline__ float4 lds128f(uint32_t addr) {
    float4 r; asm volatile("ld.shared.v4.f32 {%0, %1, %2, %3}, [%4];" : "=f"(r.x), "=f"(r.y), "=f"(r.z), "=f"(r.w) : "r"(addr)); return r;
}
__device__ __forceinline__ uint32_t clock32() { uint32_t t; asm volatile("mov.u32 %0, %%clock;" : "=r"(t)); return t; }
__device__ __forceinline__ uint32_t pack_bf16(float lo, float hi) {
    uint32_t r; asm("cvt.rn.bf16x2.f32 %0, %1, %2;" : "=r"(r) : "f"(hi), "f"(lo)); return r;
}
__device__ __forceinline__ uint32_t pack_relu_bf16(float lo, float hi) {
    uint32_t r; asm("cvt.rn.relu.bf16x2.f32 %0, %1, %2;" : "=r"(r) : "f"(hi), "f"(lo)); return r;
}
__device__ __forceinline__ uint32_t mul_bf16x2(uint32_t a, uint32_t b) {
    uint32_t r; asm("mul.rn.bf16x2 %0, %1, %2;" : "=r"(r) : "r"(a), "r"(b)); return r;
}
__device__ __forceinline__ float phi(float t, float log2e) {
    float e;
    asm("ex2.approx.ftz.f32 %0, %1;" : "=f"(e) : "f"(fminf(t * log2e, 0.f)));
    return e + (fmaxf(t, 0.f) + 1e-6f);
}
__device__ __forceinline__ float after_issue(float v, uint32_t zero) {
    return __uint_as_float(__float_as_uint(v) | (clock32() & zero));
}
constexpr float kLog2e = 1.4426950408889634f;
__device__ __forceinline__ float bf_lo(uint32_t v) { return __uint_as_float(v << 16); }
__device__ __forceinline__ float bf_hi(uint32_t v) { return __uint_as_float(v & 0xffff0000u); }
constexpr uint32_t HI128 = (1024 >> 4) | (1u << 30);
constexpr uint32_t HI64 = (512 >> 4) | (2u << 30);
constexpr uint32_t LO128 = 1u << 16, LO64 = (1024u >> 4) << 16, LO128X2 = (2048u >> 4) << 16;
constexpr uint32_t QB = 16 * 112;
constexpr uint32_t TX1 = 2 * (2 * QB + 4096), TX2 = 2 * (QB + 4096), TX3 = 12288;
__device__ __forceinline__ void grid_arrive(unsigned int* c) {
    asm volatile("fence.acq_rel.gpu;" ::: "memory");
    asm volatile("red.relaxed.gpu.global.add.u32 [%0], 1;" :: "l"(c) : "memory");
}
__device__ __forceinline__ void grid_wait(const unsigned int* c, unsigned int target) {
    unsigned int v; int it = 0;
    do {
        asm volatile("ld.relaxed.gpu.global.u32 %0, [%1];" : "=r"(v) : "l"(c) : "memory");
        if (++it > (1 << 22)) asm volatile("trap;");
    } while ((int)(v - target) < 0);
    asm volatile("ld.acquire.gpu.global.u32 %0, [%1];" : "=r"(v) : "l"(c) : "memory");
}


__host__ __device__ constexpr uint32_t p4_pack(int n) { return (n / 3) * 36864 + (n % 3) * 14336; }
__host__ __device__ constexpr uint32_t p4_off(int n) {
    return n < 6 ? OFF_X + p4_pack(n) : n < 14 ? OFF_RING + p4_pack(n - 6) : n == 14 ? OFF_X + p4_pack(6) : OFF_X + p4_pack(n - 15);
}
__host__ __device__ constexpr uint32_t p4_bar(int n) {
    return n < 6 ? BAR_XFULL + 8 * n : n < 12 ? BAR_FULL + 8 * (n - 6) : n < 14 ? BAR_P4 + 8 * (n - 12)
                 : n == 14 ? BAR_XFULL + 48 : BAR_XFULL + 8 * (n - 15);
}
__host__ __device__ constexpr uint32_t p4_par(int n) { return (n < 12 || n == 14) ? 1 : 0; }
constexpr uint32_t OFF_OUT = OFF_X + 5 * 16384;
static_assert(p4_off(7) == p4_off(6) + 14336 && p4_off(13) == p4_off(12) + 14336 && p4_off(16) == p4_off(15) + 14336, "Wd halves");
static_assert(p4_off(13) + 14336 <= OFF_STG + 8192 && p4_off(14) + 8192 == OFF_OUT, "pass-4 layout");

struct Ring {
    uint32_t slot, phase;
    __device__ __forceinline__ void advance() { if (++slot == NSLOT) { slot = 0; phase ^= 1; } }
};

struct Maps { CUtensorMap x, kv, q, g4, g3, u4, u3, d, o, out; };

__global__ void __cluster_dims__(2, 1, 1) __launch_bounds__(NTHREADS, 1)
fused_kernel(const __grid_constant__ Maps mp, const __nv_bfloat16* __restrict__ gate_w, __nv_bfloat16* __restrict__ out,
             uint32_t zero)
{
    extern __shared__ __align__(1024) unsigned char smem[];
    const uint32_t sb = (uint32_t)__cvta_generic_to_shared(smem);
    const int tid = threadIdx.x, warp = tid >> 5, lane = tid & 31;
    const int rank = blockIdx.x & 1, j = (blockIdx.x >> 1) & 7;
    const int row0 = ((blockIdx.x >> 4) * 2 + rank) * 128;
    const int par = j & 1;
    const int g4i = (7 * j + 3 * par) >> 1;

    if (warp == 9) {
        if (elect_one()) {
            prefetch_map(&mp.x);
            mbar_init(sb + BAR_XFULL, 1);
            mbar_expect_tx(sb + BAR_XFULL, 16384);
            tma2d(sb + OFF_X, &mp.x, 0, row0, sb + BAR_XFULL);
            asm volatile("fence.mbarrier_init.release.cluster;" ::: "memory");
        }
        __syncwarp();
    } else if (warp == 8) {
        if (elect_one()) {
            #pragma unroll
            for (int s = 0; s < NSLOT; s++) mbar_init(sb + BAR_FULL + 8 * s, 1);
            asm volatile("fence.mbarrier_init.release.cluster;" ::: "memory");
            mbar_expect_tx(sb + BAR_FULL, TX1);
        }
        __syncwarp();
    } else if (warp == 10) {
        if (elect_one()) {
            #pragma unroll
            for (int s = 1; s < 7; s++) mbar_init(sb + BAR_XFULL + 8 * s, 1);
            mbar_init(sb + BAR_KVDONE, 8);
            mbar_init(sb + BAR_AUX, 3);
            asm volatile("fence.mbarrier_init.release.cluster;" ::: "memory");
            if ((sb & 0xFFFFFF) != SB) asm volatile("trap;");
        }
        __syncwarp();
    } else if (warp == 11) {
        if (elect_one()) {
            #pragma unroll
            for (int s = 0; s < NSLOT; s++) mbar_init(sb + BAR_EMPTY + 8 * s, 4);
            mbar_init(sb + BAR_P4, 1);
            mbar_init(sb + BAR_P4 + 8, 1);
            asm volatile("fence.mbarrier_init.release.cluster;" ::: "memory");
        }
        __syncwarp();
    } else if (warp == 2) {
        if (elect_one()) {
            mbar_init(sb + BAR_W, 1);
            asm volatile("fence.mbarrier_init.release.cluster;" ::: "memory");
            mbar_expect_tx(sb + BAR_W, 896);
            asm volatile("cp.async.bulk.shared::cluster.global.mbarrier::complete_tx::bytes [%0], [%1], 896, [%2];"
                         :: "r"(sb + OFF_W), "l"(gate_w), "r"(sb + BAR_W) : "memory");
        }
        __syncwarp();
    }
    asm volatile("barrier.cluster.arrive.relaxed.aligned;" ::: "memory");
    if (warp == 8) {
        if (elect_one()) { prefetch_map(&mp.kv); prefetch_map(&mp.g4); }
        __syncwarp();
    }
    asm volatile("barrier.cluster.wait.aligned;" ::: "memory");
    if (warp == 8) {
        if (elect_one()) {
            tma3d_mc(sb + OFF_RING + rank * 8192 + 4096, &mp.kv, 56 * j, 16 * rank, 1, sb + BAR_FULL);
            tma3d_mc(sb + OFF_RING + rank * 8192, &mp.g4, 0, 16 * rank, g4i, sb + BAR_FULL);
        }
        __syncwarp();
    }

    if (warp >= 8) {
        asm volatile("setmaxnreg.dec.sync.aligned.u32 40;");
        if (warp == 8) {
            if (elect_one()) {
                Ring r{1, 1};
                auto acquire = [&](uint32_t bytes) -> uint32_t {
                    mbar_wait(sb + BAR_EMPTY + 8 * r.slot, r.phase);
                    mbar_expect_tx(sb + BAR_FULL + 8 * r.slot, bytes);
                    return sb + OFF_RING + r.slot * SLOT_BYTES;
                };
                #pragma unroll 1
                for (int s = 1; s < 14; s++) {
                    const uint32_t dst = acquire(TX1) + rank * 8192;
                    tma3d_mc(dst + 4096, &mp.kv, 56 * j, 32 * s + 16 * rank, 1, sb + BAR_FULL + 8 * r.slot);
                    tma3d_mc(dst, &mp.g4, 0, 32 * s + 16 * rank, g4i, sb + BAR_FULL + 8 * r.slot);
                    r.advance();
                    if ((s & 1) && s < 12) {
                        const int n = (s >> 1) + 1;
                        mbar_expect_tx(sb + BAR_XFULL + 8 * n, 16384);
                        tma2d(sb + OFF_X + n * 16384, &mp.x, 64 * n, row0, sb + BAR_XFULL + 8 * n);
                    }
                    if (s == 5) {
                        prefetch_map(&mp.q); prefetch_map(&mp.u4); prefetch_map(&mp.g3); prefetch_map(&mp.u3);
                        prefetch_map(&mp.d); prefetch_map(&mp.o); prefetch_map(&mp.out);
                    }
                }
                #pragma unroll 1
                for (int s = 0; s < 14; s++) {
                    const uint32_t dst = acquire(TX2) + rank * 6144;
                    tma3d_mc(dst, &mp.q, 56 * j, 32 * s + 16 * rank, 0, sb + BAR_FULL + 8 * r.slot);
                    tma3d_mc(dst + 2048, &mp.u4, 0, 32 * s + 16 * rank, g4i, sb + BAR_FULL + 8 * r.slot);
                    r.advance();
                }
                const int cfirst = j == 7 ? 0 : j;
                auto load4 = [&](int n) {
                    int c = cfirst + n / 3;
                    if (c >= 7) c -= 7;
                    mbar_expect_tx(sb + p4_bar(n), n % 3 == 2 ? 8192 : 14336);
                    if (n % 3 == 2) tma2d_mc(sb + p4_off(n) + rank * 4096, &mp.o, 64 * c, 56 * j + 32 * rank, sb + p4_bar(n));
                    else tma2d_mc(sb + p4_off(n) + rank * 7168, &mp.d, 64 * c, 224 * j + 112 * (n % 3) + 56 * rank, sb + p4_bar(n));
                };
                #pragma unroll 1
                for (int s = 0; s < 14; s++) {
                    const uint32_t dst = acquire(TX3) + rank * 6144;
                    tma3d_mc(dst, &mp.g3, 0, 32 * s + 16 * rank, 7 * j + 4 - 4 * par, sb + BAR_FULL + 8 * r.slot);
                    tma3d_mc(dst + 3072, &mp.u3, 0, 32 * s + 16 * rank, 7 * j + 4 - 4 * par, sb + BAR_FULL + 8 * r.slot);
                    r.advance();
                    if (s == 7) load4(0);
                    if (s == 9) load4(1);
                    if (s == 11) load4(2);
                    if (s == 13) { load4(3); load4(4); }
                }
                mbar_wait(sb + BAR_EMPTY, 0);      load4(6);
                mbar_wait(sb + BAR_EMPTY + 8, 0);  load4(5); load4(7); load4(14);
                mbar_wait(sb + BAR_EMPTY + 16, 0); load4(8);
                mbar_wait(sb + BAR_EMPTY + 24, 0); load4(9); load4(10);
                mbar_wait(sb + BAR_EMPTY + 32, 0); load4(11);
                mbar_wait(sb + BAR_EMPTY + 40, 0); load4(12);
                mbar_wait(sb + BAR_AUX, 0);        load4(13);
                #pragma unroll
                for (int n = 15; n < 21; n++) {
                    mbar_wait(sb + BAR_EMPTY + 8 * (n - 15), 1);
                    __nanosleep(100);
                    load4(n);
                }
            }
        } else {
            const int ht = tid - 288;
            unsigned int cnt0;
            asm volatile("ld.relaxed.gpu.global.u32 %0, [%1];" : "=r"(cnt0) : "l"(&g_counter[32]) : "memory");
            const unsigned int target = ((cnt0 >> 7) + 1) << 7;
            if (warp == 9) {
                reinterpret_cast<float4*>(&g_kvacc[0][0])[blockIdx.x * 32 + lane] = make_float4(0.f, 0.f, 0.f, 0.f);
                asm volatile("fence.proxy.async.global;" ::: "memory");
                __syncwarp();
                if (lane == 0) grid_arrive(&g_counter[0]);
                mbar_wait(sb + BAR_XFULL + 8 * 6, 0);
                uint4* o = reinterpret_cast<uint4*>(out) + blockIdx.x * 896 + lane;
                #pragma unroll 4
                for (int q = 0; q < 28; q++) o[q * 32] = make_uint4(0, 0, 0, 0);
                asm volatile("fence.proxy.async.global;" ::: "memory");
                __syncwarp();
                if (lane == 0) {
                    asm volatile("fence.acq_rel.gpu;" ::: "memory");
                    grid_wait(&g_counter[0], target);
                }
                __syncwarp();
            }
            mbar_wait(sb + BAR_KVDONE, 0);
            {
                #pragma unroll
                for (int i0 = 0; i0 < 5; i0 += 2) {
                    float4 pa[2], pb[2];
                    #pragma unroll
                    for (int i = 0; i < 2 && i0 + i < 5; i++) {
                        const int q = min(ht + 96 * (i0 + i), 447);
                        pa[i] = lds128f(sb + OFF_STG + q * 16); pb[i] = lds128f(sb + OFF_STG + 8192 + q * 16);
                    }
                    #pragma unroll
                    for (int i = 0; i < 2 && i0 + i < 5; i++) {
                        const int q = ht + 96 * (i0 + i);
                        if (q < 448) asm volatile("st.shared.v4.f32 [%0], {%1, %2, %3, %4};" :: "r"(sb + OFF_STG + q * 16),
                            "f"(pa[i].x + pb[i].x), "f"(pa[i].y + pb[i].y), "f"(pa[i].z + pb[i].z), "f"(pa[i].w + pb[i].w) : "memory");
                    }
                }
                fence_async_smem();
            }
            bar_sync<3, 96>();
            if (warp == 9) {
                if (elect_one()) {
                    bulk_reduce_f32(&g_kvacc[j][0], sb + OFF_STG, 7168);
                    asm volatile("cp.async.bulk.commit_group;" ::: "memory");
                    asm volatile("cp.async.bulk.wait_group 0;" ::: "memory");
                    asm volatile("red.relaxed.gpu.global.add.u32 [%0], 1;" :: "l"(&g_counter[32]) : "memory");
                }
            }
            __syncwarp();
            #pragma unroll
            for (int i = 0; i < 3; i++) {
                const int q = ht + 96 * i;
                const int d = q < 168 ? q / 3 : 56 + ((q - 168) >> 3);
                const int c = q < 168 ? (q - 3 * d + (d < 28 ? 4 : 0)) : (q & 7);
                if (q < 232) asm volatile("st.shared.v4.u32 [%0], {%1, %1, %1, %1};" :: "r"(sb + OFF_STG + 8192 + d * 128 + ((c ^ (d & 7)) << 4)), "r"(0) : "memory");
            }
            uint32_t plan[3];
            #pragma unroll
            for (int i = 0; i < 3; i++) {
                const int q = min(ht + 96 * i, 279), d = q / 5, m = q - 5 * d;
                const bool h0 = d < 28;
                const int c = m == 4 ? 7 : (h0 ? m : m + 3), pc = m < 4 ? m : (h0 ? 3 : 0);
                const int kind = m == 4 ? (h0 ? 3 : 4) : c == 3 ? (h0 ? 1 : 2) : 0;
                plan[i] = (d * 128 + ((c ^ (d & 7)) << 4)) | ((d * 4 + (pc ^ (d & 3))) << 13) | (kind << 23);
                asm volatile("" : "+r"(plan[i]));
            }
            if (lane == 0) grid_wait(&g_counter[32], target);
            __syncwarp();
            const float4* src = reinterpret_cast<const float4*>(&g_kvacc[j][0]);
            float4 va[3], vb[3];
            #pragma unroll
            for (int i = 0; i < 3; i++) {
                const float4* p = src + ((plan[i] >> 12) & 0x7fe);
                va[i] = __ldcg(p); vb[i] = __ldcg(p + 1);
            }
            #pragma unroll
            for (int i = 0; i < 3; i++) {
                const uint32_t kind = plan[i] >> 23;
                uint32_t w0 = pack_bf16(va[i].x, va[i].y), w1 = pack_bf16(va[i].z, va[i].w);
                uint32_t w2 = pack_bf16(vb[i].x, vb[i].y), w3 = pack_bf16(vb[i].z, vb[i].w);
                if (kind == 3) w0 = w2 & 0xffffu;
                if (kind == 4) w0 <<= 16;
                if (kind == 2) w0 = 0u;
                if (kind >= 2) w1 = 0u;
                if (kind != 0 && kind != 2) w2 = w3 = 0u;
                if (i < 2 || ht < 88)
                    asm volatile("st.shared.v4.u32 [%0], {%1, %2, %3, %4};"
                                 :: "r"(sb + OFF_STG + 8192 + (plan[i] & 0x1fff)), "r"(w0), "r"(w1), "r"(w2), "r"(w3) : "memory");
            }
            fence_async_smem();
            __syncwarp();
            if (lane == 0) mbar_arrive(sb + BAR_AUX);
        }
    } else {
        asm volatile("setmaxnreg.inc.sync.aligned.u32 232;");
        const int wg = warp >> 2, w4 = warp & 3;
        const int q4 = lane & 3, g8 = lane >> 2;
        const uint32_t lx = ((lane >> 4) ^ (lane & 7)) << 4;
        const uint32_t xa = sb + OFF_X + (warp * 16 + (lane & 15)) * 128;
        const uint32_t empty_dst = mapa(sb + BAR_EMPTY, w4 & 1);
        const bool signaller = lane == 0 && w4 < 2;
        constexpr uint32_t dsb = SB >> 4;
        Ring r{0, 0};
        uint32_t cur = 0, old = 0;
        bool ready = false;
        auto release = [&](uint32_t slot) { if (signaller) mbar_arrive_cluster(empty_dst + 8 * slot); };
        auto turn_wait = [&]() { if (wg == 0) bar_sync<6, 256>(); else bar_sync<7, 256>(); };
        auto turn_pass = [&]() { if (wg == 0) bar_arrive<7, 256>(); else bar_arrive<6, 256>(); };
        auto begin = [&]() -> uint32_t {
            if (!ready) mbar_wait(sb + BAR_FULL + 8 * r.slot, r.phase);
            wg_fence();
            return dsb + (OFF_RING >> 4) + r.slot * (SLOT_BYTES >> 4);
        };
        auto commit = [&]() { wg_commit(); old = cur; cur = r.slot; r.advance(); };
        auto retire = [&]() { wg_wait<1>(); release(old); };
        auto peek = [&]() { ready = mbar_try(sb + BAR_FULL + 8 * r.slot, r.phase); };
        uint32_t a0[8], a1[8];
        auto load_a0 = [&](int kc) { ldsm4(a0, xa + kc * 16384 + lx); ldsm4(a0 + 4, xa + kc * 16384 + (lx ^ 32)); };
        auto load_a1 = [&](int kc) { ldsm4(a1, xa + kc * 16384 + (lx ^ 64)); ldsm4(a1 + 4, xa + kc * 16384 + (lx ^ 96)); };

        uint32_t hp[56];
        float g0, g1, av[28], agk[92];
        {
            float d0 = 0.f, d1 = 0.f, d2 = 0.f, d3 = 0.f;
            uint32_t w0[4], w1[4];
            auto issue1 = [&](uint32_t (&a)[8], int sd) {
                const uint32_t b = begin();
                wgmma_rs184<HI128>(agk, a[0], a[1], a[2], a[3], b + LO128X2, sd);
                wgmma_rs56<HI128>(av, a[0], a[1], a[2], a[3], b + LO128 + 384, sd);
                wgmma_rs184<HI128>(agk, a[4], a[5], a[6], a[7], b + LO128X2 + 512, 1);
                wgmma_rs56<HI128>(av, a[4], a[5], a[6], a[7], b + LO128 + 896, 1);
                commit();
            };
            auto issue1s = [&](uint32_t (&a)[8]) {
                const uint32_t b = begin();
                wgmma_rs184<HI128>(agk, a[0], a[1], a[2], a[3], b + LO128X2, 1);
                wgmma_rs184<HI128>(agk, a[4], a[5], a[6], a[7], b + LO128X2 + 512, 1);
                wg_commit();
                wgmma_rs56<HI128>(av, a[0], a[1], a[2], a[3], b + LO128 + 384, 1);
                wgmma_rs56<HI128>(av, a[4], a[5], a[6], a[7], b + LO128 + 896, 1);
                commit();
            };
            auto load_w = [&](uint32_t (&w)[4], int s) {
                #pragma unroll
                for (int e = 0; e < 4; e++) w[e] = lds32(sb + OFF_W + s * 64 + q4 * 4 + e * 16);
            };
            auto dot = [&](uint32_t (&a)[8], uint32_t (&w)[4]) {
                #pragma unroll
                for (int e = 0; e < 4; e++) {
                    const uint32_t p0 = mul_bf16x2(a[2 * e], w[e]), p1 = mul_bf16x2(a[2 * e + 1], w[e]);
                    d0 += bf_lo(p0); d2 += bf_hi(p0); d1 += bf_lo(p1); d3 += bf_hi(p1);
                }
                asm volatile("" : "+f"(d0), "+f"(d1), "+f"(d2), "+f"(d3));
            };
            mbar_wait(sb + BAR_XFULL, 0);
            load_a0(0);
            mbar_wait(sb + BAR_W, 0);
            load_w(w0, 0);
            auto odd_stage = [&](int it, bool first, bool last) {
                wg_wait<1>();
                if (!first) release(old);
                load_a1(it);
                load_w(w1, 2 * it + 1);
                peek();
                dot(a0, w0);
                if (last && wg == 1) bar_sync<4, 256>();
                issue1s(a1);
                if (last && wg == 0) bar_arrive<4, 256>();
            };
            issue1(a0, 0);
            #pragma unroll
            for (int it = 0; it < 6; it++) {
                const bool xok = mbar_try(sb + BAR_XFULL + 8 * (it + 1), 0);
                odd_stage(it, it == 0, false);
                wg_wait<2>(); release(old);
                if (!xok) mbar_wait(sb + BAR_XFULL + 8 * (it + 1), 0);
                load_a0(it + 1);
                load_w(w0, 2 * it + 2);
                peek();
                dot(a1, w1);
                issue1(a0, 1);
            }
            odd_stage(6, false, true);
            wg_wait<2>(); release(old);
            load_a0(0);
            peek();
            dot(a1, w1);
            wg_wait<1>();
            reg_fence(agk);
            #pragma unroll
            for (int i = 0; i < 32; i++) hp[i] = pack_relu_bf16(agk[2 * i], agk[2 * i + 1]);
            reg_fence_part<0, 32>(hp);
            g0 = d0 + d2; g1 = d1 + d3;
        }

        float aq[28], au[64];
        {
            auto issue2 = [&](uint32_t (&a)[8], int sd) {
                const uint32_t b = begin();
                wgmma_rs56<HI128>(aq, a[0], a[1], a[2], a[3], b + LO128, sd);
                wgmma_rs128<HI128>(au, a[0], a[1], a[2], a[3], b + LO128X2 + 128, sd);
                wgmma_rs56<HI128>(aq, a[4], a[5], a[6], a[7], b + LO128 + 384, 1);
                wgmma_rs128<HI128>(au, a[4], a[5], a[6], a[7], b + LO128X2 + 512, 1);
            };
            const uint32_t st_base = wg == 0 ? OFF_STG : OFF_RING + 12288, st_step = wg == 0 ? 2048 : SLOT_BYTES, st_v = wg == 0 ? 8192 : 2048;
            const uint32_t sk = sb + st_base + w4 * st_step + (lane & 15) * 128;
            float tok = kLog2e;
            uint32_t pk[16];
            pk[14] = 0u; pk[15] = 0u;
            auto stage_k = [&](int lo, int hi) {
                #pragma unroll
                for (int i = 0; i < 14; i++) if (i >= lo && i < hi) pk[i] = pack_bf16(phi(agk[64 + 2 * i], tok), phi(agk[65 + 2 * i], tok));
                #pragma unroll
                for (int t = 0; t < 4; t++) {
                    const int need = t < 3 ? 4 * t + 4 : 14;
                    if (need > lo && need <= hi) stsm4(sk + (lx ^ (t * 32)), pk[4 * t], pk[4 * t + 1], pk[4 * t + 2], pk[4 * t + 3]);
                }
                #pragma unroll
                for (int i = 0; i < 14; i++) if (i >= lo && i < hi) asm volatile("" : "+r"(pk[i]));
            };
            issue2(a0, 0); commit();
            tok = after_issue(kLog2e, zero);
            retire();
            reg_fence(av);
            if (wg == 0) bar_arrive<8, 256>();
            load_a1(0); peek();
            uint32_t pv[14];
            #pragma unroll
            for (int i = 0; i < 14; i++) pv[i] = pack_bf16(av[2 * i], av[2 * i + 1]);
            if (wg == 1) bar_sync<8, 256>();
            {
                const uint32_t ones = q4 == 0 ? 0x3f803f80u : 0u;
                #pragma unroll
                for (int t = 0; t < 3; t++) stsm4(sk + st_v + (lx ^ (t * 32)), pv[4 * t], pv[4 * t + 1], pv[4 * t + 2], pv[4 * t + 3]);
                stsm4(sk + st_v + (lx ^ 96), pv[12], pv[13], ones, ones);
            }
            stage_k(0, 2);
            issue2(a1, 1); commit();
            tok = after_issue(kLog2e, zero);
            retire(); load_a0(1); peek();
            stage_k(2, 5);
            issue2(a0, 1); commit();
            tok = after_issue(kLog2e, zero);
            retire(); load_a1(1); peek();
            stage_k(5, 8);
            issue2(a1, 1); commit();
            tok = after_issue(kLog2e, zero);
            retire(); load_a0(2); peek();
            stage_k(8, 11);
            issue2(a0, 1); commit();
            tok = after_issue(kLog2e, zero);
            retire(); load_a1(2); peek();
            stage_k(11, 14);
            issue2(a1, 1); commit();
            retire(); load_a0(3); peek();
            fence_async_smem();
            if (wg == 0) bar_sync<1, 128>(); else bar_sync<2, 128>();
            float kv[32];
            issue2(a0, 1);
            {
                const uint32_t dk = dsb + LO128 + (st_base >> 4), ds = st_step >> 4, dv = st_v >> 4;
                #pragma unroll
                for (int ks = 0; ks < 4; ks++) wgmma_ss64_tt<HI128>(kv, dk + ks * ds, dk + ks * ds + dv, ks);
            }
            commit();
            tok = after_issue(-kLog2e, zero);
            retire(); load_a1(3); peek();
            {
                g0 += __shfl_xor_sync(0xffffffffu, g0, 1); g1 += __shfl_xor_sync(0xffffffffu, g1, 1);
                g0 += __shfl_xor_sync(0xffffffffu, g0, 2); g1 += __shfl_xor_sync(0xffffffffu, g1, 2);
                const uint32_t lg = pack_bf16(g0, g1);
                float e0, e1;
                asm("ex2.approx.ftz.f32 %0, %1;" : "=f"(e0) : "f"(bf_lo(lg) * tok));
                asm("ex2.approx.ftz.f32 %0, %1;" : "=f"(e1) : "f"(bf_hi(lg) * tok));
                const uint32_t gg = pack_bf16(__fdividef(1.f, 1.f + e0), __fdividef(1.f, 1.f + e1));
                g0 = bf_lo(gg); g1 = bf_hi(gg);
                asm volatile("" : "+f"(g0), "+f"(g1));
            }
            issue2(a1, 1); commit();
            retire(); load_a0(4); peek();
            reg_fence(kv);
            if (wg == 0) { bar_arrive<5, 256>(); bar_sync<1, 128>(); } else bar_sync<5, 256>();
            auto stage_kv = [&](int hh) {
                const int d = w4 * 16 + g8 + 8 * hh;
                const bool h0 = d < 28;
                const uint32_t rowa = sb + OFF_STG + wg * 8192 + d * 128 + q4 * 8;
                #pragma unroll
                for (int t = 0; t < 4; t++) {
                    float v0 = h0 ? kv[4 * t + 2 * hh] : kv[4 * t + 12 + 2 * hh];
                    float v1 = h0 ? kv[4 * t + 2 * hh + 1] : kv[4 * t + 13 + 2 * hh];
                    if (t == 0 && !h0 && q4 == 0) v0 = kv[28 + 2 * hh];
                    if (d < 56 && !(t == 3 && h0 && q4 == 2))
                        asm volatile("st.shared.v2.f32 [%0], {%1, %2};" :: "r"(rowa + ((t ^ (g8 & 3)) << 5)), "f"(v0), "f"(v1) : "memory");
                }
                if (h0 && q4 == 0)
                    asm volatile("st.shared.v2.f32 [%0], {%1, %1};" :: "r"(rowa + ((3 ^ (g8 & 3)) << 5) + 16), "f"(kv[28 + 2 * hh]) : "memory");
            };
            stage_kv(0);
            issue2(a0, 1); commit();
            retire(); load_a1(4); peek();
            stage_kv(1);
            __syncwarp();
            if (lane == 0) mbar_arrive(sb + BAR_KVDONE);
            issue2(a1, 1); commit();
            retire(); load_a0(5); peek();
            auto prescale = [&](int lo, int hi) {
                const float t0 = after_issue(1.f - g0, zero), t1 = after_issue(1.f - g1, zero);
                const uint32_t s0 = pack_bf16(t0, t0), s1 = pack_bf16(t1, t1);
                #pragma unroll
                for (int i = 0; i < 32; i++) if (i >= lo && i < hi) { hp[i] = mul_bf16x2(hp[i], (i & 1) ? s1 : s0); asm volatile("" : "+r"(hp[i])); }
            };
            prescale(0, 16);
            issue2(a0, 1); commit();
            retire(); load_a1(5); peek();
            prescale(16, 32);
            issue2(a1, 1); commit();
            retire(); load_a0(6); peek();
            issue2(a0, 1); commit();
            retire(); load_a1(6); peek();
            if (wg == 1) bar_sync<4, 256>();
            const uint32_t b = begin();
            wgmma_rs128<HI128>(au, a1[0], a1[1], a1[2], a1[3], b + LO128X2 + 128, 1);
            wgmma_rs128<HI128>(au, a1[4], a1[5], a1[6], a1[7], b + LO128X2 + 512, 1);
            wg_commit();
            wgmma_rs56<HI128>(aq, a1[0], a1[1], a1[2], a1[3], b + LO128, 1);
            wgmma_rs56<HI128>(aq, a1[4], a1[5], a1[6], a1[7], b + LO128 + 384, 1);
            commit();
            if (wg == 0) bar_arrive<4, 256>();
            wg_wait<2>(); release(old);
            load_a0(0); peek();
            wg_wait<1>();
            reg_fence(au);
        }
        #pragma unroll
        for (int i = 0; i < 32; i++) hp[i] = mul_bf16x2(hp[i], pack_bf16(au[2 * i], au[2 * i + 1]));
        reg_fence_part<0, 32>(hp);

        float ag[96];
        uint32_t op[16];
        {
            auto issue3 = [&](uint32_t (&a)[8], int sd) {
                const uint32_t b = begin();
                wgmma_rs192<HI64>(ag, a[0], a[1], a[2], a[3], b + LO64, sd);
                wgmma_rs192<HI64>(ag, a[4], a[5], a[6], a[7], b + LO64 + 384, 1);
            };
            uint32_t pq[16];
            issue3(a0, 0); commit();
            retire();
            reg_fence(aq);
            load_a1(0); peek();
            pq[14] = 0u; pq[15] = 0u;
            bool aux = false;
            #pragma unroll
            for (int st = 1; st < 12; st++) {
                if (st & 1) issue3(a1, 1); else issue3(a0, 1);
                commit();
                const float tok = st < 8 ? after_issue(kLog2e, zero) : 0.f;
                if (st == 11) aux = mbar_try(sb + BAR_AUX, 0);
                retire();
                if (st & 1) load_a0((st + 1) >> 1); else load_a1(st >> 1);
                peek();
                if (st < 8) {
                    const int i = 2 * st - 2;
                    pq[i] = pack_bf16(phi(aq[2 * i], tok), phi(aq[2 * i + 1], tok));
                    pq[i + 1] = pack_bf16(phi(aq[2 * i + 2], tok), phi(aq[2 * i + 3], tok));
                    asm volatile("" : "+r"(pq[i]), "+r"(pq[i + 1]));
                }
            }
            if (!aux) mbar_wait(sb + BAR_AUX, 0);
            if (wg == 1) bar_sync<4, 256>();
            float nd[32];
            issue3(a0, 1);
            {
                const uint32_t dk = dsb + LO128 + ((OFF_STG + 8192) >> 4);
                #pragma unroll
                for (int ks = 0; ks < 4; ks++) wgmma_rs64<HI128>(nd, pq[4 * ks], pq[4 * ks + 1], pq[4 * ks + 2], pq[4 * ks + 3], dk + ks * 128, ks);
            }
            commit();
            retire(); load_a1(6); peek();
            issue3(a1, 1); commit();
            if (wg == 0) bar_arrive<4, 256>();
            ready = mbar_try(sb + p4_bar(0), p4_par(0));
            retire();
            reg_fence(nd);
            const int src = lane & ~3;
            const float s00 = __fdividef(g0, __shfl_sync(0xffffffffu, nd[28], src) + 1e-6f);
            const float s01 = __fdividef(g0, __shfl_sync(0xffffffffu, nd[29], src) + 1e-6f);
            const float s10 = __fdividef(g1, __shfl_sync(0xffffffffu, nd[30], src) + 1e-6f);
            const float s11 = __fdividef(g1, __shfl_sync(0xffffffffu, nd[31], src) + 1e-6f);
            #pragma unroll
            for (int t = 0; t < 7; t++) {
                const bool h1 = t > 3 || (t == 3 && q4 >= 2);
                const float sa = h1 ? s01 : s00, sc = h1 ? s11 : s10;
                op[2 * t] = pack_bf16(nd[4 * t] * sa, nd[4 * t + 1] * sa);
                op[2 * t + 1] = pack_bf16(nd[4 * t + 2] * sc, nd[4 * t + 3] * sc);
            }
            op[14] = 0u; op[15] = 0u;
            reg_fence(op);
        }

        float oa[32], ob[32];
        int c = j == 7 ? 0 : j;
        const int wsh = __shfl_sync(0xffffffffu, warp * 16, 0);
        const uint32_t sh0 = par * 768, sh1 = par * 1024;
        bool ready2 = false;
        auto issue_d = [&](float (&o)[32], int c0, int half) {
            const int n = 3 * c0;
            if (half == 0) {
                if (!ready) mbar_wait(sb + p4_bar(n), p4_par(n));
                if (!ready2) mbar_wait(sb + p4_bar(n + 1), p4_par(n + 1));
                ready = mbar_try(sb + p4_bar(n + 2), p4_par(n + 2));
            }
            wg_fence();
            const uint32_t b = dsb + LO128 + (p4_off(n) >> 4);
            #pragma unroll
            for (int ks = 7 * half; ks < 7 * half + 7; ks++)
                wgmma_rs64<HI128>(o, hp[4 * ks], hp[4 * ks + 1], hp[4 * ks + 2], hp[4 * ks + 3],
                                  b + ks * 128 + (ks < 8 ? sh0 : 0u - sh1), ks);
        };
        auto issue_o = [&](float (&o)[32], int c0) {
            const int n = 3 * c0 + 2;
            if (!ready) mbar_wait(sb + p4_bar(n), p4_par(n));
            if (c0 < 6) {
                ready = mbar_try(sb + p4_bar(n + 1), p4_par(n + 1));
                ready2 = mbar_try(sb + p4_bar(n + 2), p4_par(n + 2));
            }
            wg_fence();
            const uint32_t b = dsb + LO128 + (p4_off(n) >> 4);
            #pragma unroll
            for (int ks = 0; ks < 4; ks++) wgmma_rs64<HI128>(o, op[4 * ks], op[4 * ks + 1], op[4 * ks + 2], op[4 * ks + 3], b + ks * 128, 1);
            wg_commit();
        };
        auto ship = [&](float (&o)[32], int c0) {
            reg_fence(o);
            const uint32_t so = xa + OFF_OUT + (c0 & 1) * 16384;
            #pragma unroll
            for (int t = 0; t < 4; t++)
                stsm4(so + (lx ^ (t * 32)), pack_bf16(o[8 * t], o[8 * t + 1]), pack_bf16(o[8 * t + 2], o[8 * t + 3]),
                      pack_bf16(o[8 * t + 4], o[8 * t + 5]), pack_bf16(o[8 * t + 6], o[8 * t + 7]));
            fence_async_smem();
            __syncwarp();
            if (elect_one()) {
                tma_reduce2d(&mp.out, sb + OFF_OUT + (c0 & 1) * 16384 + wsh * 128, 64 * c, row0 + wsh);
                asm volatile("cp.async.bulk.commit_group;" ::: "memory");
            }
            if (++c == 7) c = 0;
        };
        auto finish_h = [&]() {
            reg_fence(ag);
            release(cur);
            const uint32_t uu = pack_bf16(1.f - g0, 1.f - g1);
            const float u0 = bf_lo(uu), u1 = bf_hi(uu);
            #pragma unroll
            for (int i = 0; i < 24; i++) {
                const float u = (i & 1) ? u1 : u0;
                hp[32 + i] = mul_bf16x2(pack_relu_bf16(ag[2 * i], ag[2 * i + 1]), pack_bf16(ag[48 + 2 * i] * u, ag[49 + 2 * i] * u));
            }
            reg_fence_part<32, 56>(hp);
        };
        ready2 = mbar_try(sb + p4_bar(1), p4_par(1));
        wg_wait<0>();
        finish_h();
        #pragma unroll
        for (int c0 = 0; c0 < 7; c0++) {
            float (&o)[32] = (c0 & 1) ? ob : oa;
            if (c0 > 0 || wg == 1) turn_wait();
            issue_d(o, c0, 0);
            issue_d(o, c0, 1);
            issue_o(o, c0);
            if (!(c0 == 6 && wg == 1)) turn_pass();
            if (c0 >= 2) {
                if (elect_one()) asm volatile("cp.async.bulk.wait_group.read 1;" ::: "memory");
                __syncwarp();
            }
            wg_wait<0>();
            if (c0 < 2) { release(3 * c0); release(3 * c0 + 1); release(3 * c0 + 2); }
            ship(o, c0);
        }
        if (elect_one()) asm volatile("cp.async.bulk.wait_group.read 0;" ::: "memory");
    }
}

typedef CUresult (*EncodeFn)(CUtensorMap*, CUtensorMapDataType, cuuint32_t, void*, const cuuint64_t*, const cuuint64_t*,
                             const cuuint32_t*, const cuuint32_t*, CUtensorMapInterleave, CUtensorMapSwizzle,
                             CUtensorMapL2promotion, CUtensorMapFloatOOBfill);

void make_map(EncodeFn enc, CUtensorMap* m, const void* base, int rank, const cuuint64_t* dims, const cuuint64_t* strides,
              cuuint32_t b0, cuuint32_t b1, cuuint32_t b2, CUtensorMapSwizzle sw) {
    const cuuint32_t es[3] = {1, 1, 1}, box[3] = {b0, b1, b2};
    enc(m, CU_TENSOR_MAP_DATA_TYPE_BFLOAT16, rank, const_cast<void*>(base), dims, strides, box, es,
        CU_TENSOR_MAP_INTERLEAVE_NONE, sw, CU_TENSOR_MAP_L2_PROMOTION_L2_128B, CU_TENSOR_MAP_FLOAT_OOB_FILL_NONE);
}

}

extern "C" void kernel_launch(void* const* d_in, const int* in_sizes, int n_in, void* d_out, int out_size) {
    (void)in_sizes; (void)n_in; (void)out_size;
    static EncodeFn enc = nullptr;
    if (!enc) {
        void* fn = nullptr;
        cudaDriverEntryPointQueryResult st;
        cudaGetDriverEntryPoint("cuTensorMapEncodeTiled", &fn, cudaEnableDefault, &st);
        enc = (EncodeFn)fn;
        cudaFuncSetAttribute(fused_kernel, cudaFuncAttributeMaxDynamicSharedMemorySize, SMEM_BYTES);
    }
    Maps mp;
    const cuuint64_t dimx[2] = {kD, kS}, dimd[2] = {kD, kF}, dimo[2] = {kD, kD}, strd[1] = {kD * 2};
    make_map(enc, &mp.x, d_in[0], 2, dimx, strd, 64, 128, 1, CU_TENSOR_MAP_SWIZZLE_128B);
    make_map(enc, &mp.out, d_out, 2, dimx, strd, 64, 16, 1, CU_TENSOR_MAP_SWIZZLE_128B);
    make_map(enc, &mp.d, d_in[6], 2, dimd, strd, 64, 56, 1, CU_TENSOR_MAP_SWIZZLE_128B);
    make_map(enc, &mp.o, d_in[2], 2, dimo, strd, 64, 32, 1, CU_TENSOR_MAP_SWIZZLE_128B);
    const cuuint64_t dimq[3] = {kD, kD, 3}, strq[2] = {3 * kD * 2, kD * 2};
    make_map(enc, &mp.kv, d_in[1], 3, dimq, strq, 56, 16, 2, CU_TENSOR_MAP_SWIZZLE_128B);
    make_map(enc, &mp.q, d_in[1], 3, dimq, strq, 56, 16, 1, CU_TENSOR_MAP_SWIZZLE_128B);
    const cuuint64_t dimf[3] = {32, kD, kF / 32}, strf[2] = {kF * 2, 64};
    const cuuint64_t dimw[3] = {64, kD, kF / 64}, strw[2] = {kF * 2, 128};
    make_map(enc, &mp.g4, d_in[4], 3, dimw, strw, 64, 16, 2, CU_TENSOR_MAP_SWIZZLE_128B);
    make_map(enc, &mp.u4, d_in[5], 3, dimw, strw, 64, 16, 2, CU_TENSOR_MAP_SWIZZLE_128B);
    make_map(enc, &mp.g3, d_in[4], 3, dimf, strf, 32, 16, 3, CU_TENSOR_MAP_SWIZZLE_64B);
    make_map(enc, &mp.u3, d_in[5], 3, dimf, strf, 32, 16, 3, CU_TENSOR_MAP_SWIZZLE_64B);
    fused_kernel<<<NCTA, NTHREADS, SMEM_BYTES>>>(mp, (const __nv_bfloat16*)d_in[7], (__nv_bfloat16*)d_out, 0u);
}
```

```cpp
#include <cuda_runtime.h>
#include <cuda_bf16.h>
#include <cuda.h>
#include <stdint.h>

namespace {

constexpr int kS = 2048, kD = 448, kF = 1792;
constexpr int NTHREADS = 384;
constexpr int NCTA = 128;
constexpr uint32_t OFF_X = 0;
constexpr uint32_t OFF_RING = 114688;
constexpr uint32_t SLOT_BYTES = 16384;
constexpr int NSLOT = 6;
constexpr uint32_t OFF_STG = 212992;
constexpr uint32_t OFF_MISC = 229376;
constexpr uint32_t SMEM_BYTES = 232448;
constexpr uint32_t BAR_FULL = OFF_MISC, BAR_EMPTY = OFF_MISC + 48, BAR_XFULL = OFF_MISC + 96;
constexpr uint32_t BAR_W = OFF_MISC + 152, BAR_KVDONE = OFF_MISC + 160, BAR_AUX = OFF_MISC + 168, BAR_P4 = OFF_MISC + 176;
constexpr uint32_t BAR_REFILL = OFF_MISC + 192;
constexpr uint32_t OFF_W = OFF_MISC + 256;
constexpr uint32_t SB = 1024;

__device__ __align__(128) float g_kvacc[8][2048];
__device__ unsigned int g_counter[64];

__device__ __forceinline__ void mbar_init(uint32_t bar, uint32_t cnt) {
    asm volatile("mbarrier.init.shared::cta.b64 [%0], %1;" :: "r"(bar), "r"(cnt) : "memory");
}
__device__ __forceinline__ void mbar_expect_tx(uint32_t bar, uint32_t bytes) {
    asm volatile("mbarrier.arrive.expect_tx.shared::cta.b64 _, [%0], %1;" :: "r"(bar), "r"(bytes) : "memory");
}
__device__ __forceinline__ void mbar_arrive(uint32_t bar) {
    asm volatile("mbarrier.arrive.shared::cta.b64 _, [%0];" :: "r"(bar) : "memory");
}
__device__ __forceinline__ void mbar_arrive_cluster(uint32_t bar) {
    asm volatile("mbarrier.arrive.shared::cluster.b64 _, [%0];" :: "r"(bar) : "memory");
}
__device__ __forceinline__ void mbar_wait(uint32_t bar, uint32_t parity) {
    asm volatile("{\n"
                 ".reg .pred p;\n"
                 ".reg .u32 c;\n"
                 "mov.u32 c, 0;\n"
                 "AGAIN:\n"
                 "mbarrier.try_wait.parity.shared::cta.b64 p, [%0], %1;\n"
                 "@p bra DONE;\n"
                 "add.u32 c, c, 1;\n"
                 "setp.lt.u32 p, c, 4194304;\n"
                 "@p bra AGAIN;\n"
                 "trap;\n"
                 "DONE:\n"
                 "}" :: "r"(bar), "r"(parity) : "memory");
}
__device__ __forceinline__ uint32_t mapa(uint32_t addr, uint32_t cta) {
    uint32_t r; asm("mapa.shared::cluster.u32 %0, %1, %2;" : "=r"(r) : "r"(addr), "r"(cta)); return r;
}
__device__ __forceinline__ bool elect_one() {
    uint32_t p;
    asm volatile("{ .reg .pred P; elect.sync _|P, 0xffffffff; selp.u32 %0, 1, 0, P; }" : "=r"(p));
    return p;
}
__device__ __forceinline__ void tma2d(uint32_t dst, const CUtensorMap* m, int c0, int c1, uint32_t bar) {
    asm volatile("cp.async.bulk.tensor.2d.shared::cluster.global.mbarrier::complete_tx::bytes [%0], [%1, {%3, %4}], [%2];"
                 :: "r"(dst), "l"(m), "r"(bar), "r"(c0), "r"(c1) : "memory");
}
__device__ __forceinline__ void tma2d_mc(uint32_t dst, const CUtensorMap* m, int c0, int c1, uint32_t bar) {
    asm volatile("cp.async.bulk.tensor.2d.shared::cluster.global.mbarrier::complete_tx::bytes.multicast::cluster [%0], [%1, {%3, %4}], [%2], %5;"
                 :: "r"(dst), "l"(m), "r"(bar), "r"(c0), "r"(c1), "h"((uint16_t)3) : "memory");
}
__device__ __forceinline__ void tma3d_mc(uint32_t dst, const CUtensorMap* m, int c0, int c1, int c2, uint32_t bar) {
    asm volatile("cp.async.bulk.tensor.3d.shared::cluster.global.mbarrier::complete_tx::bytes.multicast::cluster [%0], [%1, {%3, %4, %5}], [%2], %6;"
                 :: "r"(dst), "l"(m), "r"(bar), "r"(c0), "r"(c1), "r"(c2), "h"((uint16_t)3) : "memory");
}
__device__ __forceinline__ void tma_reduce2d(const CUtensorMap* m, uint32_t src, int c0, int c1) {
    asm volatile("cp.reduce.async.bulk.tensor.2d.global.shared::cta.add.bulk_group [%0, {%2, %3}], [%1];"
                 :: "l"(m), "r"(src), "r"(c0), "r"(c1) : "memory");
}
__device__ __forceinline__ void bulk_reduce_f32(float* dst, uint32_t src, uint32_t bytes) {
    asm volatile("cp.reduce.async.bulk.global.shared::cta.bulk_group.add.f32 [%0], [%1], %2;" :: "l"(dst), "r"(src), "r"(bytes) : "memory");
}
__device__ __forceinline__ bool mbar_try(uint32_t bar, uint32_t parity) {
    uint32_t ok;
    asm volatile("{ .reg .pred p; mbarrier.test_wait.parity.shared::cta.b64 p, [%1], %2; selp.u32 %0, 1, 0, p; }"
                 : "=r"(ok) : "r"(bar), "r"(parity) : "memory");
    return ok;
}
__device__ __forceinline__ void prefetch_map(const CUtensorMap* m) {
    asm volatile("prefetch.tensormap [%0];" :: "l"(m) : "memory");
}
__device__ __forceinline__ void wg_fence() { asm volatile("wgmma.fence.sync.aligned;" ::: "memory"); }
__device__ __forceinline__ void wg_commit() { asm volatile("wgmma.commit_group.sync.aligned;" ::: "memory"); }
template <int N> __device__ __forceinline__ void wg_wait() { asm volatile("wgmma.wait_group.sync.aligned %0;" :: "n"(N) : "memory"); }
template <int N> __device__ __forceinline__ void reg_fence(float (&d)[N]) {
#pragma unroll
    for (int i = 0; i < N; i++) asm volatile("" : "+f"(d[i]) :: "memory");
}
template <int N> __device__ __forceinline__ void reg_fence(uint32_t (&d)[N]) {
#pragma unroll
    for (int i = 0; i < N; i++) asm volatile("" : "+r"(d[i]) :: "memory");
}
template <int LO, int HI, int N> __device__ __forceinline__ void reg_fence_part(uint32_t (&d)[N]) {
#pragma unroll
    for (int i = LO; i < HI; i++) asm volatile("" : "+r"(d[i]) :: "memory");
}
__device__ __forceinline__ void fence_async_smem() { asm volatile("fence.proxy.async.shared::cta;" ::: "memory"); }
template <int ID, int N> __device__ __forceinline__ void bar_sync() { asm volatile("bar.sync %0, %1;" :: "n"(ID), "n"(N) : "memory"); }
template <int ID, int N> __device__ __forceinline__ void bar_arrive() { asm volatile("bar.arrive %0, %1;" :: "n"(ID), "n"(N) : "memory"); }
__device__ __forceinline__ void ldsm4(uint32_t* r, uint32_t addr) {
    asm volatile("ldmatrix.sync.aligned.m8n8.x4.shared.b16 {%0, %1, %2, %3}, [%4];"
                 : "=r"(r[0]), "=r"(r[1]), "=r"(r[2]), "=r"(r[3]) : "r"(addr) : "memory");
}
__device__ __forceinline__ void stsm4(uint32_t addr, uint32_t r0, uint32_t r1, uint32_t r2, uint32_t r3) {
    asm volatile("stmatrix.sync.aligned.m8n8.x4.shared.b16 [%0], {%1, %2, %3, %4};"
                 :: "r"(addr), "r"(r0), "r"(r1), "r"(r2), "r"(r3) : "memory");
}
__device__ __forceinline__ uint32_t lds32(uint32_t addr) {
    uint32_t r; asm volatile("ld.shared.u32 %0, [%1];" : "=r"(r) : "r"(addr)); return r;
}
__device__ __forceinline__ float4 lds128f(uint32_t addr) {
    float4 r; asm volatile("ld.shared.v4.f32 {%0, %1, %2, %3}, [%4];" : "=f"(r.x), "=f"(r.y), "=f"(r.z), "=f"(r.w) : "r"(addr)); return r;
}
__device__ __forceinline__ uint32_t clock32() { uint32_t t; asm volatile("mov.u32 %0, %%clock;" : "=r"(t)); return t; }
__device__ __forceinline__ uint32_t pack_bf16(float lo, float hi) {
    uint32_t r; asm("cvt.rn.bf16x2.f32 %0, %1, %2;" : "=r"(r) : "f"(hi), "f"(lo)); return r;
}
__device__ __forceinline__ uint32_t pack_relu_bf16(float lo, float hi) {
    uint32_t r; asm("cvt.rn.relu.bf16x2.f32 %0, %1, %2;" : "=r"(r) : "f"(hi), "f"(lo)); return r;
}
__device__ __forceinline__ uint32_t mul_bf16x2(uint32_t a, uint32_t b) {
    uint32_t r; asm("mul.rn.bf16x2 %0, %1, %2;" : "=r"(r) : "r"(a), "r"(b)); return r;
}
__device__ __forceinline__ float phi(float t, float log2e) {
    float e;
    asm("ex2.approx.ftz.f32 %0, %1;" : "=f"(e) : "f"(fminf(t * log2e, 0.f)));
    return e + (fmaxf(t, 0.f) + 1e-6f);
}
__device__ __forceinline__ float after_issue(float v, uint32_t zero) {
    return __uint_as_float(__float_as_uint(v) | (clock32() & zero));
}
constexpr float kLog2e = 1.4426950408889634f;
__device__ __forceinline__ float bf_lo(uint32_t v) { return __uint_as_float(v << 16); }
__device__ __forceinline__ float bf_hi(uint32_t v) { return __uint_as_float(v & 0xffff0000u); }
constexpr uint32_t HI128 = (1024 >> 4) | (1u << 30);
constexpr uint32_t HI64 = (512 >> 4) | (2u << 30);
constexpr uint32_t LO128 = 1u << 16, LO64 = (1024u >> 4) << 16, LO128X2 = (2048u >> 4) << 16;
constexpr uint32_t QB = 16 * 112;
constexpr uint32_t TX1 = 2 * (2 * QB + 4096), TX2 = 2 * (QB + 4096), TX3 = 12288;
__device__ __forceinline__ void grid_arrive(unsigned int* c) {
    asm volatile("fence.acq_rel.gpu;" ::: "memory");
    asm volatile("red.relaxed.gpu.global.add.u32 [%0], 1;" :: "l"(c) : "memory");
}
__device__ __forceinline__ void grid_wait(const unsigned int* c, unsigned int target) {
    unsigned int v; int it = 0;
    do {
        asm volatile("ld.relaxed.gpu.global.u32 %0, [%1];" : "=r"(v) : "l"(c) : "memory");
        if (++it > (1 << 22)) asm volatile("trap;");
    } while ((int)(v - target) < 0);
    asm volatile("ld.acquire.gpu.global.u32 %0, [%1];" : "=r"(v) : "l"(c) : "memory");
}


__host__ __device__ constexpr uint32_t p4_pack(int n) { return (n / 3) * 36864 + (n % 3) * 14336; }
__host__ __device__ constexpr uint32_t p4_off(int n) {
    return n < 6 ? OFF_X + p4_pack(n) : n < 14 ? OFF_RING + p4_pack(n - 6) : n == 14 ? OFF_X + p4_pack(6) : OFF_X + p4_pack(n - 15);
}
__host__ __device__ constexpr uint32_t p4_bar(int n) {
    return n < 6 ? BAR_XFULL + 8 * n : n < 12 ? BAR_FULL + 8 * (n - 6) : n < 14 ? BAR_P4 + 8 * (n - 12)
                 : n == 14 ? BAR_XFULL + 48 : BAR_XFULL + 8 * (n - 15);
}
__host__ __device__ constexpr uint32_t p4_par(int n) { return (n < 12 || n == 14) ? 1 : 0; }
constexpr uint32_t OFF_OUT = OFF_X + 5 * 16384;
static_assert(p4_off(7) == p4_off(6) + 14336 && p4_off(13) == p4_off(12) + 14336 && p4_off(16) == p4_off(15) + 14336, "Wd halves");
static_assert(p4_off(13) + 14336 <= OFF_STG + 8192 && p4_off(14) + 8192 == OFF_OUT, "pass-4 layout");

struct Ring {
    uint32_t slot, phase;
    __device__ __forceinline__ void advance() { if (++slot == NSLOT) { slot = 0; phase ^= 1; } }
};

struct Maps { CUtensorMap x, kv, q, g4, g3, u4, u3, d, o, out; };

__global__ void __cluster_dims__(2, 1, 1) __launch_bounds__(NTHREADS, 1)
fused_kernel(const __grid_constant__ Maps mp, const __nv_bfloat16* __restrict__ gate_w, __nv_bfloat16* __restrict__ out,
             uint32_t zero)
{
    extern __shared__ __align__(1024) unsigned char smem[];
    const uint32_t sb = (uint32_t)__cvta_generic_to_shared(smem);
    const int tid = threadIdx.x, warp = tid >> 5, lane = tid & 31;
    const int rank = blockIdx.x & 1, j = (blockIdx.x >> 1) & 7;
    const int row0 = ((blockIdx.x >> 4) * 2 + rank) * 128;
    const int par = j & 1;
    const int g4i = (7 * j + 3 * par) >> 1;

    if (warp == 9) {
        if (elect_one()) {
            prefetch_map(&mp.x);
            mbar_init(sb + BAR_XFULL, 1);
            mbar_expect_tx(sb + BAR_XFULL, 16384);
            tma2d(sb + OFF_X, &mp.x, 0, row0, sb + BAR_XFULL);
            asm volatile("fence.mbarrier_init.release.cluster;" ::: "memory");
        }
        __syncwarp();
    } else if (warp == 8) {
        if (elect_one()) {
            #pragma unroll
            for (int s = 0; s < NSLOT; s++) mbar_init(sb + BAR_FULL + 8 * s, 1);
            asm volatile("fence.mbarrier_init.release.cluster;" ::: "memory");
            mbar_expect_tx(sb + BAR_FULL, TX1);
        }
        __syncwarp();
    } else if (warp == 10) {
        if (elect_one()) {
            #pragma unroll
            for (int s = 1; s < 7; s++) mbar_init(sb + BAR_XFULL + 8 * s, 1);
            mbar_init(sb + BAR_KVDONE, 8);
            mbar_init(sb + BAR_AUX, 3);
            asm volatile("fence.mbarrier_init.release.cluster;" ::: "memory");
            if ((sb & 0xFFFFFF) != SB) asm volatile("trap;");
        }
        __syncwarp();
    } else if (warp == 11) {
        if (elect_one()) {
            #pragma unroll
            for (int s = 0; s < NSLOT; s++) mbar_init(sb + BAR_EMPTY + 8 * s, 4);
            mbar_init(sb + BAR_P4, 1);
            mbar_init(sb + BAR_P4 + 8, 1);
            mbar_init(sb + BAR_REFILL, 4);
            mbar_init(sb + BAR_REFILL + 8, 4);
            asm volatile("fence.mbarrier_init.release.cluster;" ::: "memory");
        }
        __syncwarp();
    } else if (warp == 2) {
        if (elect_one()) {
            mbar_init(sb + BAR_W, 1);
            asm volatile("fence.mbarrier_init.release.cluster;" ::: "memory");
            mbar_expect_tx(sb + BAR_W, 896);
            asm volatile("cp.async.bulk.shared::cluster.global.mbarrier::complete_tx::bytes [%0], [%1], 896, [%2];"
                         :: "r"(sb + OFF_W), "l"(gate_w), "r"(sb + BAR_W) : "memory");
        }
        __syncwarp();
    }
    asm volatile("barrier.cluster.arrive.relaxed.aligned;" ::: "memory");
    if (warp == 8) {
        if (elect_one()) { prefetch_map(&mp.kv); prefetch_map(&mp.g4); }
        __syncwarp();
    }
    asm volatile("barrier.cluster.wait.aligned;" ::: "memory");
    if (warp == 8) {
        if (elect_one()) {
            tma3d_mc(sb + OFF_RING + rank * 8192 + 4096, &mp.kv, 56 * j, 16 * rank, 1, sb + BAR_FULL);
            tma3d_mc(sb + OFF_RING + rank * 8192, &mp.g4, 0, 16 * rank, g4i, sb + BAR_FULL);
        }
        __syncwarp();
    }

    if (warp >= 8) {
        asm volatile("setmaxnreg.dec.sync.aligned.u32 40;");
        if (warp == 8) {
            if (elect_one()) {
                Ring r{1, 1};
                auto acquire = [&](uint32_t bytes) -> uint32_t {
                    mbar_wait(sb + BAR_EMPTY + 8 * r.slot, r.phase);
                    mbar_expect_tx(sb + BAR_FULL + 8 * r.slot, bytes);
                    return sb + OFF_RING + r.slot * SLOT_BYTES;
                };
                #pragma unroll 1
                for (int s = 1; s < 14; s++) {
                    const uint32_t dst = acquire(TX1) + rank * 8192;
                    tma3d_mc(dst + 4096, &mp.kv, 56 * j, 32 * s + 16 * rank, 1, sb + BAR_FULL + 8 * r.slot);
                    tma3d_mc(dst, &mp.g4, 0, 32 * s + 16 * rank, g4i, sb + BAR_FULL + 8 * r.slot);
                    r.advance();
                    if ((s & 1) && s < 12) {
                        const int n = (s >> 1) + 1;
                        mbar_expect_tx(sb + BAR_XFULL + 8 * n, 16384);
                        tma2d(sb + OFF_X + n * 16384, &mp.x, 64 * n, row0, sb + BAR_XFULL + 8 * n);
                    }
                    if (s == 5) {
                        prefetch_map(&mp.q); prefetch_map(&mp.u4); prefetch_map(&mp.g3); prefetch_map(&mp.u3);
                        prefetch_map(&mp.d); prefetch_map(&mp.o); prefetch_map(&mp.out);
                    }
                }
                #pragma unroll 1
                for (int s = 0; s < 14; s++) {
                    const uint32_t dst = acquire(TX2) + rank * 6144;
                    tma3d_mc(dst, &mp.q, 56 * j, 32 * s + 16 * rank, 0, sb + BAR_FULL + 8 * r.slot);
                    tma3d_mc(dst + 2048, &mp.u4, 0, 32 * s + 16 * rank, g4i, sb + BAR_FULL + 8 * r.slot);
                    r.advance();
                }
                const int cfirst = j == 7 ? 0 : j;
                auto load4 = [&](int n) {
                    int c = cfirst + n / 3;
                    if (c >= 7) c -= 7;
                    mbar_expect_tx(sb + p4_bar(n), n % 3 == 2 ? 8192 : 14336);
                    if (n % 3 == 2) tma2d_mc(sb + p4_off(n) + rank * 4096, &mp.o, 64 * c, 56 * j + 32 * rank, sb + p4_bar(n));
                    else tma2d_mc(sb + p4_off(n) + rank * 7168, &mp.d, 64 * c, 224 * j + 112 * (n % 3) + 56 * rank, sb + p4_bar(n));
                };
                #pragma unroll 1
                for (int s = 0; s < 14; s++) {
                    const uint32_t dst = acquire(TX3) + rank * 6144;
                    tma3d_mc(dst, &mp.g3, 0, 32 * s + 16 * rank, 7 * j + 4 - 4 * par, sb + BAR_FULL + 8 * r.slot);
                    tma3d_mc(dst + 3072, &mp.u3, 0, 32 * s + 16 * rank, 7 * j + 4 - 4 * par, sb + BAR_FULL + 8 * r.slot);
                    r.advance();
                    if (s == 7) load4(0);
                    if (s == 9) load4(1);
                    if (s == 11) load4(2);
                    if (s == 13) { load4(3); load4(4); }
                }
                mbar_wait(sb + BAR_EMPTY, 0);      load4(6);
                mbar_wait(sb + BAR_EMPTY + 8, 0);  load4(5); load4(7); load4(14);
                mbar_wait(sb + BAR_EMPTY + 16, 0); load4(8);
                mbar_wait(sb + BAR_EMPTY + 24, 0); load4(9); load4(10);
                mbar_wait(sb + BAR_EMPTY + 32, 0); load4(11);
                mbar_wait(sb + BAR_EMPTY + 40, 0); load4(12);
                mbar_wait(sb + BAR_AUX, 0);        load4(13);
                #pragma unroll
                for (int n = 15; n < 21; n++) {
                    if (n % 3 == 0) mbar_wait(sb + BAR_REFILL + 8 * (n / 3 - 5), 0);
                    __nanosleep(100);
                    load4(n);
                }
            }
        } else {
            const int ht = tid - 288;
            unsigned int cnt0;
            asm volatile("ld.relaxed.gpu.global.u32 %0, [%1];" : "=r"(cnt0) : "l"(&g_counter[32]) : "memory");
            const unsigned int target = ((cnt0 >> 7) + 1) << 7;
            if (warp == 9) {
                reinterpret_cast<float4*>(&g_kvacc[0][0])[blockIdx.x * 32 + lane] = make_float4(0.f, 0.f, 0.f, 0.f);
                asm volatile("fence.proxy.async.global;" ::: "memory");
                __syncwarp();
                if (lane == 0) grid_arrive(&g_counter[0]);
                mbar_wait(sb + BAR_XFULL + 8 * 6, 0);
                uint4* o = reinterpret_cast<uint4*>(out) + blockIdx.x * 896 + lane;
                #pragma unroll 4
                for (int q = 0; q < 28; q++) o[q * 32] = make_uint4(0, 0, 0, 0);
                asm volatile("fence.proxy.async.global;" ::: "memory");
                __syncwarp();
                if (lane == 0) {
                    asm volatile("fence.acq_rel.gpu;" ::: "memory");
                    grid_wait(&g_counter[0], target);
                }
                __syncwarp();
            }
            mbar_wait(sb + BAR_KVDONE, 0);
            {
                #pragma unroll
                for (int i0 = 0; i0 < 5; i0 += 2) {
                    float4 pa[2], pb[2];
                    #pragma unroll
                    for (int i = 0; i < 2 && i0 + i < 5; i++) {
                        const int q = min(ht + 96 * (i0 + i), 447);
                        pa[i] = lds128f(sb + OFF_STG + q * 16); pb[i] = lds128f(sb + OFF_STG + 8192 + q * 16);
                    }
                    #pragma unroll
                    for (int i = 0; i < 2 && i0 + i < 5; i++) {
                        const int q = ht + 96 * (i0 + i);
                        if (q < 448) asm volatile("st.shared.v4.f32 [%0], {%1, %2, %3, %4};" :: "r"(sb + OFF_STG + q * 16),
                            "f"(pa[i].x + pb[i].x), "f"(pa[i].y + pb[i].y), "f"(pa[i].z + pb[i].z), "f"(pa[i].w + pb[i].w) : "memory");
                    }
                }
                fence_async_smem();
            }
            bar_sync<3, 96>();
            if (warp == 9) {
                if (elect_one()) {
                    bulk_reduce_f32(&g_kvacc[j][0], sb + OFF_STG, 7168);
                    asm volatile("cp.async.bulk.commit_group;" ::: "memory");
                    asm volatile("cp.async.bulk.wait_group 0;" ::: "memory");
                    asm volatile("red.relaxed.gpu.global.add.u32 [%0], 1;" :: "l"(&g_counter[32]) : "memory");
                }
            }
            __syncwarp();
            #pragma unroll
            for (int i = 0; i < 3; i++) {
                const int q = ht + 96 * i;
                const int d = q < 168 ? q / 3 : 56 + ((q - 168) >> 3);
                const int c = q < 168 ? (q - 3 * d + (d < 28 ? 4 : 0)) : (q & 7);
                if (q < 232) asm volatile("st.shared.v4.u32 [%0], {%1, %1, %1, %1};" :: "r"(sb + OFF_STG + 8192 + d * 128 + ((c ^ (d & 7)) << 4)), "r"(0) : "memory");
            }
            uint32_t plan[3];
            #pragma unroll
            for (int i = 0; i < 3; i++) {
                const int q = min(ht + 96 * i, 279), d = q / 5, m = q - 5 * d;
                const bool h0 = d < 28;
                const int c = m == 4 ? 7 : (h0 ? m : m + 3), pc = m < 4 ? m : (h0 ? 3 : 0);
                const int kind = m == 4 ? (h0 ? 3 : 4) : c == 3 ? (h0 ? 1 : 2) : 0;
                plan[i] = (d * 128 + ((c ^ (d & 7)) << 4)) | ((d * 4 + (pc ^ (d & 3))) << 13) | (kind << 23);
                asm volatile("" : "+r"(plan[i]));
            }
            if (lane == 0) grid_wait(&g_counter[32], target);
            __syncwarp();
            const float4* src = reinterpret_cast<const float4*>(&g_kvacc[j][0]);
            float4 va[3], vb[3];
            #pragma unroll
            for (int i = 0; i < 3; i++) {
                const float4* p = src + ((plan[i] >> 12) & 0x7fe);
                va[i] = __ldcg(p); vb[i] = __ldcg(p + 1);
            }
            #pragma unroll
            for (int i = 0; i < 3; i++) {
                const uint32_t kind = plan[i] >> 23;
                uint32_t w0 = pack_bf16(va[i].x, va[i].y), w1 = pack_bf16(va[i].z, va[i].w);
                uint32_t w2 = pack_bf16(vb[i].x, vb[i].y), w3 = pack_bf16(vb[i].z, vb[i].w);
                if (kind == 3) w0 = w2 & 0xffffu;
                if (kind == 4) w0 <<= 16;
                if (kind == 2) w0 = 0u;
                if (kind >= 2) w1 = 0u;
                if (kind != 0 && kind != 2) w2 = w3 = 0u;
                if (i < 2 || ht < 88)
                    asm volatile("st.shared.v4.u32 [%0], {%1, %2, %3, %4};"
                                 :: "r"(sb + OFF_STG + 8192 + (plan[i] & 0x1fff)), "r"(w0), "r"(w1), "r"(w2), "r"(w3) : "memory");
            }
            fence_async_smem();
            __syncwarp();
            if (lane == 0) mbar_arrive(sb + BAR_AUX);
        }
    } else {
        asm volatile("setmaxnreg.inc.sync.aligned.u32 232;");
        const int wg = warp >> 2, w4 = warp & 3;
        const int q4 = lane & 3, g8 = lane >> 2;
        const uint32_t lx = ((lane >> 4) ^ (lane & 7)) << 4;
        const uint32_t xa = sb + OFF_X + (warp * 16 + (lane & 15)) * 128;
        const uint32_t empty_dst = mapa(sb + BAR_EMPTY, w4 & 1);
        const bool signaller = lane == 0 && w4 < 2;
        constexpr uint32_t dsb = SB >> 4;
        Ring r{0, 0};
        uint32_t cur = 0, old = 0;
        bool ready = false;
        auto release = [&](uint32_t slot) { if (signaller) mbar_arrive_cluster(empty_dst + 8 * slot); };
        auto turn_wait = [&]() { if (wg == 0) bar_sync<6, 256>(); else bar_sync<7, 256>(); };
        auto turn_pass = [&]() { if (wg == 0) bar_arrive<7, 256>(); else bar_arrive<6, 256>(); };
        auto begin = [&]() -> uint32_t {
            if (!ready) mbar_wait(sb + BAR_FULL + 8 * r.slot, r.phase);
            wg_fence();
            return dsb + (OFF_RING >> 4) + r.slot * (SLOT_BYTES >> 4);
        };
        auto commit = [&]() { wg_commit(); old = cur; cur = r.slot; r.advance(); };
        auto retire = [&]() { wg_wait<1>(); release(old); };
        auto peek = [&]() { ready = mbar_try(sb + BAR_FULL + 8 * r.slot, r.phase); };
        uint32_t a0[8], a1[8];
        auto load_a0 = [&](int kc) { ldsm4(a0, xa + kc * 16384 + lx); ldsm4(a0 + 4, xa + kc * 16384 + (lx ^ 32)); };
        auto load_a1 = [&](int kc) { ldsm4(a1, xa + kc * 16384 + (lx ^ 64)); ldsm4(a1 + 4, xa + kc * 16384 + (lx ^ 96)); };

        uint32_t hp[56];
        float g0, g1, av[28], agk[92];
        {
            float d0 = 0.f, d1 = 0.f, d2 = 0.f, d3 = 0.f;
            uint32_t w0[4], w1[4];
            auto issue1 = [&](uint32_t (&a)[8], int sd) {
                const uint32_t b = begin();
                wgmma_rs184<HI128>(agk, a[0], a[1], a[2], a[3], b + LO128X2, sd);
                wgmma_rs56<HI128>(av, a[0], a[1], a[2], a[3], b + LO128 + 384, sd);
                wgmma_rs184<HI128>(agk, a[4], a[5], a[6], a[7], b + LO128X2 + 512, 1);
                wgmma_rs56<HI128>(av, a[4], a[5], a[6], a[7], b + LO128 + 896, 1);
                commit();
            };
            auto issue1s = [&](uint32_t (&a)[8]) {
                const uint32_t b = begin();
                wgmma_rs184<HI128>(agk, a[0], a[1], a[2], a[3], b + LO128X2, 1);
                wgmma_rs184<HI128>(agk, a[4], a[5], a[6], a[7], b + LO128X2 + 512, 1);
                wg_commit();
                wgmma_rs56<HI128>(av, a[0], a[1], a[2], a[3], b + LO128 + 384, 1);
                wgmma_rs56<HI128>(av, a[4], a[5], a[6], a[7], b + LO128 + 896, 1);
                commit();
            };
            auto load_w = [&](uint32_t (&w)[4], int s) {
                #pragma unroll
                for (int e = 0; e < 4; e++) w[e] = lds32(sb + OFF_W + s * 64 + q4 * 4 + e * 16);
            };
            auto dot = [&](uint32_t (&a)[8], uint32_t (&w)[4]) {
                #pragma unroll
                for (int e = 0; e < 4; e++) {
                    const uint32_t p0 = mul_bf16x2(a[2 * e], w[e]), p1 = mul_bf16x2(a[2 * e + 1], w[e]);
                    d0 += bf_lo(p0); d2 += bf_hi(p0); d1 += bf_lo(p1); d3 += bf_hi(p1);
                }
                asm volatile("" : "+f"(d0), "+f"(d1), "+f"(d2), "+f"(d3));
            };
            mbar_wait(sb + BAR_XFULL, 0);
            load_a0(0);
            mbar_wait(sb + BAR_W, 0);
            load_w(w0, 0);
            auto odd_stage = [&](int it, bool first, bool last) {
                wg_wait<1>();
                if (!first) release(old);
                load_a1(it);
                load_w(w1, 2 * it + 1);
                peek();
                dot(a0, w0);
                if (last && wg == 1) bar_sync<4, 256>();
                issue1s(a1);
                if (last && wg == 0) bar_arrive<4, 256>();
            };
            issue1(a0, 0);
            #pragma unroll
            for (int it = 0; it < 6; it++) {
                const bool xok = mbar_try(sb + BAR_XFULL + 8 * (it + 1), 0);
                odd_stage(it, it == 0, false);
                wg_wait<2>(); release(old);
                if (!xok) mbar_wait(sb + BAR_XFULL + 8 * (it + 1), 0);
                load_a0(it + 1);
                load_w(w0, 2 * it + 2);
                peek();
                dot(a1, w1);
                issue1(a0, 1);
            }
            odd_stage(6, false, true);
            wg_wait<2>(); release(old);
            load_a0(0);
            peek();
            dot(a1, w1);
            wg_wait<1>();
            reg_fence(agk);
            #pragma unroll
            for (int i = 0; i < 32; i++) hp[i] = pack_relu_bf16(agk[2 * i], agk[2 * i + 1]);
            reg_fence_part<0, 32>(hp);
            g0 = d0 + d2; g1 = d1 + d3;
        }

        float aq[28], au[64];
        {
            auto issue2 = [&](uint32_t (&a)[8], int sd) {
                const uint32_t b = begin();
                wgmma_rs56<HI128>(aq, a[0], a[1], a[2], a[3], b + LO128, sd);
                wgmma_rs128<HI128>(au, a[0], a[1], a[2], a[3], b + LO128X2 + 128, sd);
                wgmma_rs56<HI128>(aq, a[4], a[5], a[6], a[7], b + LO128 + 384, 1);
                wgmma_rs128<HI128>(au, a[4], a[5], a[6], a[7], b + LO128X2 + 512, 1);
            };
            const uint32_t st_base = wg == 0 ? OFF_STG : OFF_RING + 12288, st_step = wg == 0 ? 2048 : SLOT_BYTES, st_v = wg == 0 ? 8192 : 2048;
            const uint32_t sk = sb + st_base + w4 * st_step + (lane & 15) * 128;
            float tok = kLog2e;
            uint32_t pk[16];
            pk[14] = 0u; pk[15] = 0u;
            auto stage_k = [&](int lo, int hi) {
                #pragma unroll
                for (int i = 0; i < 14; i++) if (i >= lo && i < hi) pk[i] = pack_bf16(phi(agk[64 + 2 * i], tok), phi(agk[65 + 2 * i], tok));
                #pragma unroll
                for (int t = 0; t < 4; t++) {
                    const int need = t < 3 ? 4 * t + 4 : 14;
                    if (need > lo && need <= hi) stsm4(sk + (lx ^ (t * 32)), pk[4 * t], pk[4 * t + 1], pk[4 * t + 2], pk[4 * t + 3]);
                }
                #pragma unroll
                for (int i = 0; i < 14; i++) if (i >= lo && i < hi) asm volatile("" : "+r"(pk[i]));
            };
            issue2(a0, 0); commit();
            tok = after_issue(kLog2e, zero);
            retire();
            reg_fence(av);
            if (wg == 0) bar_arrive<8, 256>();
            load_a1(0); peek();
            uint32_t pv[14];
            #pragma unroll
            for (int i = 0; i < 14; i++) pv[i] = pack_bf16(av[2 * i], av[2 * i + 1]);
            if (wg == 1) bar_sync<8, 256>();
            {
                const uint32_t ones = q4 == 0 ? 0x3f803f80u : 0u;
                #pragma unroll
                for (int t = 0; t < 3; t++) stsm4(sk + st_v + (lx ^ (t * 32)), pv[4 * t], pv[4 * t + 1], pv[4 * t + 2], pv[4 * t + 3]);
                stsm4(sk + st_v + (lx ^ 96), pv[12], pv[13], ones, ones);
            }
            stage_k(0, 2);
            issue2(a1, 1); commit();
            tok = after_issue(kLog2e, zero);
            retire(); load_a0(1); peek();
            stage_k(2, 5);
            issue2(a0, 1); commit();
            tok = after_issue(kLog2e, zero);
            retire(); load_a1(1); peek();
            stage_k(5, 8);
            issue2(a1, 1); commit();
            tok = after_issue(kLog2e, zero);
            retire(); load_a0(2); peek();
            stage_k(8, 11);
            issue2(a0, 1); commit();
            tok = after_issue(kLog2e, zero);
            retire(); load_a1(2); peek();
            stage_k(11, 14);
            issue2(a1, 1); commit();
            retire(); load_a0(3); peek();
            fence_async_smem();
            if (wg == 0) bar_sync<1, 128>(); else bar_sync<2, 128>();
            float kv[32];
            issue2(a0, 1);
            {
                const uint32_t dk = dsb + LO128 + (st_base >> 4), ds = st_step >> 4, dv = st_v >> 4;
                #pragma unroll
                for (int ks = 0; ks < 4; ks++) wgmma_ss64_tt<HI128>(kv, dk + ks * ds, dk + ks * ds + dv, ks);
            }
            commit();
            tok = after_issue(-kLog2e, zero);
            retire(); load_a1(3); peek();
            {
                g0 += __shfl_xor_sync(0xffffffffu, g0, 1); g1 += __shfl_xor_sync(0xffffffffu, g1, 1);
                g0 += __shfl_xor_sync(0xffffffffu, g0, 2); g1 += __shfl_xor_sync(0xffffffffu, g1, 2);
                const uint32_t lg = pack_bf16(g0, g1);
                float e0, e1;
                asm("ex2.approx.ftz.f32 %0, %1;" : "=f"(e0) : "f"(bf_lo(lg) * tok));
                asm("ex2.approx.ftz.f32 %0, %1;" : "=f"(e1) : "f"(bf_hi(lg) * tok));
                const uint32_t gg = pack_bf16(__fdividef(1.f, 1.f + e0), __fdividef(1.f, 1.f + e1));
                g0 = bf_lo(gg); g1 = bf_hi(gg);
                asm volatile("" : "+f"(g0), "+f"(g1));
            }
            issue2(a1, 1); commit();
            retire(); load_a0(4); peek();
            reg_fence(kv);
            if (wg == 0) { bar_arrive<5, 256>(); bar_sync<1, 128>(); } else bar_sync<5, 256>();
            auto stage_kv = [&](int hh) {
                const int d = w4 * 16 + g8 + 8 * hh;
                const bool h0 = d < 28;
                const uint32_t rowa = sb + OFF_STG + wg * 8192 + d * 128 + q4 * 8;
                #pragma unroll
                for (int t = 0; t < 4; t++) {
                    float v0 = h0 ? kv[4 * t + 2 * hh] : kv[4 * t + 12 + 2 * hh];
                    float v1 = h0 ? kv[4 * t + 2 * hh + 1] : kv[4 * t + 13 + 2 * hh];
                    if (t == 0 && !h0 && q4 == 0) v0 = kv[28 + 2 * hh];
                    if (d < 56 && !(t == 3 && h0 && q4 == 2))
                        asm volatile("st.shared.v2.f32 [%0], {%1, %2};" :: "r"(rowa + ((t ^ (g8 & 3)) << 5)), "f"(v0), "f"(v1) : "memory");
                }
                if (h0 && q4 == 0)
                    asm volatile("st.shared.v2.f32 [%0], {%1, %1};" :: "r"(rowa + ((3 ^ (g8 & 3)) << 5) + 16), "f"(kv[28 + 2 * hh]) : "memory");
            };
            stage_kv(0);
            issue2(a0, 1); commit();
            retire(); load_a1(4); peek();
            stage_kv(1);
            __syncwarp();
            if (lane == 0) mbar_arrive(sb + BAR_KVDONE);
            issue2(a1, 1); commit();
            retire(); load_a0(5); peek();
            auto prescale = [&](int lo, int hi) {
                const float t0 = after_issue(1.f - g0, zero), t1 = after_issue(1.f - g1, zero);
                const uint32_t s0 = pack_bf16(t0, t0), s1 = pack_bf16(t1, t1);
                #pragma unroll
                for (int i = 0; i < 32; i++) if (i >= lo && i < hi) { hp[i] = mul_bf16x2(hp[i], (i & 1) ? s1 : s0); asm volatile("" : "+r"(hp[i])); }
            };
            prescale(0, 16);
            issue2(a0, 1); commit();
            retire(); load_a1(5); peek();
            prescale(16, 32);
            issue2(a1, 1); commit();
            retire(); load_a0(6); peek();
            issue2(a0, 1); commit();
            retire(); load_a1(6); peek();
            if (wg == 1) bar_sync<4, 256>();
            const uint32_t b = begin();
            wgmma_rs128<HI128>(au, a1[0], a1[1], a1[2], a1[3], b + LO128X2 + 128, 1);
            wgmma_rs128<HI128>(au, a1[4], a1[5], a1[6], a1[7], b + LO128X2 + 512, 1);
            wg_commit();
            wgmma_rs56<HI128>(aq, a1[0], a1[1], a1[2], a1[3], b + LO128, 1);
            wgmma_rs56<HI128>(aq, a1[4], a1[5], a1[6], a1[7], b + LO128 + 384, 1);
            commit();
            if (wg == 0) bar_arrive<4, 256>();
            wg_wait<2>(); release(old);
            load_a0(0); peek();
            wg_wait<1>();
            reg_fence(au);
        }
        #pragma unroll
        for (int i = 0; i < 32; i++) hp[i] = mul_bf16x2(hp[i], pack_bf16(au[2 * i], au[2 * i + 1]));
        reg_fence_part<0, 32>(hp);

        float ag[96];
        uint32_t op[16];
        {
            auto issue3 = [&](uint32_t (&a)[8], int sd) {
                const uint32_t b = begin();
                wgmma_rs192<HI64>(ag, a[0], a[1], a[2], a[3], b + LO64, sd);
                wgmma_rs192<HI64>(ag, a[4], a[5], a[6], a[7], b + LO64 + 384, 1);
            };
            uint32_t pq[16];
            issue3(a0, 0); commit();
            retire();
            reg_fence(aq);
            load_a1(0); peek();
            pq[14] = 0u; pq[15] = 0u;
            bool aux = false;
            #pragma unroll
            for (int st = 1; st < 12; st++) {
                if (st & 1) issue3(a1, 1); else issue3(a0, 1);
                commit();
                const float tok = st < 8 ? after_issue(kLog2e, zero) : 0.f;
                if (st == 11) aux = mbar_try(sb + BAR_AUX, 0);
                retire();
                if (st & 1) load_a0((st + 1) >> 1); else load_a1(st >> 1);
                peek();
                if (st < 8) {
                    const int i = 2 * st - 2;
                    pq[i] = pack_bf16(phi(aq[2 * i], tok), phi(aq[2 * i + 1], tok));
                    pq[i + 1] = pack_bf16(phi(aq[2 * i + 2], tok), phi(aq[2 * i + 3], tok));
                    asm volatile("" : "+r"(pq[i]), "+r"(pq[i + 1]));
                }
            }
            if (!aux) mbar_wait(sb + BAR_AUX, 0);
            if (wg == 1) bar_sync<4, 256>();
            float nd[32];
            issue3(a0, 1);
            {
                const uint32_t dk = dsb + LO128 + ((OFF_STG + 8192) >> 4);
                #pragma unroll
                for (int ks = 0; ks < 4; ks++) wgmma_rs64<HI128>(nd, pq[4 * ks], pq[4 * ks + 1], pq[4 * ks + 2], pq[4 * ks + 3], dk + ks * 128, ks);
            }
            commit();
            retire(); load_a1(6); peek();
            issue3(a1, 1); commit();
            if (wg == 0) bar_arrive<4, 256>();
            ready = mbar_try(sb + p4_bar(0), p4_par(0));
            retire();
            reg_fence(nd);
            const int src = lane & ~3;
            const float s00 = __fdividef(g0, __shfl_sync(0xffffffffu, nd[28], src) + 1e-6f);
            const float s01 = __fdividef(g0, __shfl_sync(0xffffffffu, nd[29], src) + 1e-6f);
            const float s10 = __fdividef(g1, __shfl_sync(0xffffffffu, nd[30], src) + 1e-6f);
            const float s11 = __fdividef(g1, __shfl_sync(0xffffffffu, nd[31], src) + 1e-6f);
            #pragma unroll
            for (int t = 0; t < 7; t++) {
                const bool h1 = t > 3 || (t == 3 && q4 >= 2);
                const float sa = h1 ? s01 : s00, sc = h1 ? s11 : s10;
                op[2 * t] = pack_bf16(nd[4 * t] * sa, nd[4 * t + 1] * sa);
                op[2 * t + 1] = pack_bf16(nd[4 * t + 2] * sc, nd[4 * t + 3] * sc);
            }
            op[14] = 0u; op[15] = 0u;
            reg_fence(op);
        }

        float oa[32], ob[32];
        int c = j == 7 ? 0 : j;
        const int wsh = __shfl_sync(0xffffffffu, warp * 16, 0);
        const uint32_t sh0 = par * 768, sh1 = par * 1024;
        bool ready2 = false;
        auto issue_d = [&](float (&o)[32], int c0, int half) {
            const int n = 3 * c0;
            if (half == 0) {
                if (!ready) mbar_wait(sb + p4_bar(n), p4_par(n));
                if (!ready2) mbar_wait(sb + p4_bar(n + 1), p4_par(n + 1));
                ready = mbar_try(sb + p4_bar(n + 2), p4_par(n + 2));
            }
            wg_fence();
            const uint32_t b = dsb + LO128 + (p4_off(n) >> 4);
            #pragma unroll
            for (int ks = 7 * half; ks < 7 * half + 7; ks++)
                wgmma_rs64<HI128>(o, hp[4 * ks], hp[4 * ks + 1], hp[4 * ks + 2], hp[4 * ks + 3],
                                  b + ks * 128 + (ks < 8 ? sh0 : 0u - sh1), ks);
        };
        auto issue_o = [&](float (&o)[32], int c0) {
            const int n = 3 * c0 + 2;
            if (!ready) mbar_wait(sb + p4_bar(n), p4_par(n));
            if (c0 < 6) {
                ready = mbar_try(sb + p4_bar(n + 1), p4_par(n + 1));
                ready2 = mbar_try(sb + p4_bar(n + 2), p4_par(n + 2));
            }
            wg_fence();
            const uint32_t b = dsb + LO128 + (p4_off(n) >> 4);
            #pragma unroll
            for (int ks = 0; ks < 4; ks++) wgmma_rs64<HI128>(o, op[4 * ks], op[4 * ks + 1], op[4 * ks + 2], op[4 * ks + 3], b + ks * 128, 1);
            wg_commit();
        };
        auto ship = [&](float (&o)[32], int c0) {
            reg_fence(o);
            const uint32_t so = xa + OFF_OUT + (c0 & 1) * 16384;
            #pragma unroll
            for (int t = 0; t < 4; t++)
                stsm4(so + (lx ^ (t * 32)), pack_bf16(o[8 * t], o[8 * t + 1]), pack_bf16(o[8 * t + 2], o[8 * t + 3]),
                      pack_bf16(o[8 * t + 4], o[8 * t + 5]), pack_bf16(o[8 * t + 6], o[8 * t + 7]));
            fence_async_smem();
            __syncwarp();
            if (elect_one()) {
                tma_reduce2d(&mp.out, sb + OFF_OUT + (c0 & 1) * 16384 + wsh * 128, 64 * c, row0 + wsh);
                asm volatile("cp.async.bulk.commit_group;" ::: "memory");
            }
            if (++c == 7) c = 0;
        };
        auto finish_h = [&]() {
            reg_fence(ag);
            release(cur);
            const uint32_t uu = pack_bf16(1.f - g0, 1.f - g1);
            const float u0 = bf_lo(uu), u1 = bf_hi(uu);
            #pragma unroll
            for (int i = 0; i < 24; i++) {
                const float u = (i & 1) ? u1 : u0;
                hp[32 + i] = mul_bf16x2(pack_relu_bf16(ag[2 * i], ag[2 * i + 1]), pack_bf16(ag[48 + 2 * i] * u, ag[49 + 2 * i] * u));
            }
            reg_fence_part<32, 56>(hp);
        };
        ready2 = mbar_try(sb + p4_bar(1), p4_par(1));
        wg_wait<0>();
        finish_h();
        #pragma unroll
        for (int c0 = 0; c0 < 7; c0++) {
            float (&o)[32] = (c0 & 1) ? ob : oa;
            if (c0 > 0 || wg == 1) turn_wait();
            issue_d(o, c0, 0);
            issue_d(o, c0, 1);
            issue_o(o, c0);
            if (!(c0 == 6 && wg == 1)) turn_pass();
            if (c0 >= 2) {
                if (elect_one()) asm volatile("cp.async.bulk.wait_group.read 1;" ::: "memory");
                __syncwarp();
            }
            wg_wait<0>();
            if (c0 < 2 && signaller) mbar_arrive_cluster(empty_dst + (BAR_REFILL - BAR_EMPTY) + 8 * c0);
            ship(o, c0);
        }
        if (elect_one()) asm volatile("cp.async.bulk.wait_group.read 0;" ::: "memory");
    }
}

typedef CUresult (*EncodeFn)(CUtensorMap*, CUtensorMapDataType, cuuint32_t, void*, const cuuint64_t*, const cuuint64_t*,
                             const cuuint32_t*, const cuuint32_t*, CUtensorMapInterleave, CUtensorMapSwizzle,
                             CUtensorMapL2promotion, CUtensorMapFloatOOBfill);

void make_map(EncodeFn enc, CUtensorMap* m, const void* base, int rank, const cuuint64_t* dims, const cuuint64_t* strides,
              cuuint32_t b0, cuuint32_t b1, cuuint32_t b2, CUtensorMapSwizzle sw) {
    const cuuint32_t es[3] = {1, 1, 1}, box[3] = {b0, b1, b2};
    enc(m, CU_TENSOR_MAP_DATA_TYPE_BFLOAT16, rank, const_cast<void*>(base), dims, strides, box, es,
        CU_TENSOR_MAP_INTERLEAVE_NONE, sw, CU_TENSOR_MAP_L2_PROMOTION_L2_128B, CU_TENSOR_MAP_FLOAT_OOB_FILL_NONE);
}

}

extern "C" void kernel_launch(void* const* d_in, const int* in_sizes, int n_in, void* d_out, int out_size) {
    (void)in_sizes; (void)n_in; (void)out_size;
    static EncodeFn enc = nullptr;
    if (!enc) {
        void* fn = nullptr;
        cudaDriverEntryPointQueryResult st;
        cudaGetDriverEntryPoint("cuTensorMapEncodeTiled", &fn, cudaEnableDefault, &st);
        enc = (EncodeFn)fn;
        cudaFuncSetAttribute(fused_kernel, cudaFuncAttributeMaxDynamicSharedMemorySize, SMEM_BYTES);
    }
    Maps mp;
    const cuuint64_t dimx[2] = {kD, kS}, dimd[2] = {kD, kF}, dimo[2] = {kD, kD}, strd[1] = {kD * 2};
    make_map(enc, &mp.x, d_in[0], 2, dimx, strd, 64, 128, 1, CU_TENSOR_MAP_SWIZZLE_128B);
    make_map(enc, &mp.out, d_out, 2, dimx, strd, 64, 16, 1, CU_TENSOR_MAP_SWIZZLE_128B);
    make_map(enc, &mp.d, d_in[6], 2, dimd, strd, 64, 56, 1, CU_TENSOR_MAP_SWIZZLE_128B);
    make_map(enc, &mp.o, d_in[2], 2, dimo, strd, 64, 32, 1, CU_TENSOR_MAP_SWIZZLE_128B);
    const cuuint64_t dimq[3] = {kD, kD, 3}, strq[2] = {3 * kD * 2, kD * 2};
    make_map(enc, &mp.kv, d_in[1], 3, dimq, strq, 56, 16, 2, CU_TENSOR_MAP_SWIZZLE_128B);
    make_map(enc, &mp.q, d_in[1], 3, dimq, strq, 56, 16, 1, CU_TENSOR_MAP_SWIZZLE_128B);
    const cuuint64_t dimf[3] = {32, kD, kF / 32}, strf[2] = {kF * 2, 64};
    const cuuint64_t dimw[3] = {64, kD, kF / 64}, strw[2] = {kF * 2, 128};
    make_map(enc, &mp.g4, d_in[4], 3, dimw, strw, 64, 16, 2, CU_TENSOR_MAP_SWIZZLE_128B);
    make_map(enc, &mp.u4, d_in[5], 3, dimw, strw, 64, 16, 2, CU_TENSOR_MAP_SWIZZLE_128B);
    make_map(enc, &mp.g3, d_in[4], 3, dimf, strf, 32, 16, 3, CU_TENSOR_MAP_SWIZZLE_64B);
    make_map(enc, &mp.u3, d_in[5], 3, dimf, strf, 32, 16, 3, CU_TENSOR_MAP_SWIZZLE_64B);
    fused_kernel<<<NCTA, NTHREADS, SMEM_BYTES>>>(mp, (const __nv_bfloat16*)d_in[7], (__nv_bfloat16*)d_out, 0u);
}
```

```cpp
#include <cuda_runtime.h>
#include <cuda_bf16.h>
#include <cuda.h>
#include <stdint.h>

namespace {

constexpr int kS = 2048, kD = 448, kF = 1792;
constexpr int NTHREADS = 384;
constexpr int NCTA = 128;
constexpr uint32_t OFF_X = 0;
constexpr uint32_t OFF_RING = 114688;
constexpr uint32_t SLOT_BYTES = 16384;
constexpr int NSLOT = 6;
constexpr uint32_t OFF_STG = 212992;
constexpr uint32_t OFF_MISC = 229376;
constexpr uint32_t SMEM_BYTES = 232448;
constexpr uint32_t BAR_FULL = OFF_MISC, BAR_EMPTY = OFF_MISC + 48, BAR_XFULL = OFF_MISC + 96;
constexpr uint32_t BAR_W = OFF_MISC + 152, BAR_KVDONE = OFF_MISC + 160, BAR_AUX = OFF_MISC + 168, BAR_P4 = OFF_MISC + 176;
constexpr uint32_t BAR_REFILL = OFF_MISC + 192;
constexpr uint32_t OFF_W = OFF_MISC + 256;
constexpr uint32_t SB = 1024;

__device__ __align__(128) float g_kvacc[8][2048];
__device__ unsigned int g_counter[64];

__device__ __forceinline__ void mbar_init(uint32_t bar, uint32_t cnt) {
    asm volatile("mbarrier.init.shared::cta.b64 [%0], %1;" :: "r"(bar), "r"(cnt) : "memory");
}
__device__ __forceinline__ void mbar_expect_tx(uint32_t bar, uint32_t bytes) {
    asm volatile("mbarrier.arrive.expect_tx.shared::cta.b64 _, [%0], %1;" :: "r"(bar), "r"(bytes) : "memory");
}
__device__ __forceinline__ void mbar_arrive(uint32_t bar) {
    asm volatile("mbarrier.arrive.shared::cta.b64 _, [%0];" :: "r"(bar) : "memory");
}
__device__ __forceinline__ void mbar_arrive_cluster(uint32_t bar) {
    asm volatile("mbarrier.arrive.shared::cluster.b64 _, [%0];" :: "r"(bar) : "memory");
}
__device__ __forceinline__ void mbar_wait(uint32_t bar, uint32_t parity) {
    asm volatile("{\n"
                 ".reg .pred p;\n"
                 ".reg .u32 c;\n"
                 "mov.u32 c, 0;\n"
                 "AGAIN:\n"
                 "mbarrier.try_wait.parity.shared::cta.b64 p, [%0], %1;\n"
                 "@p bra DONE;\n"
                 "add.u32 c, c, 1;\n"
                 "setp.lt.u32 p, c, 4194304;\n"
                 "@p bra AGAIN;\n"
                 "trap;\n"
                 "DONE:\n"
                 "}" :: "r"(bar), "r"(parity) : "memory");
}
__device__ __forceinline__ uint32_t mapa(uint32_t addr, uint32_t cta) {
    uint32_t r; asm("mapa.shared::cluster.u32 %0, %1, %2;" : "=r"(r) : "r"(addr), "r"(cta)); return r;
}
__device__ __forceinline__ bool elect_one() {
    uint32_t p;
    asm volatile("{ .reg .pred P; elect.sync _|P, 0xffffffff; selp.u32 %0, 1, 0, P; }" : "=r"(p));
    return p;
}
__device__ __forceinline__ void tma2d(uint32_t dst, const CUtensorMap* m, int c0, int c1, uint32_t bar) {
    asm volatile("cp.async.bulk.tensor.2d.shared::cluster.global.mbarrier::complete_tx::bytes [%0], [%1, {%3, %4}], [%2];"
                 :: "r"(dst), "l"(m), "r"(bar), "r"(c0), "r"(c1) : "memory");
}
__device__ __forceinline__ void tma2d_mc(uint32_t dst, const CUtensorMap* m, int c0, int c1, uint32_t bar) {
    asm volatile("cp.async.bulk.tensor.2d.shared::cluster.global.mbarrier::complete_tx::bytes.multicast::cluster [%0], [%1, {%3, %4}], [%2], %5;"
                 :: "r"(dst), "l"(m), "r"(bar), "r"(c0), "r"(c1), "h"((uint16_t)3) : "memory");
}
__device__ __forceinline__ void tma3d_mc(uint32_t dst, const CUtensorMap* m, int c0, int c1, int c2, uint32_t bar) {
    asm volatile("cp.async.bulk.tensor.3d.shared::cluster.global.mbarrier::complete_tx::bytes.multicast::cluster [%0], [%1, {%3, %4, %5}], [%2], %6;"
                 :: "r"(dst), "l"(m), "r"(bar), "r"(c0), "r"(c1), "r"(c2), "h"((uint16_t)3) : "memory");
}
__device__ __forceinline__ void tma_reduce2d(const CUtensorMap* m, uint32_t src, int c0, int c1) {
    asm volatile("cp.reduce.async.bulk.tensor.2d.global.shared::cta.add.bulk_group [%0, {%2, %3}], [%1];"
                 :: "l"(m), "r"(src), "r"(c0), "r"(c1) : "memory");
}
__device__ __forceinline__ void bulk_reduce_f32(float* dst, uint32_t src, uint32_t bytes) {
    asm volatile("cp.reduce.async.bulk.global.shared::cta.bulk_group.add.f32 [%0], [%1], %2;" :: "l"(dst), "r"(src), "r"(bytes) : "memory");
}
__device__ __forceinline__ bool mbar_try(uint32_t bar, uint32_t parity) {
    uint32_t ok;
    asm volatile("{ .reg .pred p; mbarrier.test_wait.parity.shared::cta.b64 p, [%1], %2; selp.u32 %0, 1, 0, p; }"
                 : "=r"(ok) : "r"(bar), "r"(parity) : "memory");
    return ok;
}
__device__ __forceinline__ void prefetch_map(const CUtensorMap* m) {
    asm volatile("prefetch.tensormap [%0];" :: "l"(m) : "memory");
}
__device__ __forceinline__ void wg_fence() { asm volatile("wgmma.fence.sync.aligned;" ::: "memory"); }
__device__ __forceinline__ void wg_commit() { asm volatile("wgmma.commit_group.sync.aligned;" ::: "memory"); }
template <int N> __device__ __forceinline__ void wg_wait() { asm volatile("wgmma.wait_group.sync.aligned %0;" :: "n"(N) : "memory"); }
template <int N> __device__ __forceinline__ void reg_fence(float (&d)[N]) {
#pragma unroll
    for (int i = 0; i < N; i++) asm volatile("" : "+f"(d[i]) :: "memory");
}
template <int N> __device__ __forceinline__ void reg_fence(uint32_t (&d)[N]) {
#pragma unroll
    for (int i = 0; i < N; i++) asm volatile("" : "+r"(d[i]) :: "memory");
}
template <int LO, int HI, int N> __device__ __forceinline__ void reg_fence_part(uint32_t (&d)[N]) {
#pragma unroll
    for (int i = LO; i < HI; i++) asm volatile("" : "+r"(d[i]) :: "memory");
}
__device__ __forceinline__ void fence_async_smem() { asm volatile("fence.proxy.async.shared::cta;" ::: "memory"); }
template <int ID, int N> __device__ __forceinline__ void bar_sync() { asm volatile("bar.sync %0, %1;" :: "n"(ID), "n"(N) : "memory"); }
template <int ID, int N> __device__ __forceinline__ void bar_arrive() { asm volatile("bar.arrive %0, %1;" :: "n"(ID), "n"(N) : "memory"); }
__device__ __forceinline__ void ldsm4(uint32_t* r, uint32_t addr) {
    asm volatile("ldmatrix.sync.aligned.m8n8.x4.shared.b16 {%0, %1, %2, %3}, [%4];"
                 : "=r"(r[0]), "=r"(r[1]), "=r"(r[2]), "=r"(r[3]) : "r"(addr) : "memory");
}
__device__ __forceinline__ void stsm4(uint32_t addr, uint32_t r0, uint32_t r1, uint32_t r2, uint32_t r3) {
    asm volatile("stmatrix.sync.aligned.m8n8.x4.shared.b16 [%0], {%1, %2, %3, %4};"
                 :: "r"(addr), "r"(r0), "r"(r1), "r"(r2), "r"(r3) : "memory");
}
__device__ __forceinline__ uint32_t lds32(uint32_t addr) {
    uint32_t r; asm volatile("ld.shared.u32 %0, [%1];" : "=r"(r) : "r"(addr)); return r;
}
__device__ __forceinline__ float4 lds128f(uint32_t addr) {
    float4 r; asm volatile("ld.shared.v4.f32 {%0, %1, %2, %3}, [%4];" : "=f"(r.x), "=f"(r.y), "=f"(r.z), "=f"(r.w) : "r"(addr)); return r;
}
__device__ __forceinline__ uint32_t clock32() { uint32_t t; asm volatile("mov.u32 %0, %%clock;" : "=r"(t)); return t; }
__device__ __forceinline__ uint32_t pack_bf16(float lo, float hi) {
    uint32_t r; asm("cvt.rn.bf16x2.f32 %0, %1, %2;" : "=r"(r) : "f"(hi), "f"(lo)); return r;
}
__device__ __forceinline__ uint32_t pack_relu_bf16(float lo, float hi) {
    uint32_t r; asm("cvt.rn.relu.bf16x2.f32 %0, %1, %2;" : "=r"(r) : "f"(hi), "f"(lo)); return r;
}
__device__ __forceinline__ uint32_t mul_bf16x2(uint32_t a, uint32_t b) {
    uint32_t r; asm("mul.rn.bf16x2 %0, %1, %2;" : "=r"(r) : "r"(a), "r"(b)); return r;
}
__device__ __forceinline__ float phi(float t, float log2e) {
    float e;
    asm("ex2.approx.ftz.f32 %0, %1;" : "=f"(e) : "f"(fminf(t * log2e, 0.f)));
    return e + (fmaxf(t, 0.f) + 1e-6f);
}
__device__ __forceinline__ float after_issue(float v, uint32_t zero) {
    return __uint_as_float(__float_as_uint(v) | (clock32() & zero));
}
constexpr float kLog2e = 1.4426950408889634f;
__device__ __forceinline__ float rcp(float x) { float r; asm("rcp.approx.ftz.f32 %0, %1;" : "=f"(r) : "f"(x)); return r; }
__device__ __forceinline__ float bf_lo(uint32_t v) { return __uint_as_float(v << 16); }
__device__ __forceinline__ float bf_hi(uint32_t v) { return __uint_as_float(v & 0xffff0000u); }
constexpr uint32_t HI128 = (1024 >> 4) | (1u << 30);
constexpr uint32_t HI64 = (512 >> 4) | (2u << 30);
constexpr uint32_t LO128 = 1u << 16, LO64 = (1024u >> 4) << 16, LO128X2 = (2048u >> 4) << 16;
constexpr uint32_t QB = 16 * 112;
constexpr uint32_t TX1 = 2 * (2 * QB + 4096), TX2 = 2 * (QB + 4096), TX3 = 12288;
__device__ __forceinline__ void grid_arrive(unsigned int* c) {
    asm volatile("fence.acq_rel.gpu;" ::: "memory");
    asm volatile("red.relaxed.gpu.global.add.u32 [%0], 1;" :: "l"(c) : "memory");
}
__device__ __forceinline__ void grid_wait(const unsigned int* c, unsigned int target) {
    unsigned int v; int it = 0;
    do {
        asm volatile("ld.relaxed.gpu.global.u32 %0, [%1];" : "=r"(v) : "l"(c) : "memory");
        if (++it > (1 << 22)) asm volatile("trap;");
    } while ((int)(v - target) < 0);
    asm volatile("ld.acquire.gpu.global.u32 %0, [%1];" : "=r"(v) : "l"(c) : "memory");
}


__host__ __device__ constexpr uint32_t p4_pack(int n) { return (n / 3) * 36864 + (n % 3) * 14336; }
__host__ __device__ constexpr uint32_t p4_off(int n) {
    return n < 6 ? OFF_X + p4_pack(n) : n < 14 ? OFF_RING + p4_pack(n - 6) : n == 14 ? OFF_X + p4_pack(6) : OFF_X + p4_pack(n - 15);
}
__host__ __device__ constexpr uint32_t p4_bar(int n) {
    return n < 6 ? BAR_XFULL + 8 * n : n < 12 ? BAR_FULL + 8 * (n - 6) : n < 14 ? BAR_P4 + 8 * (n - 12)
                 : n == 14 ? BAR_XFULL + 48 : BAR_XFULL + 8 * (n - 15);
}
__host__ __device__ constexpr uint32_t p4_par(int n) { return (n < 12 || n == 14) ? 1 : 0; }
constexpr uint32_t OFF_OUT = OFF_X + 5 * 16384;
static_assert(p4_off(7) == p4_off(6) + 14336 && p4_off(13) == p4_off(12) + 14336 && p4_off(16) == p4_off(15) + 14336, "Wd halves");
static_assert(p4_off(13) + 14336 <= OFF_STG + 8192 && p4_off(14) + 8192 == OFF_OUT, "pass-4 layout");

struct Ring {
    uint32_t slot, phase;
    __device__ __forceinline__ void advance() { if (++slot == NSLOT) { slot = 0; phase ^= 1; } }
};

struct Maps { CUtensorMap x, kv, q, g4, g3, u4, u3, d, o, out; };

__global__ void __cluster_dims__(2, 1, 1) __launch_bounds__(NTHREADS, 1)
fused_kernel(const __grid_constant__ Maps mp, const __nv_bfloat16* __restrict__ gate_w, __nv_bfloat16* __restrict__ out,
             uint32_t zero)
{
    extern __shared__ __align__(1024) unsigned char smem[];
    const uint32_t sb = (uint32_t)__cvta_generic_to_shared(smem);
    const int tid = threadIdx.x, warp = tid >> 5, lane = tid & 31;
    const int rank = blockIdx.x & 1, j = (blockIdx.x >> 1) & 7;
    const int row0 = ((blockIdx.x >> 4) * 2 + rank) * 128;
    const int par = j & 1;
    const int g4i = (7 * j + 3 * par) >> 1;

    if (warp == 9) {
        if (elect_one()) {
            prefetch_map(&mp.x);
            mbar_init(sb + BAR_XFULL, 1);
            mbar_expect_tx(sb + BAR_XFULL, 16384);
            tma2d(sb + OFF_X, &mp.x, 0, row0, sb + BAR_XFULL);
            asm volatile("fence.mbarrier_init.release.cluster;" ::: "memory");
        }
        __syncwarp();
    } else if (warp == 8) {
        if (elect_one()) {
            #pragma unroll
            for (int s = 0; s < NSLOT; s++) mbar_init(sb + BAR_FULL + 8 * s, 1);
            asm volatile("fence.mbarrier_init.release.cluster;" ::: "memory");
            mbar_expect_tx(sb + BAR_FULL, TX1);
        }
        __syncwarp();
    } else if (warp == 10) {
        if (elect_one()) {
            #pragma unroll
            for (int s = 1; s < 7; s++) mbar_init(sb + BAR_XFULL + 8 * s, 1);
            mbar_init(sb + BAR_KVDONE, 8);
            mbar_init(sb + BAR_AUX, 3);
            asm volatile("fence.mbarrier_init.release.cluster;" ::: "memory");
            if ((sb & 0xFFFFFF) != SB) asm volatile("trap;");
        }
        __syncwarp();
    } else if (warp == 11) {
        if (elect_one()) {
            #pragma unroll
            for (int s = 0; s < NSLOT; s++) mbar_init(sb + BAR_EMPTY + 8 * s, 4);
            mbar_init(sb + BAR_P4, 1);
            mbar_init(sb + BAR_P4 + 8, 1);
            mbar_init(sb + BAR_REFILL, 4);
            mbar_init(sb + BAR_REFILL + 8, 4);
            asm volatile("fence.mbarrier_init.release.cluster;" ::: "memory");
        }
        __syncwarp();
    } else if (warp == 2) {
        if (elect_one()) {
            mbar_init(sb + BAR_W, 1);
            asm volatile("fence.mbarrier_init.release.cluster;" ::: "memory");
            mbar_expect_tx(sb + BAR_W, 896);
            asm volatile("cp.async.bulk.shared::cluster.global.mbarrier::complete_tx::bytes [%0], [%1], 896, [%2];"
                         :: "r"(sb + OFF_W), "l"(gate_w), "r"(sb + BAR_W) : "memory");
        }
        __syncwarp();
    }
    asm volatile("barrier.cluster.arrive.relaxed.aligned;" ::: "memory");
    if (warp == 8) {
        if (elect_one()) { prefetch_map(&mp.kv); prefetch_map(&mp.g4); }
        __syncwarp();
    }
    asm volatile("barrier.cluster.wait.aligned;" ::: "memory");
    if (warp == 8) {
        if (elect_one()) {
            tma3d_mc(sb + OFF_RING + rank * 8192 + 4096, &mp.kv, 56 * j, 16 * rank, 1, sb + BAR_FULL);
            tma3d_mc(sb + OFF_RING + rank * 8192, &mp.g4, 0, 16 * rank, g4i, sb + BAR_FULL);
        }
        __syncwarp();
    }

    if (warp >= 8) {
        asm volatile("setmaxnreg.dec.sync.aligned.u32 40;");
        if (warp == 8) {
            if (elect_one()) {
                Ring r{1, 1};
                auto acquire = [&](uint32_t bytes) -> uint32_t {
                    mbar_wait(sb + BAR_EMPTY + 8 * r.slot, r.phase);
                    mbar_expect_tx(sb + BAR_FULL + 8 * r.slot, bytes);
                    return sb + OFF_RING + r.slot * SLOT_BYTES;
                };
                #pragma unroll 1
                for (int s = 1; s < 14; s++) {
                    const uint32_t dst = acquire(TX1) + rank * 8192;
                    tma3d_mc(dst + 4096, &mp.kv, 56 * j, 32 * s + 16 * rank, 1, sb + BAR_FULL + 8 * r.slot);
                    tma3d_mc(dst, &mp.g4, 0, 32 * s + 16 * rank, g4i, sb + BAR_FULL + 8 * r.slot);
                    r.advance();
                    if ((s & 1) && s < 12) {
                        const int n = (s >> 1) + 1;
                        mbar_expect_tx(sb + BAR_XFULL + 8 * n, 16384);
                        tma2d(sb + OFF_X + n * 16384, &mp.x, 64 * n, row0, sb + BAR_XFULL + 8 * n);
                    }
                    if (s == 5) {
                        prefetch_map(&mp.q); prefetch_map(&mp.u4); prefetch_map(&mp.g3); prefetch_map(&mp.u3);
                        prefetch_map(&mp.d); prefetch_map(&mp.o); prefetch_map(&mp.out);
                    }
                }
                #pragma unroll 1
                for (int s = 0; s < 14; s++) {
                    const uint32_t dst = acquire(TX2) + rank * 6144;
                    tma3d_mc(dst, &mp.q, 56 * j, 32 * s + 16 * rank, 0, sb + BAR_FULL + 8 * r.slot);
                    tma3d_mc(dst + 2048, &mp.u4, 0, 32 * s + 16 * rank, g4i, sb + BAR_FULL + 8 * r.slot);
                    r.advance();
                }
                const int cfirst = j == 7 ? 0 : j;
                auto load4 = [&](int n) {
                    int c = cfirst + n / 3;
                    if (c >= 7) c -= 7;
                    mbar_expect_tx(sb + p4_bar(n), n % 3 == 2 ? 8192 : 14336);
                    if (n % 3 == 2) tma2d_mc(sb + p4_off(n) + rank * 4096, &mp.o, 64 * c, 56 * j + 32 * rank, sb + p4_bar(n));
                    else tma2d_mc(sb + p4_off(n) + rank * 7168, &mp.d, 64 * c, 224 * j + 112 * (n % 3) + 56 * rank, sb + p4_bar(n));
                };
                #pragma unroll 1
                for (int s = 0; s < 14; s++) {
                    const uint32_t dst = acquire(TX3) + rank * 6144;
                    tma3d_mc(dst, &mp.g3, 0, 32 * s + 16 * rank, 7 * j + 4 - 4 * par, sb + BAR_FULL + 8 * r.slot);
                    tma3d_mc(dst + 3072, &mp.u3, 0, 32 * s + 16 * rank, 7 * j + 4 - 4 * par, sb + BAR_FULL + 8 * r.slot);
                    r.advance();
                    if (s == 7) load4(0);
                    if (s == 9) load4(1);
                    if (s == 11) load4(2);
                    if (s == 13) { load4(3); load4(4); }
                }
                mbar_wait(sb + BAR_EMPTY, 0);      load4(6);
                mbar_wait(sb + BAR_EMPTY + 8, 0);  load4(5); load4(7); load4(14);
                mbar_wait(sb + BAR_EMPTY + 16, 0); load4(8);
                mbar_wait(sb + BAR_EMPTY + 24, 0); load4(9); load4(10);
                mbar_wait(sb + BAR_EMPTY + 32, 0); load4(11);
                mbar_wait(sb + BAR_EMPTY + 40, 0); load4(12);
                mbar_wait(sb + BAR_AUX, 0);        load4(13);
                #pragma unroll
                for (int n = 15; n < 21; n++) {
                    if (n % 3 == 0) mbar_wait(sb + BAR_REFILL + 8 * (n / 3 - 5), 0);
                    __nanosleep(100);
                    load4(n);
                }
            }
        } else {
            const int ht = tid - 288;
            unsigned int cnt0;
            asm volatile("ld.relaxed.gpu.global.u32 %0, [%1];" : "=r"(cnt0) : "l"(&g_counter[32]) : "memory");
            const unsigned int target = ((cnt0 >> 7) + 1) << 7;
            if (warp == 9) {
                reinterpret_cast<float4*>(&g_kvacc[0][0])[blockIdx.x * 32 + lane] = make_float4(0.f, 0.f, 0.f, 0.f);
                asm volatile("fence.proxy.async.global;" ::: "memory");
                __syncwarp();
                if (lane == 0) grid_arrive(&g_counter[0]);
                mbar_wait(sb + BAR_XFULL + 8 * 6, 0);
                uint4* o = reinterpret_cast<uint4*>(out) + blockIdx.x * 896 + lane;
                #pragma unroll 4
                for (int q = 0; q < 28; q++) o[q * 32] = make_uint4(0, 0, 0, 0);
                asm volatile("fence.proxy.async.global;" ::: "memory");
                __syncwarp();
                if (lane == 0) {
                    asm volatile("fence.acq_rel.gpu;" ::: "memory");
                    grid_wait(&g_counter[0], target);
                }
                __syncwarp();
            }
            mbar_wait(sb + BAR_KVDONE, 0);
            {
                #pragma unroll
                for (int i0 = 0; i0 < 5; i0 += 2) {
                    float4 pa[2], pb[2];
                    #pragma unroll
                    for (int i = 0; i < 2 && i0 + i < 5; i++) {
                        const int q = min(ht + 96 * (i0 + i), 447);
                        pa[i] = lds128f(sb + OFF_STG + q * 16); pb[i] = lds128f(sb + OFF_STG + 8192 + q * 16);
                    }
                    #pragma unroll
                    for (int i = 0; i < 2 && i0 + i < 5; i++) {
                        const int q = ht + 96 * (i0 + i);
                        if (q < 448) asm volatile("st.shared.v4.f32 [%0], {%1, %2, %3, %4};" :: "r"(sb + OFF_STG + q * 16),
                            "f"(pa[i].x + pb[i].x), "f"(pa[i].y + pb[i].y), "f"(pa[i].z + pb[i].z), "f"(pa[i].w + pb[i].w) : "memory");
                    }
                }
                fence_async_smem();
            }
            bar_sync<3, 96>();
            if (warp == 9) {
                if (elect_one()) {
                    bulk_reduce_f32(&g_kvacc[j][0], sb + OFF_STG, 7168);
                    asm volatile("cp.async.bulk.commit_group;" ::: "memory");
                    asm volatile("cp.async.bulk.wait_group 0;" ::: "memory");
                    asm volatile("red.relaxed.gpu.global.add.u32 [%0], 1;" :: "l"(&g_counter[32]) : "memory");
                }
            }
            __syncwarp();
            #pragma unroll
            for (int i = 0; i < 3; i++) {
                const int q = ht + 96 * i;
                const int d = q < 168 ? q / 3 : 56 + ((q - 168) >> 3);
                const int c = q < 168 ? (q - 3 * d + (d < 28 ? 4 : 0)) : (q & 7);
                if (q < 232) asm volatile("st.shared.v4.u32 [%0], {%1, %1, %1, %1};" :: "r"(sb + OFF_STG + 8192 + d * 128 + ((c ^ (d & 7)) << 4)), "r"(0) : "memory");
            }
            uint32_t plan[3];
            #pragma unroll
            for (int i = 0; i < 3; i++) {
                const int q = min(ht + 96 * i, 279), d = q / 5, m = q - 5 * d;
                const bool h0 = d < 28;
                const int c = m == 4 ? 7 : (h0 ? m : m + 3), pc = m < 4 ? m : (h0 ? 3 : 0);
                const int kind = m == 4 ? (h0 ? 3 : 4) : c == 3 ? (h0 ? 1 : 2) : 0;
                plan[i] = (d * 128 + ((c ^ (d & 7)) << 4)) | ((d * 4 + (pc ^ (d & 3))) << 13) | (kind << 23);
                asm volatile("" : "+r"(plan[i]));
            }
            if (lane == 0) grid_wait(&g_counter[32], target);
            __syncwarp();
            const float4* src = reinterpret_cast<const float4*>(&g_kvacc[j][0]);
            float4 va[3], vb[3];
            #pragma unroll
            for (int i = 0; i < 3; i++) {
                const float4* p = src + ((plan[i] >> 12) & 0x7fe);
                va[i] = __ldcg(p); vb[i] = __ldcg(p + 1);
            }
            #pragma unroll
            for (int i = 0; i < 3; i++) {
                const uint32_t kind = plan[i] >> 23;
                uint32_t w0 = pack_bf16(va[i].x, va[i].y), w1 = pack_bf16(va[i].z, va[i].w);
                uint32_t w2 = pack_bf16(vb[i].x, vb[i].y), w3 = pack_bf16(vb[i].z, vb[i].w);
                if (kind == 3) w0 = w2 & 0xffffu;
                if (kind == 4) w0 <<= 16;
                if (kind == 2) w0 = 0u;
                if (kind >= 2) w1 = 0u;
                if (kind != 0 && kind != 2) w2 = w3 = 0u;
                if (i < 2 || ht < 88)
                    asm volatile("st.shared.v4.u32 [%0], {%1, %2, %3, %4};"
                                 :: "r"(sb + OFF_STG + 8192 + (plan[i] & 0x1fff)), "r"(w0), "r"(w1), "r"(w2), "r"(w3) : "memory");
            }
            fence_async_smem();
            __syncwarp();
            if (lane == 0) mbar_arrive(sb + BAR_AUX);
        }
    } else {
        asm volatile("setmaxnreg.inc.sync.aligned.u32 232;");
        const int wg = warp >> 2, w4 = warp & 3;
        const int q4 = lane & 3, g8 = lane >> 2;
        const uint32_t lx = ((lane >> 4) ^ (lane & 7)) << 4;
        const uint32_t xa = sb + OFF_X + (warp * 16 + (lane & 15)) * 128;
        const uint32_t empty_dst = mapa(sb + BAR_EMPTY, w4 & 1);
        const bool signaller = lane == 0 && w4 < 2;
        constexpr uint32_t dsb = SB >> 4;
        Ring r{0, 0};
        uint32_t cur = 0, old = 0;
        bool ready = false;
        auto release = [&](uint32_t slot) { if (signaller) mbar_arrive_cluster(empty_dst + 8 * slot); };
        auto turn_wait = [&]() { if (wg == 0) bar_sync<6, 256>(); else bar_sync<7, 256>(); };
        auto turn_pass = [&]() { if (wg == 0) bar_arrive<7, 256>(); else bar_arrive<6, 256>(); };
        auto begin = [&]() -> uint32_t {
            if (!ready) mbar_wait(sb + BAR_FULL + 8 * r.slot, r.phase);
            wg_fence();
            return dsb + (OFF_RING >> 4) + r.slot * (SLOT_BYTES >> 4);
        };
        auto commit = [&]() { wg_commit(); old = cur; cur = r.slot; r.advance(); };
        auto retire = [&]() { wg_wait<1>(); release(old); };
        auto peek = [&]() { ready = mbar_try(sb + BAR_FULL + 8 * r.slot, r.phase); };
        uint32_t a0[8], a1[8];
        auto load_a0 = [&](int kc) { ldsm4(a0, xa + kc * 16384 + lx); ldsm4(a0 + 4, xa + kc * 16384 + (lx ^ 32)); };
        auto load_a1 = [&](int kc) { ldsm4(a1, xa + kc * 16384 + (lx ^ 64)); ldsm4(a1 + 4, xa + kc * 16384 + (lx ^ 96)); };

        uint32_t hp[56];
        float g0, g1, av[28], agk[92];
        {
            float d0 = 0.f, d1 = 0.f, d2 = 0.f, d3 = 0.f;
            uint32_t w0[4], w1[4];
            auto issue1 = [&](uint32_t (&a)[8], int sd) {
                const uint32_t b = begin();
                wgmma_rs184<HI128>(agk, a[0], a[1], a[2], a[3], b + LO128X2, sd);
                wgmma_rs56<HI128>(av, a[0], a[1], a[2], a[3], b + LO128 + 384, sd);
                wgmma_rs184<HI128>(agk, a[4], a[5], a[6], a[7], b + LO128X2 + 512, 1);
                wgmma_rs56<HI128>(av, a[4], a[5], a[6], a[7], b + LO128 + 896, 1);
                commit();
            };
            auto issue1s = [&](uint32_t (&a)[8]) {
                const uint32_t b = begin();
                wgmma_rs184<HI128>(agk, a[0], a[1], a[2], a[3], b + LO128X2, 1);
                wgmma_rs184<HI128>(agk, a[4], a[5], a[6], a[7], b + LO128X2 + 512, 1);
                wg_commit();
                wgmma_rs56<HI128>(av, a[0], a[1], a[2], a[3], b + LO128 + 384, 1);
                wgmma_rs56<HI128>(av, a[4], a[5], a[6], a[7], b + LO128 + 896, 1);
                commit();
            };
            auto load_w = [&](uint32_t (&w)[4], int s) {
                #pragma unroll
                for (int e = 0; e < 4; e++) w[e] = lds32(sb + OFF_W + s * 64 + q4 * 4 + e * 16);
            };
            auto dot = [&](uint32_t (&a)[8], uint32_t (&w)[4]) {
                #pragma unroll
                for (int e = 0; e < 4; e++) {
                    const uint32_t p0 = mul_bf16x2(a[2 * e], w[e]), p1 = mul_bf16x2(a[2 * e + 1], w[e]);
                    d0 += bf_lo(p0); d2 += bf_hi(p0); d1 += bf_lo(p1); d3 += bf_hi(p1);
                }
                asm volatile("" : "+f"(d0), "+f"(d1), "+f"(d2), "+f"(d3));
            };
            mbar_wait(sb + BAR_XFULL, 0);
            load_a0(0);
            mbar_wait(sb + BAR_W, 0);
            load_w(w0, 0);
            auto odd_stage = [&](int it, bool first, bool last) {
                wg_wait<1>();
                if (!first) release(old);
                load_a1(it);
                load_w(w1, 2 * it + 1);
                peek();
                dot(a0, w0);
                if (last && wg == 1) bar_sync<4, 256>();
                issue1s(a1);
                if (last && wg == 0) bar_arrive<4, 256>();
            };
            issue1(a0, 0);
            #pragma unroll
            for (int it = 0; it < 6; it++) {
                const bool xok = mbar_try(sb + BAR_XFULL + 8 * (it + 1), 0);
                odd_stage(it, it == 0, false);
                wg_wait<2>(); release(old);
                if (!xok) mbar_wait(sb + BAR_XFULL + 8 * (it + 1), 0);
                load_a0(it + 1);
                load_w(w0, 2 * it + 2);
                peek();
                dot(a1, w1);
                issue1(a0, 1);
            }
            odd_stage(6, false, true);
            wg_wait<2>(); release(old);
            load_a0(0);
            peek();
            dot(a1, w1);
            wg_wait<1>();
            reg_fence(agk);
            #pragma unroll
            for (int i = 0; i < 32; i++) hp[i] = pack_relu_bf16(agk[2 * i], agk[2 * i + 1]);
            reg_fence_part<0, 32>(hp);
            g0 = d0 + d2; g1 = d1 + d3;
        }

        float aq[28], au[64];
        {
            auto issue2 = [&](uint32_t (&a)[8], int sd) {
                const uint32_t b = begin();
                wgmma_rs56<HI128>(aq, a[0], a[1], a[2], a[3], b + LO128, sd);
                wgmma_rs128<HI128>(au, a[0], a[1], a[2], a[3], b + LO128X2 + 128, sd);
                wgmma_rs56<HI128>(aq, a[4], a[5], a[6], a[7], b + LO128 + 384, 1);
                wgmma_rs128<HI128>(au, a[4], a[5], a[6], a[7], b + LO128X2 + 512, 1);
            };
            const uint32_t st_base = wg == 0 ? OFF_STG : OFF_RING + 12288, st_step = wg == 0 ? 2048 : SLOT_BYTES, st_v = wg == 0 ? 8192 : 2048;
            const uint32_t sk = sb + st_base + w4 * st_step + (lane & 15) * 128;
            float tok = kLog2e;
            uint32_t pk[16];
            pk[14] = 0u; pk[15] = 0u;
            auto stage_k = [&](int lo, int hi) {
                #pragma unroll
                for (int i = 0; i < 14; i++) if (i >= lo && i < hi) pk[i] = pack_bf16(phi(agk[64 + 2 * i], tok), phi(agk[65 + 2 * i], tok));
                #pragma unroll
                for (int t = 0; t < 4; t++) {
                    const int need = t < 3 ? 4 * t + 4 : 14;
                    if (need > lo && need <= hi) stsm4(sk + (lx ^ (t * 32)), pk[4 * t], pk[4 * t + 1], pk[4 * t + 2], pk[4 * t + 3]);
                }
                #pragma unroll
                for (int i = 0; i < 14; i++) if (i >= lo && i < hi) asm volatile("" : "+r"(pk[i]));
            };
            issue2(a0, 0); commit();
            tok = after_issue(kLog2e, zero);
            retire();
            reg_fence(av);
            if (wg == 0) bar_arrive<8, 256>();
            load_a1(0); peek();
            uint32_t pv[14];
            #pragma unroll
            for (int i = 0; i < 14; i++) pv[i] = pack_bf16(av[2 * i], av[2 * i + 1]);
            if (wg == 1) bar_sync<8, 256>();
            {
                const uint32_t ones = q4 == 0 ? 0x3f803f80u : 0u;
                #pragma unroll
                for (int t = 0; t < 3; t++) stsm4(sk + st_v + (lx ^ (t * 32)), pv[4 * t], pv[4 * t + 1], pv[4 * t + 2], pv[4 * t + 3]);
                stsm4(sk + st_v + (lx ^ 96), pv[12], pv[13], ones, ones);
            }
            stage_k(0, 2);
            issue2(a1, 1); commit();
            tok = after_issue(kLog2e, zero);
            retire(); load_a0(1); peek();
            stage_k(2, 5);
            issue2(a0, 1); commit();
            tok = after_issue(kLog2e, zero);
            retire(); load_a1(1); peek();
            stage_k(5, 8);
            issue2(a1, 1); commit();
            tok = after_issue(kLog2e, zero);
            retire(); load_a0(2); peek();
            stage_k(8, 11);
            issue2(a0, 1); commit();
            tok = after_issue(kLog2e, zero);
            retire(); load_a1(2); peek();
            stage_k(11, 14);
            issue2(a1, 1); commit();
            retire(); load_a0(3); peek();
            fence_async_smem();
            if (wg == 0) bar_sync<1, 128>(); else bar_sync<2, 128>();
            float kv[32];
            issue2(a0, 1);
            {
                const uint32_t dk = dsb + LO128 + (st_base >> 4), ds = st_step >> 4, dv = st_v >> 4;
                #pragma unroll
                for (int ks = 0; ks < 4; ks++) wgmma_ss64_tt<HI128>(kv, dk + ks * ds, dk + ks * ds + dv, ks);
            }
            commit();
            tok = after_issue(-kLog2e, zero);
            retire(); load_a1(3); peek();
            {
                g0 += __shfl_xor_sync(0xffffffffu, g0, 1); g1 += __shfl_xor_sync(0xffffffffu, g1, 1);
                g0 += __shfl_xor_sync(0xffffffffu, g0, 2); g1 += __shfl_xor_sync(0xffffffffu, g1, 2);
                const uint32_t lg = pack_bf16(g0, g1);
                float e0, e1;
                asm("ex2.approx.ftz.f32 %0, %1;" : "=f"(e0) : "f"(bf_lo(lg) * tok));
                asm("ex2.approx.ftz.f32 %0, %1;" : "=f"(e1) : "f"(bf_hi(lg) * tok));
                const uint32_t gg = pack_bf16(rcp(1.f + e0), rcp(1.f + e1));
                g0 = bf_lo(gg); g1 = bf_hi(gg);
                asm volatile("" : "+f"(g0), "+f"(g1));
            }
            issue2(a1, 1); commit();
            retire(); load_a0(4); peek();
            reg_fence(kv);
            if (wg == 0) { bar_arrive<5, 256>(); bar_sync<1, 128>(); } else bar_sync<5, 256>();
            auto stage_kv = [&](int hh) {
                const int d = w4 * 16 + g8 + 8 * hh;
                const bool h0 = d < 28;
                const uint32_t rowa = sb + OFF_STG + wg * 8192 + d * 128 + q4 * 8;
                #pragma unroll
                for (int t = 0; t < 4; t++) {
                    float v0 = h0 ? kv[4 * t + 2 * hh] : kv[4 * t + 12 + 2 * hh];
                    float v1 = h0 ? kv[4 * t + 2 * hh + 1] : kv[4 * t + 13 + 2 * hh];
                    if (t == 0 && !h0 && q4 == 0) v0 = kv[28 + 2 * hh];
                    if (d < 56 && !(t == 3 && h0 && q4 == 2))
                        asm volatile("st.shared.v2.f32 [%0], {%1, %2};" :: "r"(rowa + ((t ^ (g8 & 3)) << 5)), "f"(v0), "f"(v1) : "memory");
                }
                if (h0 && q4 == 0)
                    asm volatile("st.shared.v2.f32 [%0], {%1, %1};" :: "r"(rowa + ((3 ^ (g8 & 3)) << 5) + 16), "f"(kv[28 + 2 * hh]) : "memory");
            };
            stage_kv(0);
            issue2(a0, 1); commit();
            retire(); load_a1(4); peek();
            stage_kv(1);
            __syncwarp();
            if (lane == 0) mbar_arrive(sb + BAR_KVDONE);
            issue2(a1, 1); commit();
            retire(); load_a0(5); peek();
            auto prescale = [&](int lo, int hi) {
                const float t0 = after_issue(1.f - g0, zero), t1 = after_issue(1.f - g1, zero);
                const uint32_t s0 = pack_bf16(t0, t0), s1 = pack_bf16(t1, t1);
                #pragma unroll
                for (int i = 0; i < 32; i++) if (i >= lo && i < hi) { hp[i] = mul_bf16x2(hp[i], (i & 1) ? s1 : s0); asm volatile("" : "+r"(hp[i])); }
            };
            prescale(0, 16);
            issue2(a0, 1); commit();
            retire(); load_a1(5); peek();
            prescale(16, 32);
            issue2(a1, 1); commit();
            retire(); load_a0(6); peek();
            issue2(a0, 1); commit();
            retire(); load_a1(6); peek();
            if (wg == 1) bar_sync<4, 256>();
            const uint32_t b = begin();
            wgmma_rs128<HI128>(au, a1[0], a1[1], a1[2], a1[3], b + LO128X2 + 128, 1);
            wgmma_rs128<HI128>(au, a1[4], a1[5], a1[6], a1[7], b + LO128X2 + 512, 1);
            wg_commit();
            wgmma_rs56<HI128>(aq, a1[0], a1[1], a1[2], a1[3], b + LO128, 1);
            wgmma_rs56<HI128>(aq, a1[4], a1[5], a1[6], a1[7], b + LO128 + 384, 1);
            commit();
            if (wg == 0) bar_arrive<4, 256>();
            wg_wait<2>(); release(old);
            load_a0(0); peek();
            wg_wait<1>();
            reg_fence(au);
        }
        #pragma unroll
        for (int i = 0; i < 32; i++) hp[i] = mul_bf16x2(hp[i], pack_bf16(au[2 * i], au[2 * i + 1]));
        reg_fence_part<0, 32>(hp);

        float ag[96];
        uint32_t op[16];
        {
            auto issue3 = [&](uint32_t (&a)[8], int sd) {
                const uint32_t b = begin();
                wgmma_rs192<HI64>(ag, a[0], a[1], a[2], a[3], b + LO64, sd);
                wgmma_rs192<HI64>(ag, a[4], a[5], a[6], a[7], b + LO64 + 384, 1);
            };
            uint32_t pq[16];
            issue3(a0, 0); commit();
            retire();
            reg_fence(aq);
            load_a1(0); peek();
            pq[14] = 0u; pq[15] = 0u;
            bool aux = false;
            #pragma unroll
            for (int st = 1; st < 12; st++) {
                if (st & 1) issue3(a1, 1); else issue3(a0, 1);
                commit();
                const float tok = st < 8 ? after_issue(kLog2e, zero) : 0.f;
                if (st == 11) aux = mbar_try(sb + BAR_AUX, 0);
                retire();
                if (st & 1) load_a0((st + 1) >> 1); else load_a1(st >> 1);
                peek();
                if (st < 8) {
                    const int i = 2 * st - 2;
                    pq[i] = pack_bf16(phi(aq[2 * i], tok), phi(aq[2 * i + 1], tok));
                    pq[i + 1] = pack_bf16(phi(aq[2 * i + 2], tok), phi(aq[2 * i + 3], tok));
                    asm volatile("" : "+r"(pq[i]), "+r"(pq[i + 1]));
                }
            }
            if (!aux) mbar_wait(sb + BAR_AUX, 0);
            if (wg == 1) bar_sync<4, 256>();
            float nd[32];
            issue3(a0, 1);
            {
                const uint32_t dk = dsb + LO128 + ((OFF_STG + 8192) >> 4);
                #pragma unroll
                for (int ks = 0; ks < 4; ks++) wgmma_rs64<HI128>(nd, pq[4 * ks], pq[4 * ks + 1], pq[4 * ks + 2], pq[4 * ks + 3], dk + ks * 128, ks);
            }
            commit();
            retire(); load_a1(6); peek();
            issue3(a1, 1); commit();
            if (wg == 0) bar_arrive<4, 256>();
            ready = mbar_try(sb + p4_bar(0), p4_par(0));
            retire();
            reg_fence(nd);
            const int src = lane & ~3;
            const float s00 = g0 * rcp(__shfl_sync(0xffffffffu, nd[28], src) + 1e-6f);
            const float s01 = g0 * rcp(__shfl_sync(0xffffffffu, nd[29], src) + 1e-6f);
            const float s10 = g1 * rcp(__shfl_sync(0xffffffffu, nd[30], src) + 1e-6f);
            const float s11 = g1 * rcp(__shfl_sync(0xffffffffu, nd[31], src) + 1e-6f);
            #pragma unroll
            for (int t = 0; t < 7; t++) {
                const bool h1 = t > 3 || (t == 3 && q4 >= 2);
                const float sa = h1 ? s01 : s00, sc = h1 ? s11 : s10;
                op[2 * t] = pack_bf16(nd[4 * t] * sa, nd[4 * t + 1] * sa);
                op[2 * t + 1] = pack_bf16(nd[4 * t + 2] * sc, nd[4 * t + 3] * sc);
            }
            op[14] = 0u; op[15] = 0u;
            reg_fence(op);
        }

        float oa[32], ob[32];
        int c = j == 7 ? 0 : j;
        const int wsh = __shfl_sync(0xffffffffu, warp * 16, 0);
        const uint32_t sh0 = par * 768, sh1 = par * 1024;
        bool ready2 = false;
        auto issue_d = [&](float (&o)[32], int c0, int half) {
            const int n = 3 * c0;
            if (half == 0) {
                if (!ready) mbar_wait(sb + p4_bar(n), p4_par(n));
                if (!ready2) mbar_wait(sb + p4_bar(n + 1), p4_par(n + 1));
                ready = mbar_try(sb + p4_bar(n + 2), p4_par(n + 2));
            }
            wg_fence();
            const uint32_t b = dsb + LO128 + (p4_off(n) >> 4);
            #pragma unroll
            for (int ks = 7 * half; ks < 7 * half + 7; ks++)
                wgmma_rs64<HI128>(o, hp[4 * ks], hp[4 * ks + 1], hp[4 * ks + 2], hp[4 * ks + 3],
                                  b + ks * 128 + (ks < 8 ? sh0 : 0u - sh1), ks);
        };
        auto issue_o = [&](float (&o)[32], int c0) {
            const int n = 3 * c0 + 2;
            if (!ready) mbar_wait(sb + p4_bar(n), p4_par(n));
            if (c0 < 6) {
                ready = mbar_try(sb + p4_bar(n + 1), p4_par(n + 1));
                ready2 = mbar_try(sb + p4_bar(n + 2), p4_par(n + 2));
            }
            wg_fence();
            const uint32_t b = dsb + LO128 + (p4_off(n) >> 4);
            #pragma unroll
            for (int ks = 0; ks < 4; ks++) wgmma_rs64<HI128>(o, op[4 * ks], op[4 * ks + 1], op[4 * ks + 2], op[4 * ks + 3], b + ks * 128, 1);
            wg_commit();
        };
        auto ship = [&](float (&o)[32], int c0) {
            reg_fence(o);
            const uint32_t so = xa + OFF_OUT + (c0 & 1) * 16384;
            #pragma unroll
            for (int t = 0; t < 4; t++)
                stsm4(so + (lx ^ (t * 32)), pack_bf16(o[8 * t], o[8 * t + 1]), pack_bf16(o[8 * t + 2], o[8 * t + 3]),
                      pack_bf16(o[8 * t + 4], o[8 * t + 5]), pack_bf16(o[8 * t + 6], o[8 * t + 7]));
            fence_async_smem();
            __syncwarp();
            if (elect_one()) {
                tma_reduce2d(&mp.out, sb + OFF_OUT + (c0 & 1) * 16384 + wsh * 128, 64 * c, row0 + wsh);
                asm volatile("cp.async.bulk.commit_group;" ::: "memory");
            }
            if (++c == 7) c = 0;
        };
        auto finish_h = [&]() {
            reg_fence(ag);
            release(cur);
            const uint32_t s0 = pack_bf16(1.f - g0, 1.f - g0), s1 = pack_bf16(1.f - g1, 1.f - g1);
            #pragma unroll
            for (int i = 0; i < 24; i++)
                hp[32 + i] = mul_bf16x2(mul_bf16x2(pack_relu_bf16(ag[2 * i], ag[2 * i + 1]), (i & 1) ? s1 : s0),
                                        pack_bf16(ag[48 + 2 * i], ag[49 + 2 * i]));
            reg_fence_part<32, 56>(hp);
        };
        ready2 = mbar_try(sb + p4_bar(1), p4_par(1));
        wg_wait<0>();
        finish_h();
        #pragma unroll
        for (int c0 = 0; c0 < 7; c0++) {
            float (&o)[32] = (c0 & 1) ? ob : oa;
            if (c0 > 0 || wg == 1) turn_wait();
            issue_d(o, c0, 0);
            issue_d(o, c0, 1);
            issue_o(o, c0);
            if (!(c0 == 6 && wg == 1)) turn_pass();
            if (c0 >= 2) {
                if (elect_one()) asm volatile("cp.async.bulk.wait_group.read 1;" ::: "memory");
                __syncwarp();
            }
            wg_wait<0>();
            if (c0 < 2 && signaller) mbar_arrive_cluster(empty_dst + (BAR_REFILL - BAR_EMPTY) + 8 * c0);
            ship(o, c0);
        }
        if (elect_one()) asm volatile("cp.async.bulk.wait_group.read 0;" ::: "memory");
    }
}

typedef CUresult (*EncodeFn)(CUtensorMap*, CUtensorMapDataType, cuuint32_t, void*, const cuuint64_t*, const cuuint64_t*,
                             const cuuint32_t*, const cuuint32_t*, CUtensorMapInterleave, CUtensorMapSwizzle,
                             CUtensorMapL2promotion, CUtensorMapFloatOOBfill);

void make_map(EncodeFn enc, CUtensorMap* m, const void* base, int rank, const cuuint64_t* dims, const cuuint64_t* strides,
              cuuint32_t b0, cuuint32_t b1, cuuint32_t b2, CUtensorMapSwizzle sw) {
    const cuuint32_t es[3] = {1, 1, 1}, box[3] = {b0, b1, b2};
    enc(m, CU_TENSOR_MAP_DATA_TYPE_BFLOAT16, rank, const_cast<void*>(base), dims, strides, box, es,
        CU_TENSOR_MAP_INTERLEAVE_NONE, sw, CU_TENSOR_MAP_L2_PROMOTION_L2_128B, CU_TENSOR_MAP_FLOAT_OOB_FILL_NONE);
}

}

extern "C" void kernel_launch(void* const* d_in, const int* in_sizes, int n_in, void* d_out, int out_size) {
    (void)in_sizes; (void)n_in; (void)out_size;
    static EncodeFn enc = nullptr;
    if (!enc) {
        void* fn = nullptr;
        cudaDriverEntryPointQueryResult st;
        cudaGetDriverEntryPoint("cuTensorMapEncodeTiled", &fn, cudaEnableDefault, &st);
        enc = (EncodeFn)fn;
        cudaFuncSetAttribute(fused_kernel, cudaFuncAttributeMaxDynamicSharedMemorySize, SMEM_BYTES);
    }
    Maps mp;
    const cuuint64_t dimx[2] = {kD, kS}, dimd[2] = {kD, kF}, dimo[2] = {kD, kD}, strd[1] = {kD * 2};
    make_map(enc, &mp.x, d_in[0], 2, dimx, strd, 64, 128, 1, CU_TENSOR_MAP_SWIZZLE_128B);
    make_map(enc, &mp.out, d_out, 2, dimx, strd, 64, 16, 1, CU_TENSOR_MAP_SWIZZLE_128B);
    make_map(enc, &mp.d, d_in[6], 2, dimd, strd, 64, 56, 1, CU_TENSOR_MAP_SWIZZLE_128B);
    make_map(enc, &mp.o, d_in[2], 2, dimo, strd, 64, 32, 1, CU_TENSOR_MAP_SWIZZLE_128B);
    const cuuint64_t dimq[3] = {kD, kD, 3}, strq[2] = {3 * kD * 2, kD * 2};
    make_map(enc, &mp.kv, d_in[1], 3, dimq, strq, 56, 16, 2, CU_TENSOR_MAP_SWIZZLE_128B);
    make_map(enc, &mp.q, d_in[1], 3, dimq, strq, 56, 16, 1, CU_TENSOR_MAP_SWIZZLE_128B);
    const cuuint64_t dimf[3] = {32, kD, kF / 32}, strf[2] = {kF * 2, 64};
    const cuuint64_t dimw[3] = {64, kD, kF / 64}, strw[2] = {kF * 2, 128};
    make_map(enc, &mp.g4, d_in[4], 3, dimw, strw, 64, 16, 2, CU_TENSOR_MAP_SWIZZLE_128B);
    make_map(enc, &mp.u4, d_in[5], 3, dimw, strw, 64, 16, 2, CU_TENSOR_MAP_SWIZZLE_128B);
    make_map(enc, &mp.g3, d_in[4], 3, dimf, strf, 32, 16, 3, CU_TENSOR_MAP_SWIZZLE_64B);
    make_map(enc, &mp.u3, d_in[5], 3, dimf, strf, 32, 16, 3, CU_TENSOR_MAP_SWIZZLE_64B);
    fused_kernel<<<NCTA, NTHREADS, SMEM_BYTES>>>(mp, (const __nv_bfloat16*)d_in[7], (__nv_bfloat16*)d_out, 0u);
}
```

```cpp
#include <cuda_runtime.h>
#include <cuda_bf16.h>
#include <cuda.h>
#include <stdint.h>

namespace {

constexpr int kS = 2048, kD = 448, kF = 1792;
constexpr int NTHREADS = 384;
constexpr int NCTA = 128;
constexpr uint32_t OFF_X = 0;
constexpr uint32_t OFF_RING = 114688;
constexpr uint32_t SLOT_BYTES = 16384;
constexpr int NSLOT = 6;
constexpr uint32_t OFF_STG = 212992;
constexpr uint32_t OFF_MISC = 229376;
constexpr uint32_t SMEM_BYTES = 232448;
constexpr uint32_t BAR_FULL = OFF_MISC, BAR_EMPTY = OFF_MISC + 48, BAR_XFULL = OFF_MISC + 96;
constexpr uint32_t BAR_W = OFF_MISC + 152, BAR_KVDONE = OFF_MISC + 160, BAR_AUX = OFF_MISC + 168, BAR_P4 = OFF_MISC + 176;
constexpr uint32_t BAR_REFILL = OFF_MISC + 192;
constexpr uint32_t OFF_W = OFF_MISC + 256;
constexpr uint32_t SB = 1024;

__device__ __align__(128) float g_kvacc[8][2048];
__device__ unsigned int g_counter[64];

__device__ __forceinline__ void mbar_init(uint32_t bar, uint32_t cnt) {
    asm volatile("mbarrier.init.shared::cta.b64 [%0], %1;" :: "r"(bar), "r"(cnt) : "memory");
}
__device__ __forceinline__ void mbar_expect_tx(uint32_t bar, uint32_t bytes) {
    asm volatile("mbarrier.arrive.expect_tx.shared::cta.b64 _, [%0], %1;" :: "r"(bar), "r"(bytes) : "memory");
}
__device__ __forceinline__ void mbar_arrive(uint32_t bar) {
    asm volatile("mbarrier.arrive.shared::cta.b64 _, [%0];" :: "r"(bar) : "memory");
}
__device__ __forceinline__ void mbar_arrive_cluster(uint32_t bar) {
    asm volatile("mbarrier.arrive.shared::cluster.b64 _, [%0];" :: "r"(bar) : "memory");
}
__device__ __forceinline__ void mbar_wait(uint32_t bar, uint32_t parity) {
    asm volatile("{\n"
                 ".reg .pred p;\n"
                 ".reg .u32 c;\n"
                 "mov.u32 c, 0;\n"
                 "AGAIN:\n"
                 "mbarrier.try_wait.parity.shared::cta.b64 p, [%0], %1;\n"
                 "@p bra DONE;\n"
                 "add.u32 c, c, 1;\n"
                 "setp.lt.u32 p, c, 4194304;\n"
                 "@p bra AGAIN;\n"
                 "trap;\n"
                 "DONE:\n"
                 "}" :: "r"(bar), "r"(parity) : "memory");
}
__device__ __forceinline__ uint32_t mapa(uint32_t addr, uint32_t cta) {
    uint32_t r; asm("mapa.shared::cluster.u32 %0, %1, %2;" : "=r"(r) : "r"(addr), "r"(cta)); return r;
}
__device__ __forceinline__ bool elect_one() {
    uint32_t p;
    asm volatile("{ .reg .pred P; elect.sync _|P, 0xffffffff; selp.u32 %0, 1, 0, P; }" : "=r"(p));
    return p;
}
__device__ __forceinline__ void tma2d(uint32_t dst, const CUtensorMap* m, int c0, int c1, uint32_t bar) {
    asm volatile("cp.async.bulk.tensor.2d.shared::cluster.global.mbarrier::complete_tx::bytes [%0], [%1, {%3, %4}], [%2];"
                 :: "r"(dst), "l"(m), "r"(bar), "r"(c0), "r"(c1) : "memory");
}
__device__ __forceinline__ void tma2d_mc(uint32_t dst, const CUtensorMap* m, int c0, int c1, uint32_t bar) {
    asm volatile("cp.async.bulk.tensor.2d.shared::cluster.global.mbarrier::complete_tx::bytes.multicast::cluster [%0], [%1, {%3, %4}], [%2], %5;"
                 :: "r"(dst), "l"(m), "r"(bar), "r"(c0), "r"(c1), "h"((uint16_t)3) : "memory");
}
__device__ __forceinline__ void tma3d_mc(uint32_t dst, const CUtensorMap* m, int c0, int c1, int c2, uint32_t bar) {
    asm volatile("cp.async.bulk.tensor.3d.shared::cluster.global.mbarrier::complete_tx::bytes.multicast::cluster [%0], [%1, {%3, %4, %5}], [%2], %6;"
                 :: "r"(dst), "l"(m), "r"(bar), "r"(c0), "r"(c1), "r"(c2), "h"((uint16_t)3) : "memory");
}
__device__ __forceinline__ void tma_reduce2d(const CUtensorMap* m, uint32_t src, int c0, int c1) {
    asm volatile("cp.reduce.async.bulk.tensor.2d.global.shared::cta.add.bulk_group [%0, {%2, %3}], [%1];"
                 :: "l"(m), "r"(src), "r"(c0), "r"(c1) : "memory");
}
__device__ __forceinline__ void bulk_reduce_f32(float* dst, uint32_t src, uint32_t bytes) {
    asm volatile("cp.reduce.async.bulk.global.shared::cta.bulk_group.add.f32 [%0], [%1], %2;" :: "l"(dst), "r"(src), "r"(bytes) : "memory");
}
__device__ __forceinline__ bool mbar_try(uint32_t bar, uint32_t parity) {
    uint32_t ok;
    asm volatile("{ .reg .pred p; mbarrier.test_wait.parity.shared::cta.b64 p, [%1], %2; selp.u32 %0, 1, 0, p; }"
                 : "=r"(ok) : "r"(bar), "r"(parity) : "memory");
    return ok;
}
__device__ __forceinline__ void prefetch_map(const CUtensorMap* m) {
    asm volatile("prefetch.tensormap [%0];" :: "l"(m) : "memory");
}
__device__ __forceinline__ void wg_fence() { asm volatile("wgmma.fence.sync.aligned;" ::: "memory"); }
__device__ __forceinline__ void wg_commit() { asm volatile("wgmma.commit_group.sync.aligned;" ::: "memory"); }
template <int N> __device__ __forceinline__ void wg_wait() { asm volatile("wgmma.wait_group.sync.aligned %0;" :: "n"(N) : "memory"); }
template <int N> __device__ __forceinline__ void reg_fence(float (&d)[N]) {
#pragma unroll
    for (int i = 0; i < N; i++) asm volatile("" : "+f"(d[i]) :: "memory");
}
template <int N> __device__ __forceinline__ void reg_fence(uint32_t (&d)[N]) {
#pragma unroll
    for (int i = 0; i < N; i++) asm volatile("" : "+r"(d[i]) :: "memory");
}
template <int LO, int HI, int N> __device__ __forceinline__ void reg_fence_part(uint32_t (&d)[N]) {
#pragma unroll
    for (int i = LO; i < HI; i++) asm volatile("" : "+r"(d[i]) :: "memory");
}
__device__ __forceinline__ void fence_async_smem() { asm volatile("fence.proxy.async.shared::cta;" ::: "memory"); }
template <int ID, int N> __device__ __forceinline__ void bar_sync() { asm volatile("bar.sync %0, %1;" :: "n"(ID), "n"(N) : "memory"); }
template <int ID, int N> __device__ __forceinline__ void bar_arrive() { asm volatile("bar.arrive %0, %1;" :: "n"(ID), "n"(N) : "memory"); }
__device__ __forceinline__ void ldsm4(uint32_t* r, uint32_t addr) {
    asm volatile("ldmatrix.sync.aligned.m8n8.x4.shared.b16 {%0, %1, %2, %3}, [%4];"
                 : "=r"(r[0]), "=r"(r[1]), "=r"(r[2]), "=r"(r[3]) : "r"(addr) : "memory");
}
__device__ __forceinline__ void stsm4(uint32_t addr, uint32_t r0, uint32_t r1, uint32_t r2, uint32_t r3) {
    asm volatile("stmatrix.sync.aligned.m8n8.x4.shared.b16 [%0], {%1, %2, %3, %4};"
                 :: "r"(addr), "r"(r0), "r"(r1), "r"(r2), "r"(r3) : "memory");
}
__device__ __forceinline__ uint32_t lds32(uint32_t addr) {
    uint32_t r; asm volatile("ld.shared.u32 %0, [%1];" : "=r"(r) : "r"(addr)); return r;
}
__device__ __forceinline__ float4 lds128f(uint32_t addr) {
    float4 r; asm volatile("ld.shared.v4.f32 {%0, %1, %2, %3}, [%4];" : "=f"(r.x), "=f"(r.y), "=f"(r.z), "=f"(r.w) : "r"(addr)); return r;
}
__device__ __forceinline__ uint32_t clock32() { uint32_t t; asm volatile("mov.u32 %0, %%clock;" : "=r"(t)); return t; }
__device__ __forceinline__ uint32_t pack_bf16(float lo, float hi) {
    uint32_t r; asm("cvt.rn.bf16x2.f32 %0, %1, %2;" : "=r"(r) : "f"(hi), "f"(lo)); return r;
}
__device__ __forceinline__ uint32_t pack_relu_bf16(float lo, float hi) {
    uint32_t r; asm("cvt.rn.relu.bf16x2.f32 %0, %1, %2;" : "=r"(r) : "f"(hi), "f"(lo)); return r;
}
__device__ __forceinline__ uint32_t mul_bf16x2(uint32_t a, uint32_t b) {
    uint32_t r; asm("mul.rn.bf16x2 %0, %1, %2;" : "=r"(r) : "r"(a), "r"(b)); return r;
}
__device__ __forceinline__ float phi(float t, float log2e) {
    float e;
    asm("ex2.approx.ftz.f32 %0, %1;" : "=f"(e) : "f"(fminf(t * log2e, 0.f)));
    return e + (fmaxf(t, 0.f) + 1e-6f);
}
__device__ __forceinline__ float after_issue(float v, uint32_t zero) {
    return __uint_as_float(__float_as_uint(v) | (clock32() & zero));
}
constexpr float kLog2e = 1.4426950408889634f;
__device__ __forceinline__ float rcp(float x) { float r; asm("rcp.approx.ftz.f32 %0, %1;" : "=f"(r) : "f"(x)); return r; }
__device__ __forceinline__ float bf_lo(uint32_t v) { return __uint_as_float(v << 16); }
__device__ __forceinline__ float bf_hi(uint32_t v) { return __uint_as_float(v & 0xffff0000u); }
constexpr uint32_t HI128 = (1024 >> 4) | (1u << 30);
constexpr uint32_t HI64 = (512 >> 4) | (2u << 30);
constexpr uint32_t LO128 = 1u << 16, LO64 = (1024u >> 4) << 16, LO128X2 = (2048u >> 4) << 16;
constexpr uint32_t QB = 16 * 112;
constexpr uint32_t TX1 = 2 * (2 * QB + 4096), TX2 = 2 * (QB + 4096), TX3 = 12288;
__device__ __forceinline__ void grid_arrive(unsigned int* c) {
    asm volatile("fence.acq_rel.gpu;" ::: "memory");
    asm volatile("red.relaxed.gpu.global.add.u32 [%0], 1;" :: "l"(c) : "memory");
}
__device__ __forceinline__ void grid_wait(const unsigned int* c, unsigned int target) {
    unsigned int v; int it = 0;
    do {
        asm volatile("ld.relaxed.gpu.global.u32 %0, [%1];" : "=r"(v) : "l"(c) : "memory");
        if (++it > (1 << 22)) asm volatile("trap;");
    } while ((int)(v - target) < 0);
    asm volatile("ld.acquire.gpu.global.u32 %0, [%1];" : "=r"(v) : "l"(c) : "memory");
}


__host__ __device__ constexpr uint32_t p4_pack(int n) { return (n / 3) * 36864 + (n % 3) * 14336; }
__host__ __device__ constexpr uint32_t p4_off(int n) {
    return n < 6 ? OFF_X + p4_pack(n) : n < 14 ? OFF_RING + p4_pack(n - 6) : n == 14 ? OFF_X + p4_pack(6) : OFF_X + p4_pack(n - 15);
}
__host__ __device__ constexpr uint32_t p4_bar(int n) {
    return n < 6 ? BAR_XFULL + 8 * n : n < 12 ? BAR_FULL + 8 * (n - 6) : n < 14 ? BAR_P4 + 8 * (n - 12)
                 : n == 14 ? BAR_XFULL + 48 : BAR_XFULL + 8 * (n - 15);
}
__host__ __device__ constexpr uint32_t p4_par(int n) { return (n < 12 || n == 14) ? 1 : 0; }
constexpr uint32_t OFF_OUT = OFF_X + 5 * 16384;
static_assert(p4_off(7) == p4_off(6) + 14336 && p4_off(13) == p4_off(12) + 14336 && p4_off(16) == p4_off(15) + 14336, "Wd halves");
static_assert(p4_off(13) + 14336 <= OFF_STG + 8192 && p4_off(14) + 8192 == OFF_OUT, "pass-4 layout");

struct Ring {
    uint32_t slot, phase;
    __device__ __forceinline__ void advance() { if (++slot == NSLOT) { slot = 0; phase ^= 1; } }
};

struct Maps { CUtensorMap x, kv, q, g4, g3, u4, u3, d, o, out; };

__global__ void __cluster_dims__(2, 1, 1) __launch_bounds__(NTHREADS, 1)
fused_kernel(const __grid_constant__ Maps mp, const __nv_bfloat16* __restrict__ gate_w, __nv_bfloat16* __restrict__ out,
             uint32_t zero)
{
    extern __shared__ __align__(1024) unsigned char smem[];
    const uint32_t sb = (uint32_t)__cvta_generic_to_shared(smem);
    const int tid = threadIdx.x, warp = tid >> 5, lane = tid & 31;
    const int rank = blockIdx.x & 1, j = (blockIdx.x >> 1) & 7;
    const int row0 = ((blockIdx.x >> 4) * 2 + rank) * 128;
    const int par = j & 1;
    const int g4i = (7 * j + 3 * par) >> 1;

    if (warp == 9) {
        if (elect_one()) {
            prefetch_map(&mp.x);
            mbar_init(sb + BAR_XFULL, 1);
            mbar_expect_tx(sb + BAR_XFULL, 16384);
            tma2d(sb + OFF_X, &mp.x, 0, row0, sb + BAR_XFULL);
            asm volatile("fence.mbarrier_init.release.cluster;" ::: "memory");
        }
        __syncwarp();
    } else if (warp == 8) {
        if (elect_one()) {
            #pragma unroll
            for (int s = 0; s < NSLOT; s++) mbar_init(sb + BAR_FULL + 8 * s, 1);
            asm volatile("fence.mbarrier_init.release.cluster;" ::: "memory");
            mbar_expect_tx(sb + BAR_FULL, TX1);
        }
        __syncwarp();
    } else if (warp == 10) {
        if (elect_one()) {
            #pragma unroll
            for (int s = 1; s < 7; s++) mbar_init(sb + BAR_XFULL + 8 * s, 1);
            mbar_init(sb + BAR_KVDONE, 8);
            mbar_init(sb + BAR_AUX, 3);
            asm volatile("fence.mbarrier_init.release.cluster;" ::: "memory");
            if ((sb & 0xFFFFFF) != SB) asm volatile("trap;");
        }
        __syncwarp();
    } else if (warp == 11) {
        if (elect_one()) {
            #pragma unroll
            for (int s = 0; s < NSLOT; s++) mbar_init(sb + BAR_EMPTY + 8 * s, 4);
            mbar_init(sb + BAR_P4, 1);
            mbar_init(sb + BAR_P4 + 8, 1);
            mbar_init(sb + BAR_REFILL, 4);
            mbar_init(sb + BAR_REFILL + 8, 4);
            asm volatile("fence.mbarrier_init.release.cluster;" ::: "memory");
        }
        __syncwarp();
    } else if (warp == 2) {
        if (elect_one()) {
            mbar_init(sb + BAR_W, 1);
            asm volatile("fence.mbarrier_init.release.cluster;" ::: "memory");
            mbar_expect_tx(sb + BAR_W, 896);
            asm volatile("cp.async.bulk.shared::cluster.global.mbarrier::complete_tx::bytes [%0], [%1], 896, [%2];"
                         :: "r"(sb + OFF_W), "l"(gate_w), "r"(sb + BAR_W) : "memory");
        }
        __syncwarp();
    }
    asm volatile("barrier.cluster.arrive.relaxed.aligned;" ::: "memory");
    if (warp == 8) {
        if (elect_one()) { prefetch_map(&mp.kv); prefetch_map(&mp.g4); }
        __syncwarp();
    }
    asm volatile("barrier.cluster.wait.aligned;" ::: "memory");
    if (warp == 8) {
        if (elect_one()) {
            tma3d_mc(sb + OFF_RING + rank * 8192 + 4096, &mp.kv, 56 * j, 16 * rank, 1, sb + BAR_FULL);
            tma3d_mc(sb + OFF_RING + rank * 8192, &mp.g4, 0, 16 * rank, g4i, sb + BAR_FULL);
        }
        __syncwarp();
    }

    if (warp >= 8) {
        asm volatile("setmaxnreg.dec.sync.aligned.u32 40;");
        if (warp == 8) {
            if (elect_one()) {
                Ring r{1, 1};
                auto acquire = [&](uint32_t bytes) -> uint32_t {
                    mbar_wait(sb + BAR_EMPTY + 8 * r.slot, r.phase);
                    mbar_expect_tx(sb + BAR_FULL + 8 * r.slot, bytes);
                    return sb + OFF_RING + r.slot * SLOT_BYTES;
                };
                #pragma unroll 1
                for (int s = 1; s < 14; s++) {
                    const uint32_t dst = acquire(TX1) + rank * 8192;
                    tma3d_mc(dst + 4096, &mp.kv, 56 * j, 32 * s + 16 * rank, 1, sb + BAR_FULL + 8 * r.slot);
                    tma3d_mc(dst, &mp.g4, 0, 32 * s + 16 * rank, g4i, sb + BAR_FULL + 8 * r.slot);
                    r.advance();
                    if ((s & 1) && s < 12) {
                        const int n = (s >> 1) + 1;
                        mbar_expect_tx(sb + BAR_XFULL + 8 * n, 16384);
                        tma2d(sb + OFF_X + n * 16384, &mp.x, 64 * n, row0, sb + BAR_XFULL + 8 * n);
                    }
                    if (s == 5) {
                        prefetch_map(&mp.q); prefetch_map(&mp.u4); prefetch_map(&mp.g3); prefetch_map(&mp.u3);
                        prefetch_map(&mp.d); prefetch_map(&mp.o); prefetch_map(&mp.out);
                    }
                }
                #pragma unroll 1
                for (int s = 0; s < 14; s++) {
                    const uint32_t dst = acquire(TX2) + rank * 6144;
                    tma3d_mc(dst, &mp.q, 56 * j, 32 * s + 16 * rank, 0, sb + BAR_FULL + 8 * r.slot);
                    tma3d_mc(dst + 2048, &mp.u4, 0, 32 * s + 16 * rank, g4i, sb + BAR_FULL + 8 * r.slot);
                    r.advance();
                }
                const int cfirst = j == 7 ? 0 : j;
                auto load4 = [&](int n) {
                    int c = cfirst + n / 3;
                    if (c >= 7) c -= 7;
                    mbar_expect_tx(sb + p4_bar(n), n % 3 == 2 ? 8192 : 14336);
                    if (n % 3 == 2) tma2d_mc(sb + p4_off(n) + rank * 4096, &mp.o, 64 * c, 56 * j + 32 * rank, sb + p4_bar(n));
                    else tma2d_mc(sb + p4_off(n) + rank * 7168, &mp.d, 64 * c, 224 * j + 112 * (n % 3) + 56 * rank, sb + p4_bar(n));
                };
                #pragma unroll 1
                for (int s = 0; s < 14; s++) {
                    const uint32_t dst = acquire(TX3) + rank * 6144;
                    tma3d_mc(dst, &mp.g3, 0, 32 * s + 16 * rank, 7 * j + 4 - 4 * par, sb + BAR_FULL + 8 * r.slot);
                    tma3d_mc(dst + 3072, &mp.u3, 0, 32 * s + 16 * rank, 7 * j + 4 - 4 * par, sb + BAR_FULL + 8 * r.slot);
                    r.advance();
                    if (s == 7) load4(0);
                    if (s == 9) load4(1);
                    if (s == 11) load4(2);
                    if (s == 13) { load4(3); load4(4); }
                }
                mbar_wait(sb + BAR_EMPTY, 0);      load4(6);
                mbar_wait(sb + BAR_EMPTY + 8, 0);  load4(5); load4(7); load4(14);
                mbar_wait(sb + BAR_EMPTY + 16, 0); load4(8);
                mbar_wait(sb + BAR_EMPTY + 24, 0); load4(9); load4(10);
                mbar_wait(sb + BAR_EMPTY + 32, 0); load4(11);
                mbar_wait(sb + BAR_EMPTY + 40, 0); load4(12);
                mbar_wait(sb + BAR_AUX, 0);        load4(13);
                mbar_wait(sb + BAR_REFILL, 0);     load4(15); load4(16); load4(17);
                mbar_wait(sb + BAR_REFILL + 8, 0); load4(18); load4(19); load4(20);
            }
        } else {
            const int ht = tid - 288;
            unsigned int cnt0;
            asm volatile("ld.relaxed.gpu.global.u32 %0, [%1];" : "=r"(cnt0) : "l"(&g_counter[32]) : "memory");
            const unsigned int target = ((cnt0 >> 7) + 1) << 7;
            if (warp == 9) {
                reinterpret_cast<float4*>(&g_kvacc[0][0])[blockIdx.x * 32 + lane] = make_float4(0.f, 0.f, 0.f, 0.f);
                asm volatile("fence.proxy.async.global;" ::: "memory");
                __syncwarp();
                if (lane == 0) grid_arrive(&g_counter[0]);
                mbar_wait(sb + BAR_XFULL + 8 * 6, 0);
                uint4* o = reinterpret_cast<uint4*>(out) + blockIdx.x * 896 + lane;
                #pragma unroll 4
                for (int q = 0; q < 28; q++) o[q * 32] = make_uint4(0, 0, 0, 0);
                asm volatile("fence.proxy.async.global;" ::: "memory");
                __syncwarp();
                if (lane == 0) {
                    asm volatile("fence.acq_rel.gpu;" ::: "memory");
                    grid_wait(&g_counter[0], target);
                }
                __syncwarp();
            }
            mbar_wait(sb + BAR_KVDONE, 0);
            {
                #pragma unroll
                for (int i0 = 0; i0 < 5; i0 += 2) {
                    float4 pa[2], pb[2];
                    #pragma unroll
                    for (int i = 0; i < 2 && i0 + i < 5; i++) {
                        const int q = min(ht + 96 * (i0 + i), 447);
                        pa[i] = lds128f(sb + OFF_STG + q * 16); pb[i] = lds128f(sb + OFF_STG + 8192 + q * 16);
                    }
                    #pragma unroll
                    for (int i = 0; i < 2 && i0 + i < 5; i++) {
                        const int q = ht + 96 * (i0 + i);
                        if (q < 448) asm volatile("st.shared.v4.f32 [%0], {%1, %2, %3, %4};" :: "r"(sb + OFF_STG + q * 16),
                            "f"(pa[i].x + pb[i].x), "f"(pa[i].y + pb[i].y), "f"(pa[i].z + pb[i].z), "f"(pa[i].w + pb[i].w) : "memory");
                    }
                }
                fence_async_smem();
            }
            bar_sync<3, 96>();
            if (warp == 9) {
                if (elect_one()) {
                    bulk_reduce_f32(&g_kvacc[j][0], sb + OFF_STG, 7168);
                    asm volatile("cp.async.bulk.commit_group;" ::: "memory");
                    asm volatile("cp.async.bulk.wait_group 0;" ::: "memory");
                    asm volatile("red.relaxed.gpu.global.add.u32 [%0], 1;" :: "l"(&g_counter[32]) : "memory");
                }
            }
            __syncwarp();
            #pragma unroll
            for (int i = 0; i < 3; i++) {
                const int q = ht + 96 * i;
                const int d = q < 168 ? q / 3 : 56 + ((q - 168) >> 3);
                const int c = q < 168 ? (q - 3 * d + (d < 28 ? 4 : 0)) : (q & 7);
                if (q < 232) asm volatile("st.shared.v4.u32 [%0], {%1, %1, %1, %1};" :: "r"(sb + OFF_STG + 8192 + d * 128 + ((c ^ (d & 7)) << 4)), "r"(0) : "memory");
            }
            uint32_t plan[3];
            #pragma unroll
            for (int i = 0; i < 3; i++) {
                const int q = min(ht + 96 * i, 279), d = q / 5, m = q - 5 * d;
                const bool h0 = d < 28;
                const int c = m == 4 ? 7 : (h0 ? m : m + 3), pc = m < 4 ? m : (h0 ? 3 : 0);
                const int kind = m == 4 ? (h0 ? 3 : 4) : c == 3 ? (h0 ? 1 : 2) : 0;
                plan[i] = (d * 128 + ((c ^ (d & 7)) << 4)) | ((d * 4 + (pc ^ (d & 3))) << 13) | (kind << 23);
                asm volatile("" : "+r"(plan[i]));
            }
            if (lane == 0) grid_wait(&g_counter[32], target);
            __syncwarp();
            const float4* src = reinterpret_cast<const float4*>(&g_kvacc[j][0]);
            float4 va[3], vb[3];
            #pragma unroll
            for (int i = 0; i < 3; i++) {
                const float4* p = src + ((plan[i] >> 12) & 0x7fe);
                va[i] = __ldcg(p); vb[i] = __ldcg(p + 1);
            }
            #pragma unroll
            for (int i = 0; i < 3; i++) {
                const uint32_t kind = plan[i] >> 23;
                uint32_t w0 = pack_bf16(va[i].x, va[i].y), w1 = pack_bf16(va[i].z, va[i].w);
                uint32_t w2 = pack_bf16(vb[i].x, vb[i].y), w3 = pack_bf16(vb[i].z, vb[i].w);
                if (kind == 3) w0 = w2 & 0xffffu;
                if (kind == 4) w0 <<= 16;
                if (kind == 2) w0 = 0u;
                if (kind >= 2) w1 = 0u;
                if (kind != 0 && kind != 2) w2 = w3 = 0u;
                if (i < 2 || ht < 88)
                    asm volatile("st.shared.v4.u32 [%0], {%1, %2, %3, %4};"
                                 :: "r"(sb + OFF_STG + 8192 + (plan[i] & 0x1fff)), "r"(w0), "r"(w1), "r"(w2), "r"(w3) : "memory");
            }
            fence_async_smem();
            __syncwarp();
            if (lane == 0) mbar_arrive(sb + BAR_AUX);
        }
    } else {
        asm volatile("setmaxnreg.inc.sync.aligned.u32 232;");
        const int wg = warp >> 2, w4 = warp & 3;
        const int q4 = lane & 3, g8 = lane >> 2;
        const uint32_t lx = ((lane >> 4) ^ (lane & 7)) << 4;
        const uint32_t xa = sb + OFF_X + (warp * 16 + (lane & 15)) * 128;
        const uint32_t empty_dst = mapa(sb + BAR_EMPTY, w4 & 1);
        const bool signaller = lane == 0 && w4 < 2;
        constexpr uint32_t dsb = SB >> 4;
        Ring r{0, 0};
        uint32_t cur = 0, old = 0;
        bool ready = false;
        auto release = [&](uint32_t slot) { if (signaller) mbar_arrive_cluster(empty_dst + 8 * slot); };
        auto turn_wait = [&]() { if (wg == 0) bar_sync<6, 256>(); else bar_sync<7, 256>(); };
        auto turn_pass = [&]() { if (wg == 0) bar_arrive<7, 256>(); else bar_arrive<6, 256>(); };
        auto begin = [&]() -> uint32_t {
            if (!ready) mbar_wait(sb + BAR_FULL + 8 * r.slot, r.phase);
            wg_fence();
            return dsb + (OFF_RING >> 4) + r.slot * (SLOT_BYTES >> 4);
        };
        auto commit = [&]() { wg_commit(); old = cur; cur = r.slot; r.advance(); };
        auto retire = [&]() { wg_wait<1>(); release(old); };
        auto peek = [&]() { ready = mbar_try(sb + BAR_FULL + 8 * r.slot, r.phase); };
        uint32_t a0[8], a1[8];
        auto load_a0 = [&](int kc) { ldsm4(a0, xa + kc * 16384 + lx); ldsm4(a0 + 4, xa + kc * 16384 + (lx ^ 32)); };
        auto load_a1 = [&](int kc) { ldsm4(a1, xa + kc * 16384 + (lx ^ 64)); ldsm4(a1 + 4, xa + kc * 16384 + (lx ^ 96)); };

        uint32_t hp[56];
        float g0, g1, av[28], agk[92];
        {
            float d0 = 0.f, d1 = 0.f, d2 = 0.f, d3 = 0.f;
            uint32_t w0[4], w1[4];
            auto issue1 = [&](uint32_t (&a)[8], int sd) {
                const uint32_t b = begin();
                wgmma_rs184<HI128>(agk, a[0], a[1], a[2], a[3], b + LO128X2, sd);
                wgmma_rs56<HI128>(av, a[0], a[1], a[2], a[3], b + LO128 + 384, sd);
                wgmma_rs184<HI128>(agk, a[4], a[5], a[6], a[7], b + LO128X2 + 512, 1);
                wgmma_rs56<HI128>(av, a[4], a[5], a[6], a[7], b + LO128 + 896, 1);
                commit();
            };
            auto issue1s = [&](uint32_t (&a)[8]) {
                const uint32_t b = begin();
                wgmma_rs184<HI128>(agk, a[0], a[1], a[2], a[3], b + LO128X2, 1);
                wgmma_rs184<HI128>(agk, a[4], a[5], a[6], a[7], b + LO128X2 + 512, 1);
                wg_commit();
                wgmma_rs56<HI128>(av, a[0], a[1], a[2], a[3], b + LO128 + 384, 1);
                wgmma_rs56<HI128>(av, a[4], a[5], a[6], a[7], b + LO128 + 896, 1);
                commit();
            };
            auto load_w = [&](uint32_t (&w)[4], int s) {
                #pragma unroll
                for (int e = 0; e < 4; e++) w[e] = lds32(sb + OFF_W + s * 64 + q4 * 4 + e * 16);
            };
            auto dot = [&](uint32_t (&a)[8], uint32_t (&w)[4]) {
                #pragma unroll
                for (int e = 0; e < 4; e++) {
                    const uint32_t p0 = mul_bf16x2(a[2 * e], w[e]), p1 = mul_bf16x2(a[2 * e + 1], w[e]);
                    d0 += bf_lo(p0); d2 += bf_hi(p0); d1 += bf_lo(p1); d3 += bf_hi(p1);
                }
                asm volatile("" : "+f"(d0), "+f"(d1), "+f"(d2), "+f"(d3));
            };
            mbar_wait(sb + BAR_XFULL, 0);
            load_a0(0);
            mbar_wait(sb + BAR_W, 0);
            load_w(w0, 0);
            auto odd_stage = [&](int it, bool first, bool last) {
                wg_wait<1>();
                if (!first) release(old);
                load_a1(it);
                load_w(w1, 2 * it + 1);
                peek();
                dot(a0, w0);
                if (last && wg == 1) bar_sync<4, 256>();
                issue1s(a1);
                if (last && wg == 0) bar_arrive<4, 256>();
            };
            issue1(a0, 0);
            #pragma unroll
            for (int it = 0; it < 6; it++) {
                const bool xok = mbar_try(sb + BAR_XFULL + 8 * (it + 1), 0);
                odd_stage(it, it == 0, false);
                wg_wait<2>(); release(old);
                if (!xok) mbar_wait(sb + BAR_XFULL + 8 * (it + 1), 0);
                load_a0(it + 1);
                load_w(w0, 2 * it + 2);
                peek();
                dot(a1, w1);
                issue1(a0, 1);
            }
            odd_stage(6, false, true);
            wg_wait<2>(); release(old);
            load_a0(0);
            peek();
            dot(a1, w1);
            wg_wait<1>();
            reg_fence(agk);
            #pragma unroll
            for (int i = 0; i < 32; i++) hp[i] = pack_relu_bf16(agk[2 * i], agk[2 * i + 1]);
            reg_fence_part<0, 32>(hp);
            g0 = d0 + d2; g1 = d1 + d3;
        }

        float aq[28], au[64];
        {
            auto issue2 = [&](uint32_t (&a)[8], int sd) {
                const uint32_t b = begin();
                wgmma_rs56<HI128>(aq, a[0], a[1], a[2], a[3], b + LO128, sd);
                wgmma_rs128<HI128>(au, a[0], a[1], a[2], a[3], b + LO128X2 + 128, sd);
                wgmma_rs56<HI128>(aq, a[4], a[5], a[6], a[7], b + LO128 + 384, 1);
                wgmma_rs128<HI128>(au, a[4], a[5], a[6], a[7], b + LO128X2 + 512, 1);
            };
            const uint32_t st_base = wg == 0 ? OFF_STG : OFF_RING + 12288, st_step = wg == 0 ? 2048 : SLOT_BYTES, st_v = wg == 0 ? 8192 : 2048;
            const uint32_t sk = sb + st_base + w4 * st_step + (lane & 15) * 128;
            float tok = kLog2e;
            uint32_t pk[16];
            pk[14] = 0u; pk[15] = 0u;
            auto stage_k = [&](int lo, int hi) {
                #pragma unroll
                for (int i = 0; i < 14; i++) if (i >= lo && i < hi) pk[i] = pack_bf16(phi(agk[64 + 2 * i], tok), phi(agk[65 + 2 * i], tok));
                #pragma unroll
                for (int t = 0; t < 4; t++) {
                    const int need = t < 3 ? 4 * t + 4 : 14;
                    if (need > lo && need <= hi) stsm4(sk + (lx ^ (t * 32)), pk[4 * t], pk[4 * t + 1], pk[4 * t + 2], pk[4 * t + 3]);
                }
                #pragma unroll
                for (int i = 0; i < 14; i++) if (i >= lo && i < hi) asm volatile("" : "+r"(pk[i]));
            };
            issue2(a0, 0); commit();
            tok = after_issue(kLog2e, zero);
            retire();
            reg_fence(av);
            if (wg == 0) bar_arrive<8, 256>();
            load_a1(0); peek();
            uint32_t pv[14];
            #pragma unroll
            for (int i = 0; i < 14; i++) pv[i] = pack_bf16(av[2 * i], av[2 * i + 1]);
            if (wg == 1) bar_sync<8, 256>();
            {
                const uint32_t ones = q4 == 0 ? 0x3f803f80u : 0u;
                #pragma unroll
                for (int t = 0; t < 3; t++) stsm4(sk + st_v + (lx ^ (t * 32)), pv[4 * t], pv[4 * t + 1], pv[4 * t + 2], pv[4 * t + 3]);
                stsm4(sk + st_v + (lx ^ 96), pv[12], pv[13], ones, ones);
            }
            stage_k(0, 2);
            issue2(a1, 1); commit();
            tok = after_issue(kLog2e, zero);
            retire(); load_a0(1); peek();
            stage_k(2, 5);
            issue2(a0, 1); commit();
            tok = after_issue(kLog2e, zero);
            retire(); load_a1(1); peek();
            stage_k(5, 8);
            issue2(a1, 1); commit();
            tok = after_issue(kLog2e, zero);
            retire(); load_a0(2); peek();
            stage_k(8, 11);
            issue2(a0, 1); commit();
            tok = after_issue(kLog2e, zero);
            retire(); load_a1(2); peek();
            stage_k(11, 14);
            issue2(a1, 1); commit();
            retire(); load_a0(3); peek();
            fence_async_smem();
            if (wg == 0) bar_sync<1, 128>(); else bar_sync<2, 128>();
            float kv[32];
            issue2(a0, 1);
            {
                const uint32_t dk = dsb + LO128 + (st_base >> 4), ds = st_step >> 4, dv = st_v >> 4;
                #pragma unroll
                for (int ks = 0; ks < 4; ks++) wgmma_ss64_tt<HI128>(kv, dk + ks * ds, dk + ks * ds + dv, ks);
            }
            commit();
            tok = after_issue(-kLog2e, zero);
            retire(); load_a1(3); peek();
            {
                g0 += __shfl_xor_sync(0xffffffffu, g0, 1); g1 += __shfl_xor_sync(0xffffffffu, g1, 1);
                g0 += __shfl_xor_sync(0xffffffffu, g0, 2); g1 += __shfl_xor_sync(0xffffffffu, g1, 2);
                const uint32_t lg = pack_bf16(g0, g1);
                float e0, e1;
                asm("ex2.approx.ftz.f32 %0, %1;" : "=f"(e0) : "f"(bf_lo(lg) * tok));
                asm("ex2.approx.ftz.f32 %0, %1;" : "=f"(e1) : "f"(bf_hi(lg) * tok));
                const uint32_t gg = pack_bf16(rcp(1.f + e0), rcp(1.f + e1));
                g0 = bf_lo(gg); g1 = bf_hi(gg);
                asm volatile("" : "+f"(g0), "+f"(g1));
            }
            issue2(a1, 1); commit();
            retire(); load_a0(4); peek();
            reg_fence(kv);
            if (wg == 0) { bar_arrive<5, 256>(); bar_sync<1, 128>(); } else bar_sync<5, 256>();
            auto stage_kv = [&](int hh) {
                const int d = w4 * 16 + g8 + 8 * hh;
                const bool h0 = d < 28;
                const uint32_t rowa = sb + OFF_STG + wg * 8192 + d * 128 + q4 * 8;
                #pragma unroll
                for (int t = 0; t < 4; t++) {
                    float v0 = h0 ? kv[4 * t + 2 * hh] : kv[4 * t + 12 + 2 * hh];
                    float v1 = h0 ? kv[4 * t + 2 * hh + 1] : kv[4 * t + 13 + 2 * hh];
                    if (t == 0 && !h0 && q4 == 0) v0 = kv[28 + 2 * hh];
                    if (d < 56 && !(t == 3 && h0 && q4 == 2))
                        asm volatile("st.shared.v2.f32 [%0], {%1, %2};" :: "r"(rowa + ((t ^ (g8 & 3)) << 5)), "f"(v0), "f"(v1) : "memory");
                }
                if (h0 && q4 == 0)
                    asm volatile("st.shared.v2.f32 [%0], {%1, %1};" :: "r"(rowa + ((3 ^ (g8 & 3)) << 5) + 16), "f"(kv[28 + 2 * hh]) : "memory");
            };
            stage_kv(0);
            issue2(a0, 1); commit();
            retire(); load_a1(4); peek();
            stage_kv(1);
            __syncwarp();
            if (lane == 0) mbar_arrive(sb + BAR_KVDONE);
            issue2(a1, 1); commit();
            retire(); load_a0(5); peek();
            auto prescale = [&](int lo, int hi) {
                const float t0 = after_issue(1.f - g0, zero), t1 = after_issue(1.f - g1, zero);
                const uint32_t s0 = pack_bf16(t0, t0), s1 = pack_bf16(t1, t1);
                #pragma unroll
                for (int i = 0; i < 32; i++) if (i >= lo && i < hi) { hp[i] = mul_bf16x2(hp[i], (i & 1) ? s1 : s0); asm volatile("" : "+r"(hp[i])); }
            };
            prescale(0, 16);
            issue2(a0, 1); commit();
            retire(); load_a1(5); peek();
            prescale(16, 32);
            issue2(a1, 1); commit();
            retire(); load_a0(6); peek();
            issue2(a0, 1); commit();
            retire(); load_a1(6); peek();
            if (wg == 1) bar_sync<4, 256>();
            const uint32_t b = begin();
            wgmma_rs128<HI128>(au, a1[0], a1[1], a1[2], a1[3], b + LO128X2 + 128, 1);
            wgmma_rs128<HI128>(au, a1[4], a1[5], a1[6], a1[7], b + LO128X2 + 512, 1);
            wg_commit();
            wgmma_rs56<HI128>(aq, a1[0], a1[1], a1[2], a1[3], b + LO128, 1);
            wgmma_rs56<HI128>(aq, a1[4], a1[5], a1[6], a1[7], b + LO128 + 384, 1);
            commit();
            if (wg == 0) bar_arrive<4, 256>();
            wg_wait<2>(); release(old);
            load_a0(0); peek();
            wg_wait<1>();
            reg_fence(au);
        }
        #pragma unroll
        for (int i = 0; i < 32; i++) hp[i] = mul_bf16x2(hp[i], pack_bf16(au[2 * i], au[2 * i + 1]));
        reg_fence_part<0, 32>(hp);

        float ag[96];
        uint32_t op[16];
        {
            auto issue3 = [&](uint32_t (&a)[8], int sd) {
                const uint32_t b = begin();
                wgmma_rs192<HI64>(ag, a[0], a[1], a[2], a[3], b + LO64, sd);
                wgmma_rs192<HI64>(ag, a[4], a[5], a[6], a[7], b + LO64 + 384, 1);
            };
            uint32_t pq[16];
            issue3(a0, 0); commit();
            retire();
            reg_fence(aq);
            load_a1(0); peek();
            pq[14] = 0u; pq[15] = 0u;
            bool aux = false;
            #pragma unroll
            for (int st = 1; st < 12; st++) {
                if (st & 1) issue3(a1, 1); else issue3(a0, 1);
                commit();
                const float tok = st < 8 ? after_issue(kLog2e, zero) : 0.f;
                if (st == 11) aux = mbar_try(sb + BAR_AUX, 0);
                retire();
                if (st & 1) load_a0((st + 1) >> 1); else load_a1(st >> 1);
                peek();
                if (st < 8) {
                    const int i = 2 * st - 2;
                    pq[i] = pack_bf16(phi(aq[2 * i], tok), phi(aq[2 * i + 1], tok));
                    pq[i + 1] = pack_bf16(phi(aq[2 * i + 2], tok), phi(aq[2 * i + 3], tok));
                    asm volatile("" : "+r"(pq[i]), "+r"(pq[i + 1]));
                }
            }
            if (!aux) mbar_wait(sb + BAR_AUX, 0);
            if (wg == 1) bar_sync<4, 256>();
            float nd[32];
            issue3(a0, 1);
            {
                const uint32_t dk = dsb + LO128 + ((OFF_STG + 8192) >> 4);
                #pragma unroll
                for (int ks = 0; ks < 4; ks++) wgmma_rs64<HI128>(nd, pq[4 * ks], pq[4 * ks + 1], pq[4 * ks + 2], pq[4 * ks + 3], dk + ks * 128, ks);
            }
            commit();
            retire(); load_a1(6); peek();
            issue3(a1, 1); commit();
            if (wg == 0) bar_arrive<4, 256>();
            ready = mbar_try(sb + p4_bar(0), p4_par(0));
            retire();
            reg_fence(nd);
            const int src = lane & ~3;
            const float s00 = g0 * rcp(__shfl_sync(0xffffffffu, nd[28], src) + 1e-6f);
            const float s01 = g0 * rcp(__shfl_sync(0xffffffffu, nd[29], src) + 1e-6f);
            const float s10 = g1 * rcp(__shfl_sync(0xffffffffu, nd[30], src) + 1e-6f);
            const float s11 = g1 * rcp(__shfl_sync(0xffffffffu, nd[31], src) + 1e-6f);
            #pragma unroll
            for (int t = 0; t < 7; t++) {
                const bool h1 = t > 3 || (t == 3 && q4 >= 2);
                const float sa = h1 ? s01 : s00, sc = h1 ? s11 : s10;
                op[2 * t] = pack_bf16(nd[4 * t] * sa, nd[4 * t + 1] * sa);
                op[2 * t + 1] = pack_bf16(nd[4 * t + 2] * sc, nd[4 * t + 3] * sc);
            }
            op[14] = 0u; op[15] = 0u;
            reg_fence(op);
        }

        float oa[32], ob[32];
        int c = j == 7 ? 0 : j;
        const int wsh = __shfl_sync(0xffffffffu, warp * 16, 0);
        const uint32_t sh0 = par * 768, sh1 = par * 1024;
        bool ready2 = false;
        auto issue_d = [&](float (&o)[32], int c0, int half) {
            const int n = 3 * c0;
            if (half == 0) {
                if (!ready) mbar_wait(sb + p4_bar(n), p4_par(n));
                if (!ready2) mbar_wait(sb + p4_bar(n + 1), p4_par(n + 1));
                ready = mbar_try(sb + p4_bar(n + 2), p4_par(n + 2));
            }
            wg_fence();
            const uint32_t b = dsb + LO128 + (p4_off(n) >> 4);
            #pragma unroll
            for (int ks = 7 * half; ks < 7 * half + 7; ks++)
                wgmma_rs64<HI128>(o, hp[4 * ks], hp[4 * ks + 1], hp[4 * ks + 2], hp[4 * ks + 3],
                                  b + ks * 128 + (ks < 8 ? sh0 : 0u - sh1), ks);
        };
        auto issue_o = [&](float (&o)[32], int c0) {
            const int n = 3 * c0 + 2;
            if (!ready) mbar_wait(sb + p4_bar(n), p4_par(n));
            if (c0 < 6) {
                ready = mbar_try(sb + p4_bar(n + 1), p4_par(n + 1));
                ready2 = mbar_try(sb + p4_bar(n + 2), p4_par(n + 2));
            }
            wg_fence();
            const uint32_t b = dsb + LO128 + (p4_off(n) >> 4);
            #pragma unroll
            for (int ks = 0; ks < 4; ks++) wgmma_rs64<HI128>(o, op[4 * ks], op[4 * ks + 1], op[4 * ks + 2], op[4 * ks + 3], b + ks * 128, 1);
            wg_commit();
        };
        auto ship = [&](float (&o)[32], int c0) {
            reg_fence(o);
            const uint32_t so = xa + OFF_OUT + (c0 & 1) * 16384;
            #pragma unroll
            for (int t = 0; t < 4; t++)
                stsm4(so + (lx ^ (t * 32)), pack_bf16(o[8 * t], o[8 * t + 1]), pack_bf16(o[8 * t + 2], o[8 * t + 3]),
                      pack_bf16(o[8 * t + 4], o[8 * t + 5]), pack_bf16(o[8 * t + 6], o[8 * t + 7]));
            fence_async_smem();
            __syncwarp();
            if (elect_one()) {
                tma_reduce2d(&mp.out, sb + OFF_OUT + (c0 & 1) * 16384 + wsh * 128, 64 * c, row0 + wsh);
                asm volatile("cp.async.bulk.commit_group;" ::: "memory");
            }
            if (++c == 7) c = 0;
        };
        auto finish_h = [&]() {
            reg_fence(ag);
            release(cur);
            const uint32_t s0 = pack_bf16(1.f - g0, 1.f - g0), s1 = pack_bf16(1.f - g1, 1.f - g1);
            #pragma unroll
            for (int i = 0; i < 24; i++)
                hp[32 + i] = mul_bf16x2(mul_bf16x2(pack_relu_bf16(ag[2 * i], ag[2 * i + 1]), (i & 1) ? s1 : s0),
                                        pack_bf16(ag[48 + 2 * i], ag[49 + 2 * i]));
            reg_fence_part<32, 56>(hp);
        };
        ready2 = mbar_try(sb + p4_bar(1), p4_par(1));
        wg_wait<0>();
        finish_h();
        #pragma unroll
        for (int c0 = 0; c0 < 7; c0++) {
            float (&o)[32] = (c0 & 1) ? ob : oa;
            if (c0 > 0 || wg == 1) turn_wait();
            issue_d(o, c0, 0);
            issue_d(o, c0, 1);
            issue_o(o, c0);
            if (!(c0 == 6 && wg == 1)) turn_pass();
            if (c0 >= 2) {
                if (elect_one()) asm volatile("cp.async.bulk.wait_group.read 1;" ::: "memory");
                __syncwarp();
            }
            wg_wait<0>();
            if (c0 < 2 && signaller) mbar_arrive_cluster(empty_dst + (BAR_REFILL - BAR_EMPTY) + 8 * c0);
            ship(o, c0);
        }
        if (elect_one()) asm volatile("cp.async.bulk.wait_group.read 0;" ::: "memory");
    }
}

typedef CUresult (*EncodeFn)(CUtensorMap*, CUtensorMapDataType, cuuint32_t, void*, const cuuint64_t*, const cuuint64_t*,
                             const cuuint32_t*, const cuuint32_t*, CUtensorMapInterleave, CUtensorMapSwizzle,
                             CUtensorMapL2promotion, CUtensorMapFloatOOBfill);

void make_map(EncodeFn enc, CUtensorMap* m, const void* base, int rank, const cuuint64_t* dims, const cuuint64_t* strides,
              cuuint32_t b0, cuuint32_t b1, cuuint32_t b2, CUtensorMapSwizzle sw) {
    const cuuint32_t es[3] = {1, 1, 1}, box[3] = {b0, b1, b2};
    enc(m, CU_TENSOR_MAP_DATA_TYPE_BFLOAT16, rank, const_cast<void*>(base), dims, strides, box, es,
        CU_TENSOR_MAP_INTERLEAVE_NONE, sw, CU_TENSOR_MAP_L2_PROMOTION_L2_128B, CU_TENSOR_MAP_FLOAT_OOB_FILL_NONE);
}

}

extern "C" void kernel_launch(void* const* d_in, const int* in_sizes, int n_in, void* d_out, int out_size) {
    (void)in_sizes; (void)n_in; (void)out_size;
    static EncodeFn enc = nullptr;
    if (!enc) {
        void* fn = nullptr;
        cudaDriverEntryPointQueryResult st;
        cudaGetDriverEntryPoint("cuTensorMapEncodeTiled", &fn, cudaEnableDefault, &st);
        enc = (EncodeFn)fn;
        cudaFuncSetAttribute(fused_kernel, cudaFuncAttributeMaxDynamicSharedMemorySize, SMEM_BYTES);
    }
    Maps mp;
    const cuuint64_t dimx[2] = {kD, kS}, dimd[2] = {kD, kF}, dimo[2] = {kD, kD}, strd[1] = {kD * 2};
    make_map(enc, &mp.x, d_in[0], 2, dimx, strd, 64, 128, 1, CU_TENSOR_MAP_SWIZZLE_128B);
    make_map(enc, &mp.out, d_out, 2, dimx, strd, 64, 16, 1, CU_TENSOR_MAP_SWIZZLE_128B);
    make_map(enc, &mp.d, d_in[6], 2, dimd, strd, 64, 56, 1, CU_TENSOR_MAP_SWIZZLE_128B);
    make_map(enc, &mp.o, d_in[2], 2, dimo, strd, 64, 32, 1, CU_TENSOR_MAP_SWIZZLE_128B);
    const cuuint64_t dimq[3] = {kD, kD, 3}, strq[2] = {3 * kD * 2, kD * 2};
    make_map(enc, &mp.kv, d_in[1], 3, dimq, strq, 56, 16, 2, CU_TENSOR_MAP_SWIZZLE_128B);
    make_map(enc, &mp.q, d_in[1], 3, dimq, strq, 56, 16, 1, CU_TENSOR_MAP_SWIZZLE_128B);
    const cuuint64_t dimf[3] = {32, kD, kF / 32}, strf[2] = {kF * 2, 64};
    const cuuint64_t dimw[3] = {64, kD, kF / 64}, strw[2] = {kF * 2, 128};
    make_map(enc, &mp.g4, d_in[4], 3, dimw, strw, 64, 16, 2, CU_TENSOR_MAP_SWIZZLE_128B);
    make_map(enc, &mp.u4, d_in[5], 3, dimw, strw, 64, 16, 2, CU_TENSOR_MAP_SWIZZLE_128B);
    make_map(enc, &mp.g3, d_in[4], 3, dimf, strf, 32, 16, 3, CU_TENSOR_MAP_SWIZZLE_64B);
    make_map(enc, &mp.u3, d_in[5], 3, dimf, strf, 32, 16, 3, CU_TENSOR_MAP_SWIZZLE_64B);
    fused_kernel<<<NCTA, NTHREADS, SMEM_BYTES>>>(mp, (const __nv_bfloat16*)d_in[7], (__nv_bfloat16*)d_out, 0u);
}
```

```cpp
#include <cuda_runtime.h>
#include <cuda_bf16.h>
#include <cuda.h>
#include <stdint.h>

namespace {

constexpr int kS = 2048, kD = 448, kF = 1792;
constexpr int NTHREADS = 384;
constexpr int NCTA = 128;
constexpr uint32_t OFF_X = 0;
constexpr uint32_t OFF_RING = 114688;
constexpr uint32_t SLOT_BYTES = 16384;
constexpr int NSLOT = 6;
constexpr uint32_t OFF_STG = 212992;
constexpr uint32_t OFF_MISC = 229376;
constexpr uint32_t SMEM_BYTES = 232448;
constexpr uint32_t BAR_FULL = OFF_MISC, BAR_EMPTY = OFF_MISC + 48, BAR_XFULL = OFF_MISC + 96;
constexpr uint32_t BAR_W = OFF_MISC + 152, BAR_KVDONE = OFF_MISC + 160, BAR_AUX = OFF_MISC + 168, BAR_P4 = OFF_MISC + 176;
constexpr uint32_t BAR_REFILL = OFF_MISC + 192;
constexpr uint32_t OFF_W = OFF_MISC + 256;
constexpr uint32_t SB = 1024;

__device__ __align__(128) float g_kvacc[8][2048];
__device__ unsigned int g_counter[10][32];

__device__ __forceinline__ void mbar_init(uint32_t bar, uint32_t cnt) {
    asm volatile("mbarrier.init.shared::cta.b64 [%0], %1;" :: "r"(bar), "r"(cnt) : "memory");
}
__device__ __forceinline__ void mbar_expect_tx(uint32_t bar, uint32_t bytes) {
    asm volatile("mbarrier.arrive.expect_tx.shared::cta.b64 _, [%0], %1;" :: "r"(bar), "r"(bytes) : "memory");
}
__device__ __forceinline__ void mbar_arrive(uint32_t bar) {
    asm volatile("mbarrier.arrive.shared::cta.b64 _, [%0];" :: "r"(bar) : "memory");
}
__device__ __forceinline__ void mbar_arrive_cluster(uint32_t bar) {
    asm volatile("mbarrier.arrive.shared::cluster.b64 _, [%0];" :: "r"(bar) : "memory");
}
__device__ __forceinline__ void mbar_wait(uint32_t bar, uint32_t parity) {
    asm volatile("{\n"
                 ".reg .pred p;\n"
                 ".reg .u32 c;\n"
                 "mov.u32 c, 0;\n"
                 "AGAIN:\n"
                 "mbarrier.try_wait.parity.shared::cta.b64 p, [%0], %1;\n"
                 "@p bra DONE;\n"
                 "add.u32 c, c, 1;\n"
                 "setp.lt.u32 p, c, 4194304;\n"
                 "@p bra AGAIN;\n"
                 "trap;\n"
                 "DONE:\n"
                 "}" :: "r"(bar), "r"(parity) : "memory");
}
__device__ __forceinline__ uint32_t mapa(uint32_t addr, uint32_t cta) {
    uint32_t r; asm("mapa.shared::cluster.u32 %0, %1, %2;" : "=r"(r) : "r"(addr), "r"(cta)); return r;
}
__device__ __forceinline__ bool elect_one() {
    uint32_t p;
    asm volatile("{ .reg .pred P; elect.sync _|P, 0xffffffff; selp.u32 %0, 1, 0, P; }" : "=r"(p));
    return p;
}
__device__ __forceinline__ void tma2d(uint32_t dst, const CUtensorMap* m, int c0, int c1, uint32_t bar) {
    asm volatile("cp.async.bulk.tensor.2d.shared::cluster.global.mbarrier::complete_tx::bytes [%0], [%1, {%3, %4}], [%2];"
                 :: "r"(dst), "l"(m), "r"(bar), "r"(c0), "r"(c1) : "memory");
}
__device__ __forceinline__ void tma2d_mc(uint32_t dst, const CUtensorMap* m, int c0, int c1, uint32_t bar) {
    asm volatile("cp.async.bulk.tensor.2d.shared::cluster.global.mbarrier::complete_tx::bytes.multicast::cluster [%0], [%1, {%3, %4}], [%2], %5;"
                 :: "r"(dst), "l"(m), "r"(bar), "r"(c0), "r"(c1), "h"((uint16_t)3) : "memory");
}
__device__ __forceinline__ void tma3d_mc(uint32_t dst, const CUtensorMap* m, int c0, int c1, int c2, uint32_t bar) {
    asm volatile("cp.async.bulk.tensor.3d.shared::cluster.global.mbarrier::complete_tx::bytes.multicast::cluster [%0], [%1, {%3, %4, %5}], [%2], %6;"
                 :: "r"(dst), "l"(m), "r"(bar), "r"(c0), "r"(c1), "r"(c2), "h"((uint16_t)3) : "memory");
}
__device__ __forceinline__ void tma_reduce2d(const CUtensorMap* m, uint32_t src, int c0, int c1) {
    asm volatile("cp.reduce.async.bulk.tensor.2d.global.shared::cta.add.bulk_group [%0, {%2, %3}], [%1];"
                 :: "l"(m), "r"(src), "r"(c0), "r"(c1) : "memory");
}
__device__ __forceinline__ void bulk_reduce_f32(float* dst, uint32_t src, uint32_t bytes) {
    asm volatile("cp.reduce.async.bulk.global.shared::cta.bulk_group.add.f32 [%0], [%1], %2;" :: "l"(dst), "r"(src), "r"(bytes) : "memory");
}
__device__ __forceinline__ bool mbar_try(uint32_t bar, uint32_t parity) {
    uint32_t ok;
    asm volatile("{ .reg .pred p; mbarrier.test_wait.parity.shared::cta.b64 p, [%1], %2; selp.u32 %0, 1, 0, p; }"
                 : "=r"(ok) : "r"(bar), "r"(parity) : "memory");
    return ok;
}
__device__ __forceinline__ void prefetch_map(const CUtensorMap* m) {
    asm volatile("prefetch.tensormap [%0];" :: "l"(m) : "memory");
}
__device__ __forceinline__ void wg_fence() { asm volatile("wgmma.fence.sync.aligned;" ::: "memory"); }
__device__ __forceinline__ void wg_commit() { asm volatile("wgmma.commit_group.sync.aligned;" ::: "memory"); }
template <int N> __device__ __forceinline__ void wg_wait() { asm volatile("wgmma.wait_group.sync.aligned %0;" :: "n"(N) : "memory"); }
template <int N> __device__ __forceinline__ void reg_fence(float (&d)[N]) {
#pragma unroll
    for (int i = 0; i < N; i++) asm volatile("" : "+f"(d[i]) :: "memory");
}
template <int N> __device__ __forceinline__ void reg_fence(uint32_t (&d)[N]) {
#pragma unroll
    for (int i = 0; i < N; i++) asm volatile("" : "+r"(d[i]) :: "memory");
}
template <int LO, int HI, int N> __device__ __forceinline__ void reg_fence_part(uint32_t (&d)[N]) {
#pragma unroll
    for (int i = LO; i < HI; i++) asm volatile("" : "+r"(d[i]) :: "memory");
}
__device__ __forceinline__ void fence_async_smem() { asm volatile("fence.proxy.async.shared::cta;" ::: "memory"); }
template <int ID, int N> __device__ __forceinline__ void bar_sync() { asm volatile("bar.sync %0, %1;" :: "n"(ID), "n"(N) : "memory"); }
template <int ID, int N> __device__ __forceinline__ void bar_arrive() { asm volatile("bar.arrive %0, %1;" :: "n"(ID), "n"(N) : "memory"); }
__device__ __forceinline__ void ldsm4(uint32_t* r, uint32_t addr) {
    asm volatile("ldmatrix.sync.aligned.m8n8.x4.shared.b16 {%0, %1, %2, %3}, [%4];"
                 : "=r"(r[0]), "=r"(r[1]), "=r"(r[2]), "=r"(r[3]) : "r"(addr) : "memory");
}
__device__ __forceinline__ void stsm4(uint32_t addr, uint32_t r0, uint32_t r1, uint32_t r2, uint32_t r3) {
    asm volatile("stmatrix.sync.aligned.m8n8.x4.shared.b16 [%0], {%1, %2, %3, %4};"
                 :: "r"(addr), "r"(r0), "r"(r1), "r"(r2), "r"(r3) : "memory");
}
__device__ __forceinline__ uint32_t lds32(uint32_t addr) {
    uint32_t r; asm volatile("ld.shared.u32 %0, [%1];" : "=r"(r) : "r"(addr)); return r;
}
__device__ __forceinline__ float4 lds128f(uint32_t addr) {
    float4 r; asm volatile("ld.shared.v4.f32 {%0, %1, %2, %3}, [%4];" : "=f"(r.x), "=f"(r.y), "=f"(r.z), "=f"(r.w) : "r"(addr)); return r;
}
__device__ __forceinline__ uint32_t clock32() { uint32_t t; asm volatile("mov.u32 %0, %%clock;" : "=r"(t)); return t; }
__device__ __forceinline__ uint32_t pack_bf16(float lo, float hi) {
    uint32_t r; asm("cvt.rn.bf16x2.f32 %0, %1, %2;" : "=r"(r) : "f"(hi), "f"(lo)); return r;
}
__device__ __forceinline__ uint32_t pack_relu_bf16(float lo, float hi) {
    uint32_t r; asm("cvt.rn.relu.bf16x2.f32 %0, %1, %2;" : "=r"(r) : "f"(hi), "f"(lo)); return r;
}
__device__ __forceinline__ uint32_t mul_bf16x2(uint32_t a, uint32_t b) {
    uint32_t r; asm("mul.rn.bf16x2 %0, %1, %2;" : "=r"(r) : "r"(a), "r"(b)); return r;
}
__device__ __forceinline__ float phi(float t, float log2e) {
    float e;
    asm("ex2.approx.ftz.f32 %0, %1;" : "=f"(e) : "f"(fminf(t * log2e, 0.f)));
    return e + (fmaxf(t, 0.f) + 1e-6f);
}
__device__ __forceinline__ float after_issue(float v, uint32_t zero) {
    return __uint_as_float(__float_as_uint(v) | (clock32() & zero));
}
constexpr float kLog2e = 1.4426950408889634f;
__device__ __forceinline__ float rcp(float x) { float r; asm("rcp.approx.ftz.f32 %0, %1;" : "=f"(r) : "f"(x)); return r; }
__device__ __forceinline__ float bf_lo(uint32_t v) { return __uint_as_float(v << 16); }
__device__ __forceinline__ float bf_hi(uint32_t v) { return __uint_as_float(v & 0xffff0000u); }
constexpr uint32_t HI128 = (1024 >> 4) | (1u << 30);
constexpr uint32_t HI64 = (512 >> 4) | (2u << 30);
constexpr uint32_t LO128 = 1u << 16, LO64 = (1024u >> 4) << 16, LO128X2 = (2048u >> 4) << 16;
constexpr uint32_t QB = 16 * 112;
constexpr uint32_t TX1 = 2 * (2 * QB + 4096), TX2 = 2 * (QB + 4096), TX3 = 12288;
__device__ __forceinline__ void grid_arrive(unsigned int* c) {
    asm volatile("fence.acq_rel.gpu;" ::: "memory");
    asm volatile("red.relaxed.gpu.global.add.u32 [%0], 1;" :: "l"(c) : "memory");
}
__device__ __forceinline__ void grid_wait(const unsigned int* c, unsigned int target) {
    unsigned int v; int it = 0;
    do {
        asm volatile("ld.relaxed.gpu.global.u32 %0, [%1];" : "=r"(v) : "l"(c) : "memory");
        if (++it > (1 << 22)) asm volatile("trap;");
    } while ((int)(v - target) < 0);
    asm volatile("ld.acquire.gpu.global.u32 %0, [%1];" : "=r"(v) : "l"(c) : "memory");
}


__host__ __device__ constexpr uint32_t p4_pack(int n) { return (n / 3) * 36864 + (n % 3) * 14336; }
__host__ __device__ constexpr uint32_t p4_off(int n) {
    return n < 6 ? OFF_X + p4_pack(n) : n < 14 ? OFF_RING + p4_pack(n - 6) : n == 14 ? OFF_X + p4_pack(6) : OFF_X + p4_pack(n - 15);
}
__host__ __device__ constexpr uint32_t p4_bar(int n) {
    return n < 6 ? BAR_XFULL + 8 * n : n < 12 ? BAR_FULL + 8 * (n - 6) : n < 14 ? BAR_P4 + 8 * (n - 12)
                 : n == 14 ? BAR_XFULL + 48 : BAR_XFULL + 8 * (n - 15);
}
__host__ __device__ constexpr uint32_t p4_par(int n) { return (n < 12 || n == 14) ? 1 : 0; }
constexpr uint32_t OFF_OUT = OFF_X + 5 * 16384;
static_assert(p4_off(7) == p4_off(6) + 14336 && p4_off(13) == p4_off(12) + 14336 && p4_off(16) == p4_off(15) + 14336, "Wd halves");
static_assert(p4_off(13) + 14336 <= OFF_STG + 8192 && p4_off(14) + 8192 == OFF_OUT, "pass-4 layout");

struct Ring {
    uint32_t slot, phase;
    __device__ __forceinline__ void advance() { if (++slot == NSLOT) { slot = 0; phase ^= 1; } }
};

struct Maps { CUtensorMap x, kv, q, g4, g3, u4, u3, d, o, out; };

__global__ void __cluster_dims__(2, 1, 1) __launch_bounds__(NTHREADS, 1)
fused_kernel(const __grid_constant__ Maps mp, const __nv_bfloat16* __restrict__ gate_w, __nv_bfloat16* __restrict__ out,
             uint32_t zero)
{
    extern __shared__ __align__(1024) unsigned char smem[];
    const uint32_t sb = (uint32_t)__cvta_generic_to_shared(smem);
    const int tid = threadIdx.x, warp = tid >> 5, lane = tid & 31;
    const int rank = blockIdx.x & 1, j = (blockIdx.x >> 1) & 7;
    const int row0 = ((blockIdx.x >> 4) * 2 + rank) * 128;
    const int par = j & 1;
    const int g4i = (7 * j + 3 * par) >> 1;

    if (warp == 9) {
        if (elect_one()) {
            prefetch_map(&mp.x);
            mbar_init(sb + BAR_XFULL, 1);
            mbar_expect_tx(sb + BAR_XFULL, 16384);
            tma2d(sb + OFF_X, &mp.x, 0, row0, sb + BAR_XFULL);
            asm volatile("fence.mbarrier_init.release.cluster;" ::: "memory");
        }
        __syncwarp();
    } else if (warp == 8) {
        if (elect_one()) {
            #pragma unroll
            for (int s = 0; s < NSLOT; s++) mbar_init(sb + BAR_FULL + 8 * s, 1);
            asm volatile("fence.mbarrier_init.release.cluster;" ::: "memory");
            mbar_expect_tx(sb + BAR_FULL, TX1);
        }
        __syncwarp();
    } else if (warp == 10) {
        if (elect_one()) {
            #pragma unroll
            for (int s = 1; s < 7; s++) mbar_init(sb + BAR_XFULL + 8 * s, 1);
            mbar_init(sb + BAR_KVDONE, 8);
            mbar_init(sb + BAR_AUX, 3);
            asm volatile("fence.mbarrier_init.release.cluster;" ::: "memory");
            if ((sb & 0xFFFFFF) != SB) asm volatile("trap;");
        }
        __syncwarp();
    } else if (warp == 11) {
        if (elect_one()) {
            #pragma unroll
            for (int s = 0; s < NSLOT; s++) mbar_init(sb + BAR_EMPTY + 8 * s, 4);
            mbar_init(sb + BAR_P4, 1);
            mbar_init(sb + BAR_P4 + 8, 1);
            mbar_init(sb + BAR_REFILL, 4);
            mbar_init(sb + BAR_REFILL + 8, 4);
            asm volatile("fence.mbarrier_init.release.cluster;" ::: "memory");
        }
        __syncwarp();
    } else if (warp == 2) {
        if (elect_one()) {
            mbar_init(sb + BAR_W, 1);
            asm volatile("fence.mbarrier_init.release.cluster;" ::: "memory");
            mbar_expect_tx(sb + BAR_W, 896);
            asm volatile("cp.async.bulk.shared::cluster.global.mbarrier::complete_tx::bytes [%0], [%1], 896, [%2];"
                         :: "r"(sb + OFF_W), "l"(gate_w), "r"(sb + BAR_W) : "memory");
        }
        __syncwarp();
    }
    asm volatile("barrier.cluster.arrive.relaxed.aligned;" ::: "memory");
    if (warp == 8) {
        if (elect_one()) { prefetch_map(&mp.kv); prefetch_map(&mp.g4); }
        __syncwarp();
    }
    asm volatile("barrier.cluster.wait.aligned;" ::: "memory");
    if (warp == 8) {
        if (elect_one()) {
            tma3d_mc(sb + OFF_RING + rank * 8192 + 4096, &mp.kv, 56 * j, 16 * rank, 1, sb + BAR_FULL);
            tma3d_mc(sb + OFF_RING + rank * 8192, &mp.g4, 0, 16 * rank, g4i, sb + BAR_FULL);
        }
        __syncwarp();
    }

    if (warp >= 8) {
        asm volatile("setmaxnreg.dec.sync.aligned.u32 40;");
        if (warp == 8) {
            if (elect_one()) {
                Ring r{1, 1};
                auto acquire = [&](uint32_t bytes) -> uint32_t {
                    mbar_wait(sb + BAR_EMPTY + 8 * r.slot, r.phase);
                    mbar_expect_tx(sb + BAR_FULL + 8 * r.slot, bytes);
                    return sb + OFF_RING + r.slot * SLOT_BYTES;
                };
                #pragma unroll 1
                for (int s = 1; s < 14; s++) {
                    const uint32_t dst = acquire(TX1) + rank * 8192;
                    tma3d_mc(dst + 4096, &mp.kv, 56 * j, 32 * s + 16 * rank, 1, sb + BAR_FULL + 8 * r.slot);
                    tma3d_mc(dst, &mp.g4, 0, 32 * s + 16 * rank, g4i, sb + BAR_FULL + 8 * r.slot);
                    r.advance();
                    if ((s & 1) && s < 12) {
                        const int n = (s >> 1) + 1;
                        mbar_expect_tx(sb + BAR_XFULL + 8 * n, 16384);
                        tma2d(sb + OFF_X + n * 16384, &mp.x, 64 * n, row0, sb + BAR_XFULL + 8 * n);
                    }
                    if (s == 5) {
                        prefetch_map(&mp.q); prefetch_map(&mp.u4); prefetch_map(&mp.g3); prefetch_map(&mp.u3);
                        prefetch_map(&mp.d); prefetch_map(&mp.o); prefetch_map(&mp.out);
                    }
                }
                #pragma unroll 1
                for (int s = 0; s < 14; s++) {
                    const uint32_t dst = acquire(TX2) + rank * 6144;
                    tma3d_mc(dst, &mp.q, 56 * j, 32 * s + 16 * rank, 0, sb + BAR_FULL + 8 * r.slot);
                    tma3d_mc(dst + 2048, &mp.u4, 0, 32 * s + 16 * rank, g4i, sb + BAR_FULL + 8 * r.slot);
                    r.advance();
                }
                const int cfirst = j == 7 ? 0 : j;
                auto load4 = [&](int n) {
                    int c = cfirst + n / 3;
                    if (c >= 7) c -= 7;
                    mbar_expect_tx(sb + p4_bar(n), n % 3 == 2 ? 8192 : 14336);
                    if (n % 3 == 2) tma2d_mc(sb + p4_off(n) + rank * 4096, &mp.o, 64 * c, 56 * j + 32 * rank, sb + p4_bar(n));
                    else tma2d_mc(sb + p4_off(n) + rank * 7168, &mp.d, 64 * c, 224 * j + 112 * (n % 3) + 56 * rank, sb + p4_bar(n));
                };
                #pragma unroll 1
                for (int s = 0; s < 14; s++) {
                    const uint32_t dst = acquire(TX3) + rank * 6144;
                    tma3d_mc(dst, &mp.g3, 0, 32 * s + 16 * rank, 7 * j + 4 - 4 * par, sb + BAR_FULL + 8 * r.slot);
                    tma3d_mc(dst + 3072, &mp.u3, 0, 32 * s + 16 * rank, 7 * j + 4 - 4 * par, sb + BAR_FULL + 8 * r.slot);
                    r.advance();
                    if (s == 7) load4(0);
                    if (s == 9) load4(1);
                    if (s == 11) load4(2);
                    if (s == 13) { load4(3); load4(4); }
                }
                mbar_wait(sb + BAR_EMPTY, 0);      load4(6);
                mbar_wait(sb + BAR_EMPTY + 8, 0);  load4(5); load4(7); load4(14);
                mbar_wait(sb + BAR_EMPTY + 16, 0); load4(8);
                mbar_wait(sb + BAR_EMPTY + 24, 0); load4(9); load4(10);
                mbar_wait(sb + BAR_EMPTY + 32, 0); load4(11);
                mbar_wait(sb + BAR_EMPTY + 40, 0); load4(12);
                mbar_wait(sb + BAR_AUX, 0);        load4(13);
                mbar_wait(sb + BAR_REFILL, 0);     load4(15); load4(16); load4(17);
                mbar_wait(sb + BAR_REFILL + 8, 0); load4(18); load4(19); load4(20);
            }
        } else {
            const int ht = tid - 288;
            unsigned int* kvc = &g_counter[2 + j][0];
            unsigned int cnt0;
            asm volatile("ld.relaxed.gpu.global.u32 %0, [%1];" : "=r"(cnt0) : "l"(kvc) : "memory");
            const unsigned int epoch = (cnt0 >> 4) + 1;
            if (warp == 9) {
                reinterpret_cast<float4*>(&g_kvacc[0][0])[blockIdx.x * 32 + lane] = make_float4(0.f, 0.f, 0.f, 0.f);
                asm volatile("fence.proxy.async.global;" ::: "memory");
                __syncwarp();
                if (lane == 0) {
                    grid_arrive(&g_counter[0][0]);
                    grid_wait(&g_counter[0][0], epoch << 7);
                }
                __syncwarp();
            } else if (warp == 10) {
                mbar_wait(sb + BAR_XFULL + 8 * 6, 0);
                uint4* o = reinterpret_cast<uint4*>(out) + blockIdx.x * 896 + lane;
                #pragma unroll 4
                for (int q = 0; q < 28; q++) o[q * 32] = make_uint4(0, 0, 0, 0);
                asm volatile("fence.proxy.async.global;" ::: "memory");
                __syncwarp();
                if (lane == 0) grid_arrive(&g_counter[1][0]);
                __syncwarp();
            }
            mbar_wait(sb + BAR_KVDONE, 0);
            {
                #pragma unroll
                for (int i0 = 0; i0 < 5; i0 += 2) {
                    float4 pa[2], pb[2];
                    #pragma unroll
                    for (int i = 0; i < 2 && i0 + i < 5; i++) {
                        const int q = min(ht + 96 * (i0 + i), 447);
                        pa[i] = lds128f(sb + OFF_STG + q * 16); pb[i] = lds128f(sb + OFF_STG + 8192 + q * 16);
                    }
                    #pragma unroll
                    for (int i = 0; i < 2 && i0 + i < 5; i++) {
                        const int q = ht + 96 * (i0 + i);
                        if (q < 448) asm volatile("st.shared.v4.f32 [%0], {%1, %2, %3, %4};" :: "r"(sb + OFF_STG + q * 16),
                            "f"(pa[i].x + pb[i].x), "f"(pa[i].y + pb[i].y), "f"(pa[i].z + pb[i].z), "f"(pa[i].w + pb[i].w) : "memory");
                    }
                }
                fence_async_smem();
            }
            bar_sync<3, 96>();
            if (warp == 9) {
                if (elect_one()) {
                    bulk_reduce_f32(&g_kvacc[j][0], sb + OFF_STG, 7168);
                    asm volatile("cp.async.bulk.commit_group;" ::: "memory");
                    asm volatile("cp.async.bulk.wait_group 0;" ::: "memory");
                    asm volatile("red.relaxed.gpu.global.add.u32 [%0], 1;" :: "l"(kvc) : "memory");
                }
            } else if (warp == 10) {
                if (lane == 0) grid_wait(&g_counter[1][0], epoch << 7);
            }
            __syncwarp();
            #pragma unroll
            for (int i = 0; i < 3; i++) {
                const int q = ht + 96 * i;
                const int d = q < 168 ? q / 3 : 56 + ((q - 168) >> 3);
                const int c = q < 168 ? (q - 3 * d + (d < 28 ? 4 : 0)) : (q & 7);
                if (q < 232) asm volatile("st.shared.v4.u32 [%0], {%1, %1, %1, %1};" :: "r"(sb + OFF_STG + 8192 + d * 128 + ((c ^ (d & 7)) << 4)), "r"(0) : "memory");
            }
            uint32_t plan[3];
            #pragma unroll
            for (int i = 0; i < 3; i++) {
                const int q = min(ht + 96 * i, 279), d = q / 5, m = q - 5 * d;
                const bool h0 = d < 28;
                const int c = m == 4 ? 7 : (h0 ? m : m + 3), pc = m < 4 ? m : (h0 ? 3 : 0);
                const int kind = m == 4 ? (h0 ? 3 : 4) : c == 3 ? (h0 ? 1 : 2) : 0;
                plan[i] = (d * 128 + ((c ^ (d & 7)) << 4)) | ((d * 4 + (pc ^ (d & 3))) << 13) | (kind << 23);
                asm volatile("" : "+r"(plan[i]));
            }
            if (lane == 0) grid_wait(kvc, epoch << 4);
            __syncwarp();
            const float4* src = reinterpret_cast<const float4*>(&g_kvacc[j][0]);
            float4 va[3], vb[3];
            #pragma unroll
            for (int i = 0; i < 3; i++) {
                const float4* p = src + ((plan[i] >> 12) & 0x7fe);
                va[i] = __ldcg(p); vb[i] = __ldcg(p + 1);
            }
            #pragma unroll
            for (int i = 0; i < 3; i++) {
                const uint32_t kind = plan[i] >> 23;
                uint32_t w0 = pack_bf16(va[i].x, va[i].y), w1 = pack_bf16(va[i].z, va[i].w);
                uint32_t w2 = pack_bf16(vb[i].x, vb[i].y), w3 = pack_bf16(vb[i].z, vb[i].w);
                if (kind == 3) w0 = w2 & 0xffffu;
                if (kind == 4) w0 <<= 16;
                if (kind == 2) w0 = 0u;
                if (kind >= 2) w1 = 0u;
                if (kind != 0 && kind != 2) w2 = w3 = 0u;
                if (i < 2 || ht < 88)
                    asm volatile("st.shared.v4.u32 [%0], {%1, %2, %3, %4};"
                                 :: "r"(sb + OFF_STG + 8192 + (plan[i] & 0x1fff)), "r"(w0), "r"(w1), "r"(w2), "r"(w3) : "memory");
            }
            fence_async_smem();
            __syncwarp();
            if (lane == 0) mbar_arrive(sb + BAR_AUX);
        }
    } else {
        asm volatile("setmaxnreg.inc.sync.aligned.u32 232;");
        const int wg = warp >> 2, w4 = warp & 3;
        const int q4 = lane & 3, g8 = lane >> 2;
        const uint32_t lx = ((lane >> 4) ^ (lane & 7)) << 4;
        const uint32_t xa = sb + OFF_X + (warp * 16 + (lane & 15)) * 128;
        const uint32_t empty_dst = mapa(sb + BAR_EMPTY, w4 & 1);
        const bool signaller = lane == 0 && w4 < 2;
        constexpr uint32_t dsb = SB >> 4;
        Ring r{0, 0};
        uint32_t cur = 0, old = 0;
        bool ready = false;
        auto release = [&](uint32_t slot) { if (signaller) mbar_arrive_cluster(empty_dst + 8 * slot); };
        auto turn_wait = [&]() { if (wg == 0) bar_sync<6, 256>(); else bar_sync<7, 256>(); };
        auto turn_pass = [&]() { if (wg == 0) bar_arrive<7, 256>(); else bar_arrive<6, 256>(); };
        auto begin = [&]() -> uint32_t {
            if (!ready) mbar_wait(sb + BAR_FULL + 8 * r.slot, r.phase);
            wg_fence();
            return dsb + (OFF_RING >> 4) + r.slot * (SLOT_BYTES >> 4);
        };
        auto commit = [&]() { wg_commit(); old = cur; cur = r.slot; r.advance(); };
        auto retire = [&]() { wg_wait<1>(); release(old); };
        auto peek = [&]() { ready = mbar_try(sb + BAR_FULL + 8 * r.slot, r.phase); };
        uint32_t a0[8], a1[8];
        auto load_a0 = [&](int kc) { ldsm4(a0, xa + kc * 16384 + lx); ldsm4(a0 + 4, xa + kc * 16384 + (lx ^ 32)); };
        auto load_a1 = [&](int kc) { ldsm4(a1, xa + kc * 16384 + (lx ^ 64)); ldsm4(a1 + 4, xa + kc * 16384 + (lx ^ 96)); };

        uint32_t hp[56];
        float g0, g1, av[28], agk[92];
        {
            float d0 = 0.f, d1 = 0.f, d2 = 0.f, d3 = 0.f;
            uint32_t w0[4], w1[4];
            auto issue1 = [&](uint32_t (&a)[8], int sd) {
                const uint32_t b = begin();
                wgmma_rs184<HI128>(agk, a[0], a[1], a[2], a[3], b + LO128X2, sd);
                wgmma_rs56<HI128>(av, a[0], a[1], a[2], a[3], b + LO128 + 384, sd);
                wgmma_rs184<HI128>(agk, a[4], a[5], a[6], a[7], b + LO128X2 + 512, 1);
                wgmma_rs56<HI128>(av, a[4], a[5], a[6], a[7], b + LO128 + 896, 1);
                commit();
            };
            auto issue1s = [&](uint32_t (&a)[8]) {
                const uint32_t b = begin();
                wgmma_rs184<HI128>(agk, a[0], a[1], a[2], a[3], b + LO128X2, 1);
                wgmma_rs184<HI128>(agk, a[4], a[5], a[6], a[7], b + LO128X2 + 512, 1);
                wg_commit();
                wgmma_rs56<HI128>(av, a[0], a[1], a[2], a[3], b + LO128 + 384, 1);
                wgmma_rs56<HI128>(av, a[4], a[5], a[6], a[7], b + LO128 + 896, 1);
                commit();
            };
            auto load_w = [&](uint32_t (&w)[4], int s) {
                #pragma unroll
                for (int e = 0; e < 4; e++) w[e] = lds32(sb + OFF_W + s * 64 + q4 * 4 + e * 16);
            };
            auto dot = [&](uint32_t (&a)[8], uint32_t (&w)[4]) {
                #pragma unroll
                for (int e = 0; e < 4; e++) {
                    const uint32_t p0 = mul_bf16x2(a[2 * e], w[e]), p1 = mul_bf16x2(a[2 * e + 1], w[e]);
                    d0 += bf_lo(p0); d2 += bf_hi(p0); d1 += bf_lo(p1); d3 += bf_hi(p1);
                }
                asm volatile("" : "+f"(d0), "+f"(d1), "+f"(d2), "+f"(d3));
            };
            mbar_wait(sb + BAR_XFULL, 0);
            load_a0(0);
            mbar_wait(sb + BAR_W, 0);
            load_w(w0, 0);
            auto odd_stage = [&](int it, bool first, bool last) {
                wg_wait<1>();
                if (!first) release(old);
                load_a1(it);
                load_w(w1, 2 * it + 1);
                peek();
                dot(a0, w0);
                if (last && wg == 1) bar_sync<4, 256>();
                issue1s(a1);
                if (last && wg == 0) bar_arrive<4, 256>();
            };
            issue1(a0, 0);
            #pragma unroll
            for (int it = 0; it < 6; it++) {
                const bool xok = mbar_try(sb + BAR_XFULL + 8 * (it + 1), 0);
                odd_stage(it, it == 0, false);
                wg_wait<2>(); release(old);
                if (!xok) mbar_wait(sb + BAR_XFULL + 8 * (it + 1), 0);
                load_a0(it + 1);
                load_w(w0, 2 * it + 2);
                peek();
                dot(a1, w1);
                issue1(a0, 1);
            }
            odd_stage(6, false, true);
            wg_wait<2>(); release(old);
            load_a0(0);
            peek();
            dot(a1, w1);
            wg_wait<1>();
            reg_fence(agk);
            #pragma unroll
            for (int i = 0; i < 32; i++) hp[i] = pack_relu_bf16(agk[2 * i], agk[2 * i + 1]);
            reg_fence_part<0, 32>(hp);
            g0 = d0 + d2; g1 = d1 + d3;
        }

        float aq[28], au[64];
        {
            auto issue2 = [&](uint32_t (&a)[8], int sd) {
                const uint32_t b = begin();
                wgmma_rs56<HI128>(aq, a[0], a[1], a[2], a[3], b + LO128, sd);
                wgmma_rs128<HI128>(au, a[0], a[1], a[2], a[3], b + LO128X2 + 128, sd);
                wgmma_rs56<HI128>(aq, a[4], a[5], a[6], a[7], b + LO128 + 384, 1);
                wgmma_rs128<HI128>(au, a[4], a[5], a[6], a[7], b + LO128X2 + 512, 1);
            };
            const uint32_t st_base = wg == 0 ? OFF_STG : OFF_RING + 12288, st_step = wg == 0 ? 2048 : SLOT_BYTES, st_v = wg == 0 ? 8192 : 2048;
            const uint32_t sk = sb + st_base + w4 * st_step + (lane & 15) * 128;
            float tok = kLog2e;
            uint32_t pk[16];
            pk[14] = 0u; pk[15] = 0u;
            auto stage_k = [&](int lo, int hi) {
                #pragma unroll
                for (int i = 0; i < 14; i++) if (i >= lo && i < hi) pk[i] = pack_bf16(phi(agk[64 + 2 * i], tok), phi(agk[65 + 2 * i], tok));
                #pragma unroll
                for (int t = 0; t < 4; t++) {
                    const int need = t < 3 ? 4 * t + 4 : 14;
                    if (need > lo && need <= hi) stsm4(sk + (lx ^ (t * 32)), pk[4 * t], pk[4 * t + 1], pk[4 * t + 2], pk[4 * t + 3]);
                }
                #pragma unroll
                for (int i = 0; i < 14; i++) if (i >= lo && i < hi) asm volatile("" : "+r"(pk[i]));
            };
            issue2(a0, 0); commit();
            tok = after_issue(kLog2e, zero);
            retire();
            reg_fence(av);
            if (wg == 0) bar_arrive<8, 256>();
            load_a1(0); peek();
            uint32_t pv[14];
            #pragma unroll
            for (int i = 0; i < 14; i++) pv[i] = pack_bf16(av[2 * i], av[2 * i + 1]);
            if (wg == 1) bar_sync<8, 256>();
            {
                const uint32_t ones = q4 == 0 ? 0x3f803f80u : 0u;
                #pragma unroll
                for (int t = 0; t < 3; t++) stsm4(sk + st_v + (lx ^ (t * 32)), pv[4 * t], pv[4 * t + 1], pv[4 * t + 2], pv[4 * t + 3]);
                stsm4(sk + st_v + (lx ^ 96), pv[12], pv[13], ones, ones);
            }
            stage_k(0, 2);
            issue2(a1, 1); commit();
            tok = after_issue(kLog2e, zero);
            retire(); load_a0(1); peek();
            stage_k(2, 5);
            issue2(a0, 1); commit();
            tok = after_issue(kLog2e, zero);
            retire(); load_a1(1); peek();
            stage_k(5, 8);
            issue2(a1, 1); commit();
            tok = after_issue(kLog2e, zero);
            retire(); load_a0(2); peek();
            stage_k(8, 11);
            issue2(a0, 1); commit();
            tok = after_issue(kLog2e, zero);
            retire(); load_a1(2); peek();
            stage_k(11, 14);
            issue2(a1, 1); commit();
            retire(); load_a0(3); peek();
            fence_async_smem();
            if (wg == 0) bar_sync<1, 128>(); else bar_sync<2, 128>();
            float kv[32];
            issue2(a0, 1);
            {
                const uint32_t dk = dsb + LO128 + (st_base >> 4), ds = st_step >> 4, dv = st_v >> 4;
                #pragma unroll
                for (int ks = 0; ks < 4; ks++) wgmma_ss64_tt<HI128>(kv, dk + ks * ds, dk + ks * ds + dv, ks);
            }
            commit();
            tok = after_issue(-kLog2e, zero);
            retire(); load_a1(3); peek();
            {
                g0 += __shfl_xor_sync(0xffffffffu, g0, 1); g1 += __shfl_xor_sync(0xffffffffu, g1, 1);
                g0 += __shfl_xor_sync(0xffffffffu, g0, 2); g1 += __shfl_xor_sync(0xffffffffu, g1, 2);
                const uint32_t lg = pack_bf16(g0, g1);
                float e0, e1;
                asm("ex2.approx.ftz.f32 %0, %1;" : "=f"(e0) : "f"(bf_lo(lg) * tok));
                asm("ex2.approx.ftz.f32 %0, %1;" : "=f"(e1) : "f"(bf_hi(lg) * tok));
                const uint32_t gg = pack_bf16(rcp(1.f + e0), rcp(1.f + e1));
                g0 = bf_lo(gg); g1 = bf_hi(gg);
                asm volatile("" : "+f"(g0), "+f"(g1));
            }
            issue2(a1, 1); commit();
            retire(); load_a0(4); peek();
            reg_fence(kv);
            if (wg == 0) { bar_arrive<5, 256>(); bar_sync<1, 128>(); } else bar_sync<5, 256>();
            auto stage_kv = [&](int hh) {
                const int d = w4 * 16 + g8 + 8 * hh;
                const bool h0 = d < 28;
                const uint32_t rowa = sb + OFF_STG + wg * 8192 + d * 128 + q4 * 8;
                #pragma unroll
                for (int t = 0; t < 4; t++) {
                    float v0 = h0 ? kv[4 * t + 2 * hh] : kv[4 * t + 12 + 2 * hh];
                    float v1 = h0 ? kv[4 * t + 2 * hh + 1] : kv[4 * t + 13 + 2 * hh];
                    if (t == 0 && !h0 && q4 == 0) v0 = kv[28 + 2 * hh];
                    if (d < 56 && !(t == 3 && h0 && q4 == 2))
                        asm volatile("st.shared.v2.f32 [%0], {%1, %2};" :: "r"(rowa + ((t ^ (g8 & 3)) << 5)), "f"(v0), "f"(v1) : "memory");
                }
                if (h0 && q4 == 0)
                    asm volatile("st.shared.v2.f32 [%0], {%1, %1};" :: "r"(rowa + ((3 ^ (g8 & 3)) << 5) + 16), "f"(kv[28 + 2 * hh]) : "memory");
            };
            stage_kv(0);
            issue2(a0, 1); commit();
            retire(); load_a1(4); peek();
            stage_kv(1);
            __syncwarp();
            if (lane == 0) mbar_arrive(sb + BAR_KVDONE);
            issue2(a1, 1); commit();
            retire(); load_a0(5); peek();
            auto prescale = [&](int lo, int hi) {
                const float t0 = after_issue(1.f - g0, zero), t1 = after_issue(1.f - g1, zero);
                const uint32_t s0 = pack_bf16(t0, t0), s1 = pack_bf16(t1, t1);
                #pragma unroll
                for (int i = 0; i < 32; i++) if (i >= lo && i < hi) { hp[i] = mul_bf16x2(hp[i], (i & 1) ? s1 : s0); asm volatile("" : "+r"(hp[i])); }
            };
            prescale(0, 16);
            issue2(a0, 1); commit();
            retire(); load_a1(5); peek();
            prescale(16, 32);
            issue2(a1, 1); commit();
            retire(); load_a0(6); peek();
            issue2(a0, 1); commit();
            retire(); load_a1(6); peek();
            if (wg == 1) bar_sync<4, 256>();
            const uint32_t b = begin();
            wgmma_rs128<HI128>(au, a1[0], a1[1], a1[2], a1[3], b + LO128X2 + 128, 1);
            wgmma_rs128<HI128>(au, a1[4], a1[5], a1[6], a1[7], b + LO128X2 + 512, 1);
            wg_commit();
            wgmma_rs56<HI128>(aq, a1[0], a1[1], a1[2], a1[3], b + LO128, 1);
            wgmma_rs56<HI128>(aq, a1[4], a1[5], a1[6], a1[7], b + LO128 + 384, 1);
            commit();
            if (wg == 0) bar_arrive<4, 256>();
            wg_wait<2>(); release(old);
            load_a0(0); peek();
            wg_wait<1>();
            reg_fence(au);
        }
        #pragma unroll
        for (int i = 0; i < 32; i++) hp[i] = mul_bf16x2(hp[i], pack_bf16(au[2 * i], au[2 * i + 1]));
        reg_fence_part<0, 32>(hp);

        float ag[96];
        uint32_t op[16];
        {
            auto issue3 = [&](uint32_t (&a)[8], int sd) {
                const uint32_t b = begin();
                wgmma_rs192<HI64>(ag, a[0], a[1], a[2], a[3], b + LO64, sd);
                wgmma_rs192<HI64>(ag, a[4], a[5], a[6], a[7], b + LO64 + 384, 1);
            };
            uint32_t pq[16];
            issue3(a0, 0); commit();
            retire();
            reg_fence(aq);
            load_a1(0); peek();
            pq[14] = 0u; pq[15] = 0u;
            bool aux = false;
            #pragma unroll
            for (int st = 1; st < 12; st++) {
                if (st & 1) issue3(a1, 1); else issue3(a0, 1);
                commit();
                const float tok = st < 8 ? after_issue(kLog2e, zero) : 0.f;
                if (st == 11) aux = mbar_try(sb + BAR_AUX, 0);
                retire();
                if (st & 1) load_a0((st + 1) >> 1); else load_a1(st >> 1);
                peek();
                if (st < 8) {
                    const int i = 2 * st - 2;
                    pq[i] = pack_bf16(phi(aq[2 * i], tok), phi(aq[2 * i + 1], tok));
                    pq[i + 1] = pack_bf16(phi(aq[2 * i + 2], tok), phi(aq[2 * i + 3], tok));
                    asm volatile("" : "+r"(pq[i]), "+r"(pq[i + 1]));
                }
            }
            if (!aux) mbar_wait(sb + BAR_AUX, 0);
            if (wg == 1) bar_sync<4, 256>();
            float nd[32];
            issue3(a0, 1);
            {
                const uint32_t dk = dsb + LO128 + ((OFF_STG + 8192) >> 4);
                #pragma unroll
                for (int ks = 0; ks < 4; ks++) wgmma_rs64<HI128>(nd, pq[4 * ks], pq[4 * ks + 1], pq[4 * ks + 2], pq[4 * ks + 3], dk + ks * 128, ks);
            }
            commit();
            retire(); load_a1(6); peek();
            issue3(a1, 1); commit();
            if (wg == 0) bar_arrive<4, 256>();
            ready = mbar_try(sb + p4_bar(0), p4_par(0));
            retire();
            reg_fence(nd);
            const int src = lane & ~3;
            const float s00 = g0 * rcp(__shfl_sync(0xffffffffu, nd[28], src) + 1e-6f);
            const float s01 = g0 * rcp(__shfl_sync(0xffffffffu, nd[29], src) + 1e-6f);
            const float s10 = g1 * rcp(__shfl_sync(0xffffffffu, nd[30], src) + 1e-6f);
            const float s11 = g1 * rcp(__shfl_sync(0xffffffffu, nd[31], src) + 1e-6f);
            #pragma unroll
            for (int t = 0; t < 7; t++) {
                const bool h1 = t > 3 || (t == 3 && q4 >= 2);
                const float sa = h1 ? s01 : s00, sc = h1 ? s11 : s10;
                op[2 * t] = pack_bf16(nd[4 * t] * sa, nd[4 * t + 1] * sa);
                op[2 * t + 1] = pack_bf16(nd[4 * t + 2] * sc, nd[4 * t + 3] * sc);
            }
            op[14] = 0u; op[15] = 0u;
            reg_fence(op);
        }

        float oa[32], ob[32];
        int c = j == 7 ? 0 : j;
        const int wsh = __shfl_sync(0xffffffffu, warp * 16, 0);
        const uint32_t sh0 = par * 768, sh1 = par * 1024;
        bool ready2 = false;
        auto issue_d = [&](float (&o)[32], int c0, int half) {
            const int n = 3 * c0;
            if (half == 0) {
                if (!ready) mbar_wait(sb + p4_bar(n), p4_par(n));
                if (!ready2) mbar_wait(sb + p4_bar(n + 1), p4_par(n + 1));
                ready = mbar_try(sb + p4_bar(n + 2), p4_par(n + 2));
            }
            wg_fence();
            const uint32_t b = dsb + LO128 + (p4_off(n) >> 4);
            #pragma unroll
            for (int ks = 7 * half; ks < 7 * half + 7; ks++)
                wgmma_rs64<HI128>(o, hp[4 * ks], hp[4 * ks + 1], hp[4 * ks + 2], hp[4 * ks + 3],
                                  b + ks * 128 + (ks < 8 ? sh0 : 0u - sh1), ks);
        };
        auto issue_o = [&](float (&o)[32], int c0) {
            const int n = 3 * c0 + 2;
            if (!ready) mbar_wait(sb + p4_bar(n), p4_par(n));
            if (c0 < 6) {
                ready = mbar_try(sb + p4_bar(n + 1), p4_par(n + 1));
                ready2 = mbar_try(sb + p4_bar(n + 2), p4_par(n + 2));
            }
            wg_fence();
            const uint32_t b = dsb + LO128 + (p4_off(n) >> 4);
            #pragma unroll
            for (int ks = 0; ks < 4; ks++) wgmma_rs64<HI128>(o, op[4 * ks], op[4 * ks + 1], op[4 * ks + 2], op[4 * ks + 3], b + ks * 128, 1);
            wg_commit();
        };
        auto ship = [&](float (&o)[32], int c0) {
            reg_fence(o);
            const uint32_t so = xa + OFF_OUT + (c0 & 1) * 16384;
            #pragma unroll
            for (int t = 0; t < 4; t++)
                stsm4(so + (lx ^ (t * 32)), pack_bf16(o[8 * t], o[8 * t + 1]), pack_bf16(o[8 * t + 2], o[8 * t + 3]),
                      pack_bf16(o[8 * t + 4], o[8 * t + 5]), pack_bf16(o[8 * t + 6], o[8 * t + 7]));
            fence_async_smem();
            __syncwarp();
            if (elect_one()) {
                tma_reduce2d(&mp.out, sb + OFF_OUT + (c0 & 1) * 16384 + wsh * 128, 64 * c, row0 + wsh);
                asm volatile("cp.async.bulk.commit_group;" ::: "memory");
            }
            if (++c == 7) c = 0;
        };
        auto finish_h = [&]() {
            reg_fence(ag);
            release(cur);
            const uint32_t s0 = pack_bf16(1.f - g0, 1.f - g0), s1 = pack_bf16(1.f - g1, 1.f - g1);
            #pragma unroll
            for (int i = 0; i < 24; i++)
                hp[32 + i] = mul_bf16x2(mul_bf16x2(pack_relu_bf16(ag[2 * i], ag[2 * i + 1]), (i & 1) ? s1 : s0),
                                        pack_bf16(ag[48 + 2 * i], ag[49 + 2 * i]));
            reg_fence_part<32, 56>(hp);
        };
        ready2 = mbar_try(sb + p4_bar(1), p4_par(1));
        wg_wait<0>();
        finish_h();
        #pragma unroll
        for (int c0 = 0; c0 < 7; c0++) {
            float (&o)[32] = (c0 & 1) ? ob : oa;
            if (c0 > 0 || wg == 1) turn_wait();
            issue_d(o, c0, 0);
            issue_d(o, c0, 1);
            issue_o(o, c0);
            if (!(c0 == 6 && wg == 1)) turn_pass();
            if (c0 >= 2) {
                if (elect_one()) asm volatile("cp.async.bulk.wait_group.read 1;" ::: "memory");
                __syncwarp();
            }
            wg_wait<0>();
            if (c0 < 2 && signaller) mbar_arrive_cluster(empty_dst + (BAR_REFILL - BAR_EMPTY) + 8 * c0);
            ship(o, c0);
        }
        if (elect_one()) asm volatile("cp.async.bulk.wait_group.read 0;" ::: "memory");
    }
}

typedef CUresult (*EncodeFn)(CUtensorMap*, CUtensorMapDataType, cuuint32_t, void*, const cuuint64_t*, const cuuint64_t*,
                             const cuuint32_t*, const cuuint32_t*, CUtensorMapInterleave, CUtensorMapSwizzle,
                             CUtensorMapL2promotion, CUtensorMapFloatOOBfill);

void make_map(EncodeFn enc, CUtensorMap* m, const void* base, int rank, const cuuint64_t* dims, const cuuint64_t* strides,
              cuuint32_t b0, cuuint32_t b1, cuuint32_t b2, CUtensorMapSwizzle sw) {
    const cuuint32_t es[3] = {1, 1, 1}, box[3] = {b0, b1, b2};
    enc(m, CU_TENSOR_MAP_DATA_TYPE_BFLOAT16, rank, const_cast<void*>(base), dims, strides, box, es,
        CU_TENSOR_MAP_INTERLEAVE_NONE, sw, CU_TENSOR_MAP_L2_PROMOTION_L2_128B, CU_TENSOR_MAP_FLOAT_OOB_FILL_NONE);
}

}

extern "C" void kernel_launch(void* const* d_in, const int* in_sizes, int n_in, void* d_out, int out_size) {
    (void)in_sizes; (void)n_in; (void)out_size;
    static EncodeFn enc = nullptr;
    if (!enc) {
        void* fn = nullptr;
        cudaDriverEntryPointQueryResult st;
        cudaGetDriverEntryPoint("cuTensorMapEncodeTiled", &fn, cudaEnableDefault, &st);
        enc = (EncodeFn)fn;
        cudaFuncSetAttribute(fused_kernel, cudaFuncAttributeMaxDynamicSharedMemorySize, SMEM_BYTES);
    }
    Maps mp;
    const cuuint64_t dimx[2] = {kD, kS}, dimd[2] = {kD, kF}, dimo[2] = {kD, kD}, strd[1] = {kD * 2};
    make_map(enc, &mp.x, d_in[0], 2, dimx, strd, 64, 128, 1, CU_TENSOR_MAP_SWIZZLE_128B);
    make_map(enc, &mp.out, d_out, 2, dimx, strd, 64, 16, 1, CU_TENSOR_MAP_SWIZZLE_128B);
    make_map(enc, &mp.d, d_in[6], 2, dimd, strd, 64, 56, 1, CU_TENSOR_MAP_SWIZZLE_128B);
    make_map(enc, &mp.o, d_in[2], 2, dimo, strd, 64, 32, 1, CU_TENSOR_MAP_SWIZZLE_128B);
    const cuuint64_t dimq[3] = {kD, kD, 3}, strq[2] = {3 * kD * 2, kD * 2};
    make_map(enc, &mp.kv, d_in[1], 3, dimq, strq, 56, 16, 2, CU_TENSOR_MAP_SWIZZLE_128B);
    make_map(enc, &mp.q, d_in[1], 3, dimq, strq, 56, 16, 1, CU_TENSOR_MAP_SWIZZLE_128B);
    const cuuint64_t dimf[3] = {32, kD, kF / 32}, strf[2] = {kF * 2, 64};
    const cuuint64_t dimw[3] = {64, kD, kF / 64}, strw[2] = {kF * 2, 128};
    make_map(enc, &mp.g4, d_in[4], 3, dimw, strw, 64, 16, 2, CU_TENSOR_MAP_SWIZZLE_128B);
    make_map(enc, &mp.u4, d_in[5], 3, dimw, strw, 64, 16, 2, CU_TENSOR_MAP_SWIZZLE_128B);
    make_map(enc, &mp.g3, d_in[4], 3, dimf, strf, 32, 16, 3, CU_TENSOR_MAP_SWIZZLE_64B);
    make_map(enc, &mp.u3, d_in[5], 3, dimf, strf, 32, 16, 3, CU_TENSOR_MAP_SWIZZLE_64B);
    fused_kernel<<<NCTA, NTHREADS, SMEM_BYTES>>>(mp, (const __nv_bfloat16*)d_in[7], (__nv_bfloat16*)d_out, 0u);
}
```

```cpp
#include <cuda_runtime.h>
#include <cuda_bf16.h>
#include <cuda.h>
#include <stdint.h>

namespace {

constexpr int kS = 2048, kD = 448, kF = 1792;
constexpr int NTHREADS = 384;
constexpr int NCTA = 128;
constexpr uint32_t OFF_X = 0;
constexpr uint32_t OFF_RING = 114688;
constexpr uint32_t SLOT_BYTES = 16384;
constexpr int NSLOT = 6;
constexpr uint32_t OFF_STG = 212992;
constexpr uint32_t OFF_MISC = 229376;
constexpr uint32_t SMEM_BYTES = 232448;
constexpr uint32_t BAR_FULL = OFF_MISC, BAR_EMPTY = OFF_MISC + 48, BAR_XFULL = OFF_MISC + 96;
constexpr uint32_t BAR_W = OFF_MISC + 152, BAR_KVDONE = OFF_MISC + 160, BAR_AUX = OFF_MISC + 168, BAR_P4 = OFF_MISC + 176;
constexpr uint32_t BAR_P17 = OFF_MISC + 208;
constexpr uint32_t BAR_REFILL = OFF_MISC + 192;
constexpr uint32_t OFF_W = OFF_MISC + 256;
constexpr uint32_t SB = 1024;

__device__ __align__(128) float g_kvacc[8][2048];
__device__ unsigned int g_counter[64];

__device__ __forceinline__ void mbar_init(uint32_t bar, uint32_t cnt) {
    asm volatile("mbarrier.init.shared::cta.b64 [%0], %1;" :: "r"(bar), "r"(cnt) : "memory");
}
__device__ __forceinline__ void mbar_expect_tx(uint32_t bar, uint32_t bytes) {
    asm volatile("mbarrier.arrive.expect_tx.shared::cta.b64 _, [%0], %1;" :: "r"(bar), "r"(bytes) : "memory");
}
__device__ __forceinline__ void mbar_arrive(uint32_t bar) {
    asm volatile("mbarrier.arrive.shared::cta.b64 _, [%0];" :: "r"(bar) : "memory");
}
__device__ __forceinline__ void mbar_arrive_cluster(uint32_t bar) {
    asm volatile("mbarrier.arrive.shared::cluster.b64 _, [%0];" :: "r"(bar) : "memory");
}
__device__ __forceinline__ void mbar_wait(uint32_t bar, uint32_t parity) {
    asm volatile("{\n"
                 ".reg .pred p;\n"
                 ".reg .u32 c;\n"
                 "mov.u32 c, 0;\n"
                 "AGAIN:\n"
                 "mbarrier.try_wait.parity.shared::cta.b64 p, [%0], %1;\n"
                 "@p bra DONE;\n"
                 "add.u32 c, c, 1;\n"
                 "setp.lt.u32 p, c, 4194304;\n"
                 "@p bra AGAIN;\n"
                 "trap;\n"
                 "DONE:\n"
                 "}" :: "r"(bar), "r"(parity) : "memory");
}
__device__ __forceinline__ uint32_t mapa(uint32_t addr, uint32_t cta) {
    uint32_t r; asm("mapa.shared::cluster.u32 %0, %1, %2;" : "=r"(r) : "r"(addr), "r"(cta)); return r;
}
__device__ __forceinline__ bool elect_one() {
    uint32_t p;
    asm volatile("{ .reg .pred P; elect.sync _|P, 0xffffffff; selp.u32 %0, 1, 0, P; }" : "=r"(p));
    return p;
}
__device__ __forceinline__ void tma2d(uint32_t dst, const CUtensorMap* m, int c0, int c1, uint32_t bar) {
    asm volatile("cp.async.bulk.tensor.2d.shared::cluster.global.mbarrier::complete_tx::bytes [%0], [%1, {%3, %4}], [%2];"
                 :: "r"(dst), "l"(m), "r"(bar), "r"(c0), "r"(c1) : "memory");
}
__device__ __forceinline__ void tma2d_mc(uint32_t dst, const CUtensorMap* m, int c0, int c1, uint32_t bar) {
    asm volatile("cp.async.bulk.tensor.2d.shared::cluster.global.mbarrier::complete_tx::bytes.multicast::cluster [%0], [%1, {%3, %4}], [%2], %5;"
                 :: "r"(dst), "l"(m), "r"(bar), "r"(c0), "r"(c1), "h"((uint16_t)3) : "memory");
}
__device__ __forceinline__ void tma3d_mc(uint32_t dst, const CUtensorMap* m, int c0, int c1, int c2, uint32_t bar) {
    asm volatile("cp.async.bulk.tensor.3d.shared::cluster.global.mbarrier::complete_tx::bytes.multicast::cluster [%0], [%1, {%3, %4, %5}], [%2], %6;"
                 :: "r"(dst), "l"(m), "r"(bar), "r"(c0), "r"(c1), "r"(c2), "h"((uint16_t)3) : "memory");
}
__device__ __forceinline__ void tma_reduce2d(const CUtensorMap* m, uint32_t src, int c0, int c1) {
    asm volatile("cp.reduce.async.bulk.tensor.2d.global.shared::cta.add.bulk_group [%0, {%2, %3}], [%1];"
                 :: "l"(m), "r"(src), "r"(c0), "r"(c1) : "memory");
}
__device__ __forceinline__ void bulk_reduce_f32(float* dst, uint32_t src, uint32_t bytes) {
    asm volatile("cp.reduce.async.bulk.global.shared::cta.bulk_group.add.f32 [%0], [%1], %2;" :: "l"(dst), "r"(src), "r"(bytes) : "memory");
}
__device__ __forceinline__ bool mbar_try(uint32_t bar, uint32_t parity) {
    uint32_t ok;
    asm volatile("{ .reg .pred p; mbarrier.test_wait.parity.shared::cta.b64 p, [%1], %2; selp.u32 %0, 1, 0, p; }"
                 : "=r"(ok) : "r"(bar), "r"(parity) : "memory");
    return ok;
}
__device__ __forceinline__ void prefetch_map(const CUtensorMap* m) {
    asm volatile("prefetch.tensormap [%0];" :: "l"(m) : "memory");
}
__device__ __forceinline__ void wg_fence() { asm volatile("wgmma.fence.sync.aligned;" ::: "memory"); }
__device__ __forceinline__ void wg_commit() { asm volatile("wgmma.commit_group.sync.aligned;" ::: "memory"); }
template <int N> __device__ __forceinline__ void wg_wait() { asm volatile("wgmma.wait_group.sync.aligned %0;" :: "n"(N) : "memory"); }
template <int N> __device__ __forceinline__ void reg_fence(float (&d)[N]) {
#pragma unroll
    for (int i = 0; i < N; i++) asm volatile("" : "+f"(d[i]) :: "memory");
}
template <int N> __device__ __forceinline__ void reg_fence(uint32_t (&d)[N]) {
#pragma unroll
    for (int i = 0; i < N; i++) asm volatile("" : "+r"(d[i]) :: "memory");
}
template <int LO, int HI, int N> __device__ __forceinline__ void reg_fence_part(uint32_t (&d)[N]) {
#pragma unroll
    for (int i = LO; i < HI; i++) asm volatile("" : "+r"(d[i]) :: "memory");
}
__device__ __forceinline__ void fence_async_smem() { asm volatile("fence.proxy.async.shared::cta;" ::: "memory"); }
template <int ID, int N> __device__ __forceinline__ void bar_sync() { asm volatile("bar.sync %0, %1;" :: "n"(ID), "n"(N) : "memory"); }
template <int ID, int N> __device__ __forceinline__ void bar_arrive() { asm volatile("bar.arrive %0, %1;" :: "n"(ID), "n"(N) : "memory"); }
__device__ __forceinline__ void ldsm4(uint32_t* r, uint32_t addr) {
    asm volatile("ldmatrix.sync.aligned.m8n8.x4.shared.b16 {%0, %1, %2, %3}, [%4];"
                 : "=r"(r[0]), "=r"(r[1]), "=r"(r[2]), "=r"(r[3]) : "r"(addr) : "memory");
}
__device__ __forceinline__ void stsm4(uint32_t addr, uint32_t r0, uint32_t r1, uint32_t r2, uint32_t r3) {
    asm volatile("stmatrix.sync.aligned.m8n8.x4.shared.b16 [%0], {%1, %2, %3, %4};"
                 :: "r"(addr), "r"(r0), "r"(r1), "r"(r2), "r"(r3) : "memory");
}
__device__ __forceinline__ uint32_t lds32(uint32_t addr) {
    uint32_t r; asm volatile("ld.shared.u32 %0, [%1];" : "=r"(r) : "r"(addr)); return r;
}
__device__ __forceinline__ float4 lds128f(uint32_t addr) {
    float4 r; asm volatile("ld.shared.v4.f32 {%0, %1, %2, %3}, [%4];" : "=f"(r.x), "=f"(r.y), "=f"(r.z), "=f"(r.w) : "r"(addr)); return r;
}
__device__ __forceinline__ uint32_t clock32() { uint32_t t; asm volatile("mov.u32 %0, %%clock;" : "=r"(t)); return t; }
__device__ __forceinline__ uint32_t pack_bf16(float lo, float hi) {
    uint32_t r; asm("cvt.rn.bf16x2.f32 %0, %1, %2;" : "=r"(r) : "f"(hi), "f"(lo)); return r;
}
__device__ __forceinline__ uint32_t pack_relu_bf16(float lo, float hi) {
    uint32_t r; asm("cvt.rn.relu.bf16x2.f32 %0, %1, %2;" : "=r"(r) : "f"(hi), "f"(lo)); return r;
}
__device__ __forceinline__ uint32_t mul_bf16x2(uint32_t a, uint32_t b) {
    uint32_t r; asm("mul.rn.bf16x2 %0, %1, %2;" : "=r"(r) : "r"(a), "r"(b)); return r;
}
__device__ __forceinline__ float phi(float t, float log2e) {
    float e;
    asm("ex2.approx.ftz.f32 %0, %1;" : "=f"(e) : "f"(fminf(t * log2e, 0.f)));
    return e + (fmaxf(t, 0.f) + 1e-6f);
}
__device__ __forceinline__ float after_issue(float v, uint32_t zero) {
    return __uint_as_float(__float_as_uint(v) | (clock32() & zero));
}
constexpr float kLog2e = 1.4426950408889634f;
__device__ __forceinline__ float rcp(float x) { float r; asm("rcp.approx.ftz.f32 %0, %1;" : "=f"(r) : "f"(x)); return r; }
__device__ __forceinline__ float bf_lo(uint32_t v) { return __uint_as_float(v << 16); }
__device__ __forceinline__ float bf_hi(uint32_t v) { return __uint_as_float(v & 0xffff0000u); }
constexpr uint32_t HI128 = (1024 >> 4) | (1u << 30);
constexpr uint32_t HI64 = (512 >> 4) | (2u << 30);
constexpr uint32_t LO128 = 1u << 16, LO64 = (1024u >> 4) << 16, LO128X2 = (2048u >> 4) << 16;
constexpr uint32_t QB = 16 * 112;
constexpr uint32_t TX1 = 2 * (2 * QB + 4096), TX2 = 2 * (QB + 4096), TX3 = 12288;
__device__ __forceinline__ void grid_arrive(unsigned int* c) {
    asm volatile("fence.acq_rel.gpu;" ::: "memory");
    asm volatile("red.relaxed.gpu.global.add.u32 [%0], 1;" :: "l"(c) : "memory");
}
__device__ __forceinline__ void grid_wait(const unsigned int* c, unsigned int target) {
    unsigned int v; int it = 0;
    do {
        asm volatile("ld.relaxed.gpu.global.u32 %0, [%1];" : "=r"(v) : "l"(c) : "memory");
        if (++it > (1 << 22)) asm volatile("trap;");
    } while ((int)(v - target) < 0);
    asm volatile("ld.acquire.gpu.global.u32 %0, [%1];" : "=r"(v) : "l"(c) : "memory");
}


__host__ __device__ constexpr uint32_t p4_pack(int n) { return (n / 3) * 36864 + (n % 3) * 14336; }
__host__ __device__ constexpr uint32_t p4_off(int n) {
    return n < 6 ? OFF_X + p4_pack(n) : n < 14 ? OFF_RING + p4_pack(n - 6) : n == 14 ? OFF_X + p4_pack(6)
                 : n == 17 ? OFF_STG + 8192 : n == 20 ? OFF_X + p4_pack(2) : OFF_X + p4_pack(n - 15);
}
__host__ __device__ constexpr uint32_t p4_bar(int n) {
    return n < 6 ? BAR_XFULL + 8 * n : n < 12 ? BAR_FULL + 8 * (n - 6) : n < 14 ? BAR_P4 + 8 * (n - 12)
                 : n == 14 ? BAR_XFULL + 48 : n == 17 ? BAR_P17 : n == 20 ? BAR_XFULL + 16 : BAR_XFULL + 8 * (n - 15);
}
__host__ __device__ constexpr uint32_t p4_par(int n) { return (n < 12 || n == 14) ? 1 : 0; }
constexpr uint32_t OFF_OUT = OFF_X + 5 * 16384;
static_assert(p4_off(7) == p4_off(6) + 14336 && p4_off(13) == p4_off(12) + 14336 && p4_off(16) == p4_off(15) + 14336, "Wd halves");
static_assert(p4_off(13) + 14336 <= OFF_STG + 8192 && p4_off(14) + 8192 == OFF_OUT, "pass-4 layout");

struct Ring {
    uint32_t slot, phase;
    __device__ __forceinline__ void advance() { if (++slot == NSLOT) { slot = 0; phase ^= 1; } }
};

struct Maps { CUtensorMap x, kv, q, g4, g3, u4, u3, d, o, out; };

__global__ void __cluster_dims__(2, 1, 1) __launch_bounds__(NTHREADS, 1)
fused_kernel(const __grid_constant__ Maps mp, const __nv_bfloat16* __restrict__ gate_w, __nv_bfloat16* __restrict__ out,
             uint32_t zero)
{
    extern __shared__ __align__(1024) unsigned char smem[];
    const uint32_t sb = (uint32_t)__cvta_generic_to_shared(smem);
    const int tid = threadIdx.x, warp = tid >> 5, lane = tid & 31;
    const int rank = blockIdx.x & 1, j = blockIdx.x >> 4;
    const int row0 = (blockIdx.x & 15) * 128;
    const int par = j & 1;
    const int g4i = (7 * j + 3 * par) >> 1;

    if (warp == 9) {
        if (elect_one()) {
            prefetch_map(&mp.x);
            mbar_init(sb + BAR_XFULL, 1);
            mbar_expect_tx(sb + BAR_XFULL, 16384);
            tma2d(sb + OFF_X, &mp.x, 0, row0, sb + BAR_XFULL);
            asm volatile("fence.mbarrier_init.release.cluster;" ::: "memory");
        }
        __syncwarp();
    } else if (warp == 8) {
        if (elect_one()) {
            #pragma unroll
            for (int s = 0; s < NSLOT; s++) mbar_init(sb + BAR_FULL + 8 * s, 1);
            asm volatile("fence.mbarrier_init.release.cluster;" ::: "memory");
            mbar_expect_tx(sb + BAR_FULL, TX1);
        }
        __syncwarp();
    } else if (warp == 10) {
        if (elect_one()) {
            #pragma unroll
            for (int s = 1; s < 7; s++) mbar_init(sb + BAR_XFULL + 8 * s, 1);
            mbar_init(sb + BAR_KVDONE, 8);
            mbar_init(sb + BAR_AUX, 3);
            asm volatile("fence.mbarrier_init.release.cluster;" ::: "memory");
            if ((sb & 0xFFFFFF) != SB) asm volatile("trap;");
        }
        __syncwarp();
    } else if (warp == 11) {
        if (elect_one()) {
            #pragma unroll
            for (int s = 0; s < NSLOT; s++) mbar_init(sb + BAR_EMPTY + 8 * s, 4);
            mbar_init(sb + BAR_P4, 1);
            mbar_init(sb + BAR_P4 + 8, 1);
            mbar_init(sb + BAR_P17, 1);
            mbar_init(sb + BAR_REFILL, 4);
            mbar_init(sb + BAR_REFILL + 8, 4);
            asm volatile("fence.mbarrier_init.release.cluster;" ::: "memory");
        }
        __syncwarp();
    } else if (warp == 2) {
        if (elect_one()) {
            mbar_init(sb + BAR_W, 1);
            asm volatile("fence.mbarrier_init.release.cluster;" ::: "memory");
            mbar_expect_tx(sb + BAR_W, 896);
            asm volatile("cp.async.bulk.shared::cluster.global.mbarrier::complete_tx::bytes [%0], [%1], 896, [%2];"
                         :: "r"(sb + OFF_W), "l"(gate_w), "r"(sb + BAR_W) : "memory");
        }
        __syncwarp();
    }
    asm volatile("barrier.cluster.arrive.relaxed.aligned;" ::: "memory");
    if (warp == 8) {
        if (elect_one()) { prefetch_map(&mp.kv); prefetch_map(&mp.g4); }
        __syncwarp();
    }
    asm volatile("barrier.cluster.wait.aligned;" ::: "memory");
    if (warp == 8) {
        if (elect_one()) {
            tma3d_mc(sb + OFF_RING + rank * 8192 + 4096, &mp.kv, 56 * j, 16 * rank, 1, sb + BAR_FULL);
            tma3d_mc(sb + OFF_RING + rank * 8192, &mp.g4, 0, 16 * rank, g4i, sb + BAR_FULL);
        }
        __syncwarp();
    }

    if (warp >= 8) {
        asm volatile("setmaxnreg.dec.sync.aligned.u32 40;");
        if (warp == 8) {
            if (elect_one()) {
                Ring r{1, 1};
                auto acquire = [&](uint32_t bytes) -> uint32_t {
                    mbar_wait(sb + BAR_EMPTY + 8 * r.slot, r.phase);
                    mbar_expect_tx(sb + BAR_FULL + 8 * r.slot, bytes);
                    return sb + OFF_RING + r.slot * SLOT_BYTES;
                };
                #pragma unroll 1
                for (int s = 1; s < 14; s++) {
                    const uint32_t dst = acquire(TX1) + rank * 8192;
                    tma3d_mc(dst + 4096, &mp.kv, 56 * j, 32 * s + 16 * rank, 1, sb + BAR_FULL + 8 * r.slot);
                    tma3d_mc(dst, &mp.g4, 0, 32 * s + 16 * rank, g4i, sb + BAR_FULL + 8 * r.slot);
                    r.advance();
                    if ((s & 1) && s < 12) {
                        const int n = (s >> 1) + 1;
                        mbar_expect_tx(sb + BAR_XFULL + 8 * n, 16384);
                        tma2d(sb + OFF_X + n * 16384, &mp.x, 64 * n, row0, sb + BAR_XFULL + 8 * n);
                    }
                    if (s == 5) {
                        prefetch_map(&mp.q); prefetch_map(&mp.u4); prefetch_map(&mp.g3); prefetch_map(&mp.u3);
                        prefetch_map(&mp.d); prefetch_map(&mp.o); prefetch_map(&mp.out);
                    }
                }
                #pragma unroll 1
                for (int s = 0; s < 14; s++) {
                    const uint32_t dst = acquire(TX2) + rank * 6144;
                    tma3d_mc(dst, &mp.q, 56 * j, 32 * s + 16 * rank, 0, sb + BAR_FULL + 8 * r.slot);
                    tma3d_mc(dst + 2048, &mp.u4, 0, 32 * s + 16 * rank, g4i, sb + BAR_FULL + 8 * r.slot);
                    r.advance();
                }
                const int cfirst = j == 7 ? 0 : j;
                auto load4 = [&](int n) {
                    int c = cfirst + n / 3;
                    if (c >= 7) c -= 7;
                    mbar_expect_tx(sb + p4_bar(n), n % 3 == 2 ? 8192 : 14336);
                    if (n % 3 == 2) tma2d_mc(sb + p4_off(n) + rank * 4096, &mp.o, 64 * c, 56 * j + 32 * rank, sb + p4_bar(n));
                    else tma2d_mc(sb + p4_off(n) + rank * 7168, &mp.d, 64 * c, 224 * j + 112 * (n % 3) + 56 * rank, sb + p4_bar(n));
                };
                #pragma unroll 1
                for (int s = 0; s < 14; s++) {
                    const uint32_t dst = acquire(TX3) + rank * 6144;
                    tma3d_mc(dst, &mp.g3, 0, 32 * s + 16 * rank, 7 * j + 4 - 4 * par, sb + BAR_FULL + 8 * r.slot);
                    tma3d_mc(dst + 3072, &mp.u3, 0, 32 * s + 16 * rank, 7 * j + 4 - 4 * par, sb + BAR_FULL + 8 * r.slot);
                    r.advance();
                    if (s == 7) load4(0);
                    if (s == 9) load4(1);
                    if (s == 11) load4(2);
                    if (s == 13) { load4(3); load4(4); }
                }
                mbar_wait(sb + BAR_EMPTY, 0);      load4(6);
                mbar_wait(sb + BAR_EMPTY + 8, 0);  load4(5); load4(7); load4(14);
                mbar_wait(sb + BAR_EMPTY + 16, 0); load4(8);
                mbar_wait(sb + BAR_EMPTY + 24, 0); load4(9); load4(10);
                mbar_wait(sb + BAR_EMPTY + 32, 0); load4(11);
                load4(17);
                mbar_wait(sb + BAR_EMPTY + 40, 0); load4(12);
                mbar_wait(sb + BAR_AUX, 0);        load4(13);
                mbar_wait(sb + BAR_REFILL, 0);     load4(15); load4(16); load4(20);
                mbar_wait(sb + BAR_REFILL + 8, 0); load4(18); load4(19);
            }
        } else {
            const int ht = tid - 288;
            unsigned int cnt0;
            asm volatile("ld.relaxed.gpu.global.u32 %0, [%1];" : "=r"(cnt0) : "l"(&g_counter[32]) : "memory");
            const unsigned int target = ((cnt0 >> 7) + 1) << 7;
            if (warp == 9) {
                reinterpret_cast<float4*>(&g_kvacc[0][0])[blockIdx.x * 32 + lane] = make_float4(0.f, 0.f, 0.f, 0.f);
                asm volatile("fence.proxy.async.global;" ::: "memory");
                __syncwarp();
                if (lane == 0) grid_arrive(&g_counter[0]);
                mbar_wait(sb + BAR_XFULL + 8 * 6, 0);
                uint4* o = reinterpret_cast<uint4*>(out) + blockIdx.x * 896 + lane;
                #pragma unroll 4
                for (int q = 0; q < 28; q++) o[q * 32] = make_uint4(0, 0, 0, 0);
                asm volatile("fence.proxy.async.global;" ::: "memory");
                __syncwarp();
                if (lane == 0) {
                    asm volatile("fence.acq_rel.gpu;" ::: "memory");
                    grid_wait(&g_counter[0], target);
                }
                __syncwarp();
            }
            mbar_wait(sb + BAR_KVDONE, 0);
            {
                #pragma unroll
                for (int i0 = 0; i0 < 5; i0 += 2) {
                    float4 pa[2], pb[2];
                    #pragma unroll
                    for (int i = 0; i < 2 && i0 + i < 5; i++) {
                        const int q = min(ht + 96 * (i0 + i), 447);
                        pa[i] = lds128f(sb + OFF_STG + q * 16); pb[i] = lds128f(sb + OFF_STG + 8192 + q * 16);
                    }
                    #pragma unroll
                    for (int i = 0; i < 2 && i0 + i < 5; i++) {
                        const int q = ht + 96 * (i0 + i);
                        if (q < 448) asm volatile("st.shared.v4.f32 [%0], {%1, %2, %3, %4};" :: "r"(sb + OFF_STG + q * 16),
                            "f"(pa[i].x + pb[i].x), "f"(pa[i].y + pb[i].y), "f"(pa[i].z + pb[i].z), "f"(pa[i].w + pb[i].w) : "memory");
                    }
                }
                fence_async_smem();
            }
            bar_sync<3, 96>();
            if (warp == 9) {
                if (elect_one()) {
                    bulk_reduce_f32(&g_kvacc[j][0], sb + OFF_STG, 7168);
                    asm volatile("cp.async.bulk.commit_group;" ::: "memory");
                    asm volatile("cp.async.bulk.wait_group 0;" ::: "memory");
                    asm volatile("red.relaxed.gpu.global.add.u32 [%0], 1;" :: "l"(&g_counter[32]) : "memory");
                }
            }
            __syncwarp();
            #pragma unroll
            for (int i = 0; i < 3; i++) {
                const int q = ht + 96 * i;
                const int d = q < 168 ? q / 3 : 56 + ((q - 168) >> 3);
                const int c = q < 168 ? (q - 3 * d + (d < 28 ? 4 : 0)) : (q & 7);
                if (q < 232) asm volatile("st.shared.v4.u32 [%0], {%1, %1, %1, %1};" :: "r"(sb + OFF_STG + 8192 + d * 128 + ((c ^ (d & 7)) << 4)), "r"(0) : "memory");
            }
            uint32_t plan[3];
            #pragma unroll
            for (int i = 0; i < 3; i++) {
                const int q = min(ht + 96 * i, 279), d = q / 5, m = q - 5 * d;
                const bool h0 = d < 28;
                const int c = m == 4 ? 7 : (h0 ? m : m + 3), pc = m < 4 ? m : (h0 ? 3 : 0);
                const int kind = m == 4 ? (h0 ? 3 : 4) : c == 3 ? (h0 ? 1 : 2) : 0;
                plan[i] = (d * 128 + ((c ^ (d & 7)) << 4)) | ((d * 4 + (pc ^ (d & 3))) << 13) | (kind << 23);
                asm volatile("" : "+r"(plan[i]));
            }
            if (lane == 0) grid_wait(&g_counter[32], target);
            __syncwarp();
            const float4* src = reinterpret_cast<const float4*>(&g_kvacc[j][0]);
            float4 va[3], vb[3];
            #pragma unroll
            for (int i = 0; i < 3; i++) {
                const float4* p = src + ((plan[i] >> 12) & 0x7fe);
                va[i] = __ldcg(p); vb[i] = __ldcg(p + 1);
            }
            #pragma unroll
            for (int i = 0; i < 3; i++) {
                const uint32_t kind = plan[i] >> 23;
                uint32_t w0 = pack_bf16(va[i].x, va[i].y), w1 = pack_bf16(va[i].z, va[i].w);
                uint32_t w2 = pack_bf16(vb[i].x, vb[i].y), w3 = pack_bf16(vb[i].z, vb[i].w);
                if (kind == 3) w0 = w2 & 0xffffu;
                if (kind == 4) w0 <<= 16;
                if (kind == 2) w0 = 0u;
                if (kind >= 2) w1 = 0u;
                if (kind != 0 && kind != 2) w2 = w3 = 0u;
                if (i < 2 || ht < 88)
                    asm volatile("st.shared.v4.u32 [%0], {%1, %2, %3, %4};"
                                 :: "r"(sb + OFF_STG + 8192 + (plan[i] & 0x1fff)), "r"(w0), "r"(w1), "r"(w2), "r"(w3) : "memory");
            }
            fence_async_smem();
            __syncwarp();
            if (lane == 0) mbar_arrive(sb + BAR_AUX);
        }
    } else {
        asm volatile("setmaxnreg.inc.sync.aligned.u32 232;");
        const int wg = warp >> 2, w4 = warp & 3;
        const int q4 = lane & 3, g8 = lane >> 2;
        const uint32_t lx = ((lane >> 4) ^ (lane & 7)) << 4;
        const uint32_t xa = sb + OFF_X + (warp * 16 + (lane & 15)) * 128;
        const uint32_t empty_dst = mapa(sb + BAR_EMPTY, w4 & 1);
        const bool signaller = lane == 0 && w4 < 2;
        constexpr uint32_t dsb = SB >> 4;
        Ring r{0, 0};
        uint32_t cur = 0, old = 0;
        bool ready = false;
        auto release = [&](uint32_t slot) { if (signaller) mbar_arrive_cluster(empty_dst + 8 * slot); };
        auto turn_wait = [&]() { if (wg == 0) bar_sync<6, 256>(); else bar_sync<7, 256>(); };
        auto turn_pass = [&]() { if (wg == 0) bar_arrive<7, 256>(); else bar_arrive<6, 256>(); };
        auto begin = [&]() -> uint32_t {
            if (!ready) mbar_wait(sb + BAR_FULL + 8 * r.slot, r.phase);
            wg_fence();
            return dsb + (OFF_RING >> 4) + r.slot * (SLOT_BYTES >> 4);
        };
        auto commit = [&]() { wg_commit(); old = cur; cur = r.slot; r.advance(); };
        auto retire = [&]() { wg_wait<1>(); release(old); };
        auto peek = [&]() { ready = mbar_try(sb + BAR_FULL + 8 * r.slot, r.phase); };
        uint32_t a0[8], a1[8];
        auto load_a0 = [&](int kc) { ldsm4(a0, xa + kc * 16384 + lx); ldsm4(a0 + 4, xa + kc * 16384 + (lx ^ 32)); };
        auto load_a1 = [&](int kc) { ldsm4(a1, xa + kc * 16384 + (lx ^ 64)); ldsm4(a1 + 4, xa + kc * 16384 + (lx ^ 96)); };

        uint32_t hp[56];
        float g0, g1, av[28], agk[92];
        {
            float d0 = 0.f, d1 = 0.f, d2 = 0.f, d3 = 0.f;
            uint32_t w0[4], w1[4];
            auto issue1 = [&](uint32_t (&a)[8], int sd) {
                const uint32_t b = begin();
                wgmma_rs184<HI128>(agk, a[0], a[1], a[2], a[3], b + LO128X2, sd);
                wgmma_rs56<HI128>(av, a[0], a[1], a[2], a[3], b + LO128 + 384, sd);
                wgmma_rs184<HI128>(agk, a[4], a[5], a[6], a[7], b + LO128X2 + 512, 1);
                wgmma_rs56<HI128>(av, a[4], a[5], a[6], a[7], b + LO128 + 896, 1);
                commit();
            };
            auto issue1s = [&](uint32_t (&a)[8]) {
                const uint32_t b = begin();
                wgmma_rs184<HI128>(agk, a[0], a[1], a[2], a[3], b + LO128X2, 1);
                wgmma_rs184<HI128>(agk, a[4], a[5], a[6], a[7], b + LO128X2 + 512, 1);
                wg_commit();
                wgmma_rs56<HI128>(av, a[0], a[1], a[2], a[3], b + LO128 + 384, 1);
                wgmma_rs56<HI128>(av, a[4], a[5], a[6], a[7], b + LO128 + 896, 1);
                commit();
            };
            auto load_w = [&](uint32_t (&w)[4], int s) {
                #pragma unroll
                for (int e = 0; e < 4; e++) w[e] = lds32(sb + OFF_W + s * 64 + q4 * 4 + e * 16);
            };
            auto dot = [&](uint32_t (&a)[8], uint32_t (&w)[4]) {
                #pragma unroll
                for (int e = 0; e < 4; e++) {
                    const uint32_t p0 = mul_bf16x2(a[2 * e], w[e]), p1 = mul_bf16x2(a[2 * e + 1], w[e]);
                    d0 += bf_lo(p0); d2 += bf_hi(p0); d1 += bf_lo(p1); d3 += bf_hi(p1);
                }
                asm volatile("" : "+f"(d0), "+f"(d1), "+f"(d2), "+f"(d3));
            };
            mbar_wait(sb + BAR_XFULL, 0);
            load_a0(0);
            mbar_wait(sb + BAR_W, 0);
            load_w(w0, 0);
            auto odd_stage = [&](int it, bool first, bool last) {
                wg_wait<1>();
                if (!first) release(old);
                load_a1(it);
                load_w(w1, 2 * it + 1);
                peek();
                dot(a0, w0);
                if (last && wg == 1) bar_sync<4, 256>();
                issue1s(a1);
                if (last && wg == 0) bar_arrive<4, 256>();
            };
            issue1(a0, 0);
            #pragma unroll
            for (int it = 0; it < 6; it++) {
                const bool xok = mbar_try(sb + BAR_XFULL + 8 * (it + 1), 0);
                odd_stage(it, it == 0, false);
                wg_wait<2>(); release(old);
                if (!xok) mbar_wait(sb + BAR_XFULL + 8 * (it + 1), 0);
                load_a0(it + 1);
                load_w(w0, 2 * it + 2);
                peek();
                dot(a1, w1);
                issue1(a0, 1);
            }
            odd_stage(6, false, true);
            wg_wait<2>(); release(old);
            load_a0(0);
            peek();
            dot(a1, w1);
            wg_wait<1>();
            reg_fence(agk);
            #pragma unroll
            for (int i = 0; i < 32; i++) hp[i] = pack_relu_bf16(agk[2 * i], agk[2 * i + 1]);
            reg_fence_part<0, 32>(hp);
            g0 = d0 + d2; g1 = d1 + d3;
        }

        float aq[28], au[64];
        {
            auto issue2 = [&](uint32_t (&a)[8], int sd) {
                const uint32_t b = begin();
                wgmma_rs56<HI128>(aq, a[0], a[1], a[2], a[3], b + LO128, sd);
                wgmma_rs128<HI128>(au, a[0], a[1], a[2], a[3], b + LO128X2 + 128, sd);
                wgmma_rs56<HI128>(aq, a[4], a[5], a[6], a[7], b + LO128 + 384, 1);
                wgmma_rs128<HI128>(au, a[4], a[5], a[6], a[7], b + LO128X2 + 512, 1);
            };
            const uint32_t st_base = wg == 0 ? OFF_STG : OFF_RING + 12288, st_step = wg == 0 ? 2048 : SLOT_BYTES, st_v = wg == 0 ? 8192 : 2048;
            const uint32_t sk = sb + st_base + w4 * st_step + (lane & 15) * 128;
            float tok = kLog2e;
            uint32_t pk[16];
            pk[14] = 0u; pk[15] = 0u;
            auto stage_k = [&](int lo, int hi) {
                #pragma unroll
                for (int i = 0; i < 14; i++) if (i >= lo && i < hi) pk[i] = pack_bf16(phi(agk[64 + 2 * i], tok), phi(agk[65 + 2 * i], tok));
                #pragma unroll
                for (int t = 0; t < 4; t++) {
                    const int need = t < 3 ? 4 * t + 4 : 14;
                    if (need > lo && need <= hi) stsm4(sk + (lx ^ (t * 32)), pk[4 * t], pk[4 * t + 1], pk[4 * t + 2], pk[4 * t + 3]);
                }
                #pragma unroll
                for (int i = 0; i < 14; i++) if (i >= lo && i < hi) asm volatile("" : "+r"(pk[i]));
            };
            issue2(a0, 0); commit();
            tok = after_issue(kLog2e, zero);
            retire();
            reg_fence(av);
            if (wg == 0) bar_arrive<8, 256>();
            load_a1(0); peek();
            uint32_t pv[14];
            #pragma unroll
            for (int i = 0; i < 14; i++) pv[i] = pack_bf16(av[2 * i], av[2 * i + 1]);
            if (wg == 1) bar_sync<8, 256>();
            {
                const uint32_t ones = q4 == 0 ? 0x3f803f80u : 0u;
                #pragma unroll
                for (int t = 0; t < 3; t++) stsm4(sk + st_v + (lx ^ (t * 32)), pv[4 * t], pv[4 * t + 1], pv[4 * t + 2], pv[4 * t + 3]);
                stsm4(sk + st_v + (lx ^ 96), pv[12], pv[13], ones, ones);
            }
            stage_k(0, 2);
            issue2(a1, 1); commit();
            tok = after_issue(kLog2e, zero);
            retire(); load_a0(1); peek();
            stage_k(2, 5);
            issue2(a0, 1); commit();
            tok = after_issue(kLog2e, zero);
            retire(); load_a1(1); peek();
            stage_k(5, 8);
            issue2(a1, 1); commit();
            tok = after_issue(kLog2e, zero);
            retire(); load_a0(2); peek();
            stage_k(8, 11);
            issue2(a0, 1); commit();
            tok = after_issue(kLog2e, zero);
            retire(); load_a1(2); peek();
            stage_k(11, 14);
            issue2(a1, 1); commit();
            retire(); load_a0(3); peek();
            fence_async_smem();
            if (wg == 0) bar_sync<1, 128>(); else bar_sync<2, 128>();
            float kv[32];
            issue2(a0, 1);
            {
                const uint32_t dk = dsb + LO128 + (st_base >> 4), ds = st_step >> 4, dv = st_v >> 4;
                #pragma unroll
                for (int ks = 0; ks < 4; ks++) wgmma_ss64_tt<HI128>(kv, dk + ks * ds, dk + ks * ds + dv, ks);
            }
            commit();
            tok = after_issue(-kLog2e, zero);
            retire(); load_a1(3); peek();
            {
                g0 += __shfl_xor_sync(0xffffffffu, g0, 1); g1 += __shfl_xor_sync(0xffffffffu, g1, 1);
                g0 += __shfl_xor_sync(0xffffffffu, g0, 2); g1 += __shfl_xor_sync(0xffffffffu, g1, 2);
                const uint32_t lg = pack_bf16(g0, g1);
                float e0, e1;
                asm("ex2.approx.ftz.f32 %0, %1;" : "=f"(e0) : "f"(bf_lo(lg) * tok));
                asm("ex2.approx.ftz.f32 %0, %1;" : "=f"(e1) : "f"(bf_hi(lg) * tok));
                const uint32_t gg = pack_bf16(rcp(1.f + e0), rcp(1.f + e1));
                g0 = bf_lo(gg); g1 = bf_hi(gg);
                asm volatile("" : "+f"(g0), "+f"(g1));
            }
            issue2(a1, 1); commit();
            retire(); load_a0(4); peek();
            reg_fence(kv);
            if (wg == 0) { bar_arrive<5, 256>(); bar_sync<1, 128>(); } else bar_sync<5, 256>();
            auto stage_kv = [&](int hh) {
                const int d = w4 * 16 + g8 + 8 * hh;
                const bool h0 = d < 28;
                const uint32_t rowa = sb + OFF_STG + wg * 8192 + d * 128 + q4 * 8;
                #pragma unroll
                for (int t = 0; t < 4; t++) {
                    float v0 = h0 ? kv[4 * t + 2 * hh] : kv[4 * t + 12 + 2 * hh];
                    float v1 = h0 ? kv[4 * t + 2 * hh + 1] : kv[4 * t + 13 + 2 * hh];
                    if (t == 0 && !h0 && q4 == 0) v0 = kv[28 + 2 * hh];
                    if (d < 56 && !(t == 3 && h0 && q4 == 2))
                        asm volatile("st.shared.v2.f32 [%0], {%1, %2};" :: "r"(rowa + ((t ^ (g8 & 3)) << 5)), "f"(v0), "f"(v1) : "memory");
                }
                if (h0 && q4 == 0)
                    asm volatile("st.shared.v2.f32 [%0], {%1, %1};" :: "r"(rowa + ((3 ^ (g8 & 3)) << 5) + 16), "f"(kv[28 + 2 * hh]) : "memory");
            };
            stage_kv(0);
            issue2(a0, 1); commit();
            retire(); load_a1(4); peek();
            stage_kv(1);
            __syncwarp();
            if (lane == 0) mbar_arrive(sb + BAR_KVDONE);
            issue2(a1, 1); commit();
            retire(); load_a0(5); peek();
            auto prescale = [&](int lo, int hi) {
                const float t0 = after_issue(1.f - g0, zero), t1 = after_issue(1.f - g1, zero);
                const uint32_t s0 = pack_bf16(t0, t0), s1 = pack_bf16(t1, t1);
                #pragma unroll
                for (int i = 0; i < 32; i++) if (i >= lo && i < hi) { hp[i] = mul_bf16x2(hp[i], (i & 1) ? s1 : s0); asm volatile("" : "+r"(hp[i])); }
            };
            prescale(0, 16);
            issue2(a0, 1); commit();
            retire(); load_a1(5); peek();
            prescale(16, 32);
            issue2(a1, 1); commit();
            retire(); load_a0(6); peek();
            issue2(a0, 1); commit();
            retire(); load_a1(6); peek();
            if (wg == 1) bar_sync<4, 256>();
            const uint32_t b = begin();
            wgmma_rs128<HI128>(au, a1[0], a1[1], a1[2], a1[3], b + LO128X2 + 128, 1);
            wgmma_rs128<HI128>(au, a1[4], a1[5], a1[6], a1[7], b + LO128X2 + 512, 1);
            wg_commit();
            wgmma_rs56<HI128>(aq, a1[0], a1[1], a1[2], a1[3], b + LO128, 1);
            wgmma_rs56<HI128>(aq, a1[4], a1[5], a1[6], a1[7], b + LO128 + 384, 1);
            commit();
            if (wg == 0) bar_arrive<4, 256>();
            wg_wait<2>(); release(old);
            load_a0(0); peek();
            wg_wait<1>();
            reg_fence(au);
        }
        #pragma unroll
        for (int i = 0; i < 32; i++) hp[i] = mul_bf16x2(hp[i], pack_bf16(au[2 * i], au[2 * i + 1]));
        reg_fence_part<0, 32>(hp);

        float ag[96];
        uint32_t op[16];
        {
            auto issue3 = [&](uint32_t (&a)[8], int sd) {
                const uint32_t b = begin();
                wgmma_rs192<HI64>(ag, a[0], a[1], a[2], a[3], b + LO64, sd);
                wgmma_rs192<HI64>(ag, a[4], a[5], a[6], a[7], b + LO64 + 384, 1);
            };
            uint32_t pq[16];
            float nd[32];
            uint32_t a2[8];
            auto load3 = [&](int st) {
                uint32_t (&a)[8] = st % 3 == 0 ? a0 : st % 3 == 1 ? a1 : a2;
                const uint32_t p = xa + (st >> 1) * 16384, x0 = lx ^ ((st & 1) * 64);
                ldsm4(a, p + x0); ldsm4(a + 4, p + (x0 ^ 32));
            };
            pq[14] = 0u; pq[15] = 0u;
            bool aux = false;
            #pragma unroll
            for (int st = 0; st < 14; st++) {
                uint32_t (&a)[8] = st % 3 == 0 ? a0 : st % 3 == 1 ? a1 : a2;
                if (st == 0) load3(2);
                if (st == 12) {
                    if (!aux) mbar_wait(sb + BAR_AUX, 0);
                    if (wg == 1) bar_sync<4, 256>();
                }
                issue3(a, st);
                if (st == 12) {
                    const uint32_t dk = dsb + LO128 + ((OFF_STG + 8192) >> 4);
                    #pragma unroll
                    for (int ks = 0; ks < 4; ks++) wgmma_rs64<HI128>(nd, pq[4 * ks], pq[4 * ks + 1], pq[4 * ks + 2], pq[4 * ks + 3], dk + ks * 128, ks);
                }
                commit();
                if (st == 13) { if (wg == 0) bar_arrive<4, 256>(); break; }
                const float tok = (st >= 1 && st < 8) ? after_issue(kLog2e, zero) : 0.f;
                if (st == 11) aux = mbar_try(sb + BAR_AUX, 0);
                peek();
                retire();
                if (st == 0) { reg_fence(aq); load3(1); }
                else if (st + 2 < 14) load3(st + 2);
                if (st >= 1 && st < 8) {
                    const int i = 2 * st - 2;
                    pq[i] = pack_bf16(phi(aq[2 * i], tok), phi(aq[2 * i + 1], tok));
                    pq[i + 1] = pack_bf16(phi(aq[2 * i + 2], tok), phi(aq[2 * i + 3], tok));
                    asm volatile("" : "+r"(pq[i]), "+r"(pq[i + 1]));
                }
            }
            ready = mbar_try(sb + p4_bar(0), p4_par(0));
            retire();
            reg_fence(nd);
            const int src = lane & ~3;
            const float s00 = g0 * rcp(__shfl_sync(0xffffffffu, nd[28], src) + 1e-6f);
            const float s01 = g0 * rcp(__shfl_sync(0xffffffffu, nd[29], src) + 1e-6f);
            const float s10 = g1 * rcp(__shfl_sync(0xffffffffu, nd[30], src) + 1e-6f);
            const float s11 = g1 * rcp(__shfl_sync(0xffffffffu, nd[31], src) + 1e-6f);
            #pragma unroll
            for (int t = 0; t < 7; t++) {
                const bool h1 = t > 3 || (t == 3 && q4 >= 2);
                const float sa = h1 ? s01 : s00, sc = h1 ? s11 : s10;
                op[2 * t] = pack_bf16(nd[4 * t] * sa, nd[4 * t + 1] * sa);
                op[2 * t + 1] = pack_bf16(nd[4 * t + 2] * sc, nd[4 * t + 3] * sc);
            }
            op[14] = 0u; op[15] = 0u;
            reg_fence(op);
        }

        float oa[32], ob[32];
        int c = j == 7 ? 0 : j;
        const int wsh = __shfl_sync(0xffffffffu, warp * 16, 0);
        const uint32_t sh0 = par * 768, sh1 = par * 1024;
        bool ready2 = false;
        auto issue_d = [&](float (&o)[32], int c0, int half) {
            const int n = 3 * c0;
            if (half == 0) {
                if (!ready) mbar_wait(sb + p4_bar(n), p4_par(n));
                if (!ready2) mbar_wait(sb + p4_bar(n + 1), p4_par(n + 1));
                ready = mbar_try(sb + p4_bar(n + 2), p4_par(n + 2));
            }
            wg_fence();
            const uint32_t b = dsb + LO128 + (p4_off(n) >> 4);
            #pragma unroll
            for (int ks = 7 * half; ks < 7 * half + 7; ks++)
                wgmma_rs64<HI128>(o, hp[4 * ks], hp[4 * ks + 1], hp[4 * ks + 2], hp[4 * ks + 3],
                                  b + ks * 128 + (ks < 8 ? sh0 : 0u - sh1), ks);
        };
        auto issue_o = [&](float (&o)[32], int c0) {
            const int n = 3 * c0 + 2;
            if (!ready) mbar_wait(sb + p4_bar(n), p4_par(n));
            if (c0 < 6) {
                ready = mbar_try(sb + p4_bar(n + 1), p4_par(n + 1));
                ready2 = mbar_try(sb + p4_bar(n + 2), p4_par(n + 2));
            }
            wg_fence();
            const uint32_t b = dsb + LO128 + (p4_off(n) >> 4);
            #pragma unroll
            for (int ks = 0; ks < 4; ks++) wgmma_rs64<HI128>(o, op[4 * ks], op[4 * ks + 1], op[4 * ks + 2], op[4 * ks + 3], b + ks * 128, 1);
            wg_commit();
        };
        auto ship = [&](float (&o)[32], int c0) {
            reg_fence(o);
            const uint32_t so = xa + OFF_OUT + (c0 & 1) * 16384;
            #pragma unroll
            for (int t = 0; t < 4; t++)
                stsm4(so + (lx ^ (t * 32)), pack_bf16(o[8 * t], o[8 * t + 1]), pack_bf16(o[8 * t + 2], o[8 * t + 3]),
                      pack_bf16(o[8 * t + 4], o[8 * t + 5]), pack_bf16(o[8 * t + 6], o[8 * t + 7]));
            fence_async_smem();
            __syncwarp();
            if (elect_one()) {
                tma_reduce2d(&mp.out, sb + OFF_OUT + (c0 & 1) * 16384 + wsh * 128, 64 * c, row0 + wsh);
                asm volatile("cp.async.bulk.commit_group;" ::: "memory");
            }
            if (++c == 7) c = 0;
        };
        auto finish_h = [&]() {
            reg_fence(ag);
            release(cur);
            const uint32_t s0 = pack_bf16(1.f - g0, 1.f - g0), s1 = pack_bf16(1.f - g1, 1.f - g1);
            #pragma unroll
            for (int i = 0; i < 24; i++)
                hp[32 + i] = mul_bf16x2(mul_bf16x2(pack_relu_bf16(ag[2 * i], ag[2 * i + 1]), (i & 1) ? s1 : s0),
                                        pack_bf16(ag[48 + 2 * i], ag[49 + 2 * i]));
            reg_fence_part<32, 56>(hp);
        };
        ready2 = mbar_try(sb + p4_bar(1), p4_par(1));
        wg_wait<0>();
        finish_h();
        #pragma unroll
        for (int c0 = 0; c0 < 7; c0++) {
            float (&o)[32] = (c0 & 1) ? ob : oa;
            if (c0 > 0 || wg == 1) turn_wait();
            issue_d(o, c0, 0);
            issue_d(o, c0, 1);
            issue_o(o, c0);
            if (!(c0 == 6 && wg == 1)) turn_pass();
            if (c0 >= 2) {
                if (elect_one()) asm volatile("cp.async.bulk.wait_group.read 1;" ::: "memory");
                __syncwarp();
            }
            wg_wait<0>();
            if (c0 < 2 && signaller) mbar_arrive_cluster(empty_dst + (BAR_REFILL - BAR_EMPTY) + 8 * c0);
            ship(o, c0);
        }
        if (elect_one()) asm volatile("cp.async.bulk.wait_group.read 0;" ::: "memory");
    }
}

typedef CUresult (*EncodeFn)(CUtensorMap*, CUtensorMapDataType, cuuint32_t, void*, const cuuint64_t*, const cuuint64_t*,
                             const cuuint32_t*, const cuuint32_t*, CUtensorMapInterleave, CUtensorMapSwizzle,
                             CUtensorMapL2promotion, CUtensorMapFloatOOBfill);

void make_map(EncodeFn enc, CUtensorMap* m, const void* base, int rank, const cuuint64_t* dims, const cuuint64_t* strides,
              cuuint32_t b0, cuuint32_t b1, cuuint32_t b2, CUtensorMapSwizzle sw) {
    const cuuint32_t es[3] = {1, 1, 1}, box[3] = {b0, b1, b2};
    enc(m, CU_TENSOR_MAP_DATA_TYPE_BFLOAT16, rank, const_cast<void*>(base), dims, strides, box, es,
        CU_TENSOR_MAP_INTERLEAVE_NONE, sw, CU_TENSOR_MAP_L2_PROMOTION_L2_128B, CU_TENSOR_MAP_FLOAT_OOB_FILL_NONE);
}

}

extern "C" void kernel_launch(void* const* d_in, const int* in_sizes, int n_in, void* d_out, int out_size) {
    (void)in_sizes; (void)n_in; (void)out_size;
    static EncodeFn enc = nullptr;
    if (!enc) {
        void* fn = nullptr;
        cudaDriverEntryPointQueryResult st;
        cudaGetDriverEntryPoint("cuTensorMapEncodeTiled", &fn, cudaEnableDefault, &st);
        enc = (EncodeFn)fn;
        cudaFuncSetAttribute(fused_kernel, cudaFuncAttributeMaxDynamicSharedMemorySize, SMEM_BYTES);
    }
    Maps mp;
    const cuuint64_t dimx[2] = {kD, kS}, dimd[2] = {kD, kF}, dimo[2] = {kD, kD}, strd[1] = {kD * 2};
    make_map(enc, &mp.x, d_in[0], 2, dimx, strd, 64, 128, 1, CU_TENSOR_MAP_SWIZZLE_128B);
    make_map(enc, &mp.out, d_out, 2, dimx, strd, 64, 16, 1, CU_TENSOR_MAP_SWIZZLE_128B);
    make_map(enc, &mp.d, d_in[6], 2, dimd, strd, 64, 56, 1, CU_TENSOR_MAP_SWIZZLE_128B);
    make_map(enc, &mp.o, d_in[2], 2, dimo, strd, 64, 32, 1, CU_TENSOR_MAP_SWIZZLE_128B);
    const cuuint64_t dimq[3] = {kD, kD, 3}, strq[2] = {3 * kD * 2, kD * 2};
    make_map(enc, &mp.kv, d_in[1], 3, dimq, strq, 56, 16, 2, CU_TENSOR_MAP_SWIZZLE_128B);
    make_map(enc, &mp.q, d_in[1], 3, dimq, strq, 56, 16, 1, CU_TENSOR_MAP_SWIZZLE_128B);
    const cuuint64_t dimf[3] = {32, kD, kF / 32}, strf[2] = {kF * 2, 64};
    const cuuint64_t dimw[3] = {64, kD, kF / 64}, strw[2] = {kF * 2, 128};
    make_map(enc, &mp.g4, d_in[4], 3, dimw, strw, 64, 16, 2, CU_TENSOR_MAP_SWIZZLE_128B);
    make_map(enc, &mp.u4, d_in[5], 3, dimw, strw, 64, 16, 2, CU_TENSOR_MAP_SWIZZLE_128B);
    make_map(enc, &mp.g3, d_in[4], 3, dimf, strf, 32, 16, 3, CU_TENSOR_MAP_SWIZZLE_64B);
    make_map(enc, &mp.u3, d_in[5], 3, dimf, strf, 32, 16, 3, CU_TENSOR_MAP_SWIZZLE_64B);
    fused_kernel<<<NCTA, NTHREADS, SMEM_BYTES>>>(mp, (const __nv_bfloat16*)d_in[7], (__nv_bfloat16*)d_out, 0u);
}
```

```cpp
#include <cuda_runtime.h>
#include <cuda_bf16.h>
#include <cuda.h>
#include <stdint.h>

namespace {

constexpr int kS = 2048, kD = 448, kF = 1792;
constexpr int NTHREADS = 384;
constexpr int NCTA = 128;
constexpr uint32_t OFF_X = 0;
constexpr uint32_t OFF_RING = 114688;
constexpr uint32_t SLOT_BYTES = 16384;
constexpr int NSLOT = 6;
constexpr uint32_t OFF_STG = 212992;
constexpr uint32_t OFF_MISC = 229376;
constexpr uint32_t SMEM_BYTES = 232448;
constexpr uint32_t BAR_FULL = OFF_MISC, BAR_EMPTY = OFF_MISC + 48, BAR_XFULL = OFF_MISC + 96;
constexpr uint32_t BAR_W = OFF_MISC + 152, BAR_KVDONE = OFF_MISC + 160, BAR_AUX = OFF_MISC + 168, BAR_P4 = OFF_MISC + 176;
constexpr uint32_t BAR_P17 = OFF_MISC + 208;
constexpr uint32_t BAR_REFILL = OFF_MISC + 192;
constexpr uint32_t OFF_W = OFF_MISC + 256;
constexpr uint32_t SB = 1024;

__device__ __align__(128) float g_kvacc[8][2048];
__device__ unsigned int g_counter[64];

__device__ __forceinline__ void mbar_init(uint32_t bar, uint32_t cnt) {
    asm volatile("mbarrier.init.shared::cta.b64 [%0], %1;" :: "r"(bar), "r"(cnt) : "memory");
}
__device__ __forceinline__ void mbar_expect_tx(uint32_t bar, uint32_t bytes) {
    asm volatile("mbarrier.arrive.expect_tx.shared::cta.b64 _, [%0], %1;" :: "r"(bar), "r"(bytes) : "memory");
}
__device__ __forceinline__ void mbar_arrive(uint32_t bar) {
    asm volatile("mbarrier.arrive.shared::cta.b64 _, [%0];" :: "r"(bar) : "memory");
}
__device__ __forceinline__ void mbar_arrive_cluster(uint32_t bar) {
    asm volatile("mbarrier.arrive.shared::cluster.b64 _, [%0];" :: "r"(bar) : "memory");
}
__device__ __forceinline__ void mbar_wait(uint32_t bar, uint32_t parity) {
    asm volatile("{\n"
                 ".reg .pred p;\n"
                 ".reg .u32 c;\n"
                 "mov.u32 c, 0;\n"
                 "AGAIN:\n"
                 "mbarrier.try_wait.parity.shared::cta.b64 p, [%0], %1;\n"
                 "@p bra DONE;\n"
                 "add.u32 c, c, 1;\n"
                 "setp.lt.u32 p, c, 4194304;\n"
                 "@p bra AGAIN;\n"
                 "trap;\n"
                 "DONE:\n"
                 "}" :: "r"(bar), "r"(parity) : "memory");
}
__device__ __forceinline__ uint32_t mapa(uint32_t addr, uint32_t cta) {
    uint32_t r; asm("mapa.shared::cluster.u32 %0, %1, %2;" : "=r"(r) : "r"(addr), "r"(cta)); return r;
}
__device__ __forceinline__ bool elect_one() {
    uint32_t p;
    asm volatile("{ .reg .pred P; elect.sync _|P, 0xffffffff; selp.u32 %0, 1, 0, P; }" : "=r"(p));
    return p;
}
__device__ __forceinline__ void tma2d(uint32_t dst, const CUtensorMap* m, int c0, int c1, uint32_t bar) {
    asm volatile("cp.async.bulk.tensor.2d.shared::cluster.global.mbarrier::complete_tx::bytes [%0], [%1, {%3, %4}], [%2];"
                 :: "r"(dst), "l"(m), "r"(bar), "r"(c0), "r"(c1) : "memory");
}
__device__ __forceinline__ void tma2d_mc(uint32_t dst, const CUtensorMap* m, int c0, int c1, uint32_t bar) {
    asm volatile("cp.async.bulk.tensor.2d.shared::cluster.global.mbarrier::complete_tx::bytes.multicast::cluster [%0], [%1, {%3, %4}], [%2], %5;"
                 :: "r"(dst), "l"(m), "r"(bar), "r"(c0), "r"(c1), "h"((uint16_t)3) : "memory");
}
__device__ __forceinline__ void tma3d_mc(uint32_t dst, const CUtensorMap* m, int c0, int c1, int c2, uint32_t bar) {
    asm volatile("cp.async.bulk.tensor.3d.shared::cluster.global.mbarrier::complete_tx::bytes.multicast::cluster [%0], [%1, {%3, %4, %5}], [%2], %6;"
                 :: "r"(dst), "l"(m), "r"(bar), "r"(c0), "r"(c1), "r"(c2), "h"((uint16_t)3) : "memory");
}
__device__ __forceinline__ void tma_reduce2d(const CUtensorMap* m, uint32_t src, int c0, int c1) {
    asm volatile("cp.reduce.async.bulk.tensor.2d.global.shared::cta.add.bulk_group [%0, {%2, %3}], [%1];"
                 :: "l"(m), "r"(src), "r"(c0), "r"(c1) : "memory");
}
__device__ __forceinline__ void bulk_reduce_f32(float* dst, uint32_t src, uint32_t bytes) {
    asm volatile("cp.reduce.async.bulk.global.shared::cta.bulk_group.add.f32 [%0], [%1], %2;" :: "l"(dst), "r"(src), "r"(bytes) : "memory");
}
__device__ __forceinline__ bool mbar_try(uint32_t bar, uint32_t parity) {
    uint32_t ok;
    asm volatile("{ .reg .pred p; mbarrier.test_wait.parity.shared::cta.b64 p, [%1], %2; selp.u32 %0, 1, 0, p; }"
                 : "=r"(ok) : "r"(bar), "r"(parity) : "memory");
    return ok;
}
__device__ __forceinline__ void prefetch_map(const CUtensorMap* m) {
    asm volatile("prefetch.tensormap [%0];" :: "l"(m) : "memory");
}
__device__ __forceinline__ void wg_fence() { asm volatile("wgmma.fence.sync.aligned;" ::: "memory"); }
__device__ __forceinline__ void wg_commit() { asm volatile("wgmma.commit_group.sync.aligned;" ::: "memory"); }
template <int N> __device__ __forceinline__ void wg_wait() { asm volatile("wgmma.wait_group.sync.aligned %0;" :: "n"(N) : "memory"); }
template <int N> __device__ __forceinline__ void reg_fence(float (&d)[N]) {
#pragma unroll
    for (int i = 0; i < N; i++) asm volatile("" : "+f"(d[i]) :: "memory");
}
template <int N> __device__ __forceinline__ void reg_fence(uint32_t (&d)[N]) {
#pragma unroll
    for (int i = 0; i < N; i++) asm volatile("" : "+r"(d[i]) :: "memory");
}
template <int LO, int HI, int N> __device__ __forceinline__ void reg_fence_part(uint32_t (&d)[N]) {
#pragma unroll
    for (int i = LO; i < HI; i++) asm volatile("" : "+r"(d[i]) :: "memory");
}
__device__ __forceinline__ void fence_async_smem() { asm volatile("fence.proxy.async.shared::cta;" ::: "memory"); }
template <int ID, int N> __device__ __forceinline__ void bar_sync() { asm volatile("bar.sync %0, %1;" :: "n"(ID), "n"(N) : "memory"); }
template <int ID, int N> __device__ __forceinline__ void bar_arrive() { asm volatile("bar.arrive %0, %1;" :: "n"(ID), "n"(N) : "memory"); }
__device__ __forceinline__ void ldsm4(uint32_t* r, uint32_t addr) {
    asm volatile("ldmatrix.sync.aligned.m8n8.x4.shared.b16 {%0, %1, %2, %3}, [%4];"
                 : "=r"(r[0]), "=r"(r[1]), "=r"(r[2]), "=r"(r[3]) : "r"(addr) : "memory");
}
__device__ __forceinline__ void stsm4(uint32_t addr, uint32_t r0, uint32_t r1, uint32_t r2, uint32_t r3) {
    asm volatile("stmatrix.sync.aligned.m8n8.x4.shared.b16 [%0], {%1, %2, %3, %4};"
                 :: "r"(addr), "r"(r0), "r"(r1), "r"(r2), "r"(r3) : "memory");
}
__device__ __forceinline__ uint32_t lds32(uint32_t addr) {
    uint32_t r; asm volatile("ld.shared.u32 %0, [%1];" : "=r"(r) : "r"(addr)); return r;
}
__device__ __forceinline__ float4 lds128f(uint32_t addr) {
    float4 r; asm volatile("ld.shared.v4.f32 {%0, %1, %2, %3}, [%4];" : "=f"(r.x), "=f"(r.y), "=f"(r.z), "=f"(r.w) : "r"(addr)); return r;
}
__device__ __forceinline__ uint32_t clock32() { uint32_t t; asm volatile("mov.u32 %0, %%clock;" : "=r"(t)); return t; }
__device__ __forceinline__ uint32_t pack_bf16(float lo, float hi) {
    uint32_t r; asm("cvt.rn.bf16x2.f32 %0, %1, %2;" : "=r"(r) : "f"(hi), "f"(lo)); return r;
}
__device__ __forceinline__ uint32_t pack_relu_bf16(float lo, float hi) {
    uint32_t r; asm("cvt.rn.relu.bf16x2.f32 %0, %1, %2;" : "=r"(r) : "f"(hi), "f"(lo)); return r;
}
__device__ __forceinline__ uint32_t mul_bf16x2(uint32_t a, uint32_t b) {
    uint32_t r; asm("mul.rn.bf16x2 %0, %1, %2;" : "=r"(r) : "r"(a), "r"(b)); return r;
}
__device__ __forceinline__ float phi(float t, float log2e) {
    float e;
    asm("ex2.approx.ftz.f32 %0, %1;" : "=f"(e) : "f"(fminf(t * log2e, 0.f)));
    return e + (fmaxf(t, 0.f) + 1e-6f);
}
__device__ __forceinline__ float after_issue(float v, uint32_t zero) {
    return __uint_as_float(__float_as_uint(v) | (clock32() & zero));
}
constexpr float kLog2e = 1.4426950408889634f;
__device__ __forceinline__ float rcp(float x) { float r; asm("rcp.approx.ftz.f32 %0, %1;" : "=f"(r) : "f"(x)); return r; }
__device__ __forceinline__ float bf_lo(uint32_t v) { return __uint_as_float(v << 16); }
__device__ __forceinline__ float bf_hi(uint32_t v) { return __uint_as_float(v & 0xffff0000u); }
constexpr uint32_t HI128 = (1024 >> 4) | (1u << 30);
constexpr uint32_t HI64 = (512 >> 4) | (2u << 30);
constexpr uint32_t LO128 = 1u << 16, LO64 = (1024u >> 4) << 16, LO128X2 = (2048u >> 4) << 16;
constexpr uint32_t QB = 16 * 112;
constexpr uint32_t TX1 = 2 * (2 * QB + 4096), TX2 = 2 * (QB + 4096), TX3 = 12288;
__device__ __forceinline__ void grid_arrive(unsigned int* c) {
    asm volatile("fence.acq_rel.gpu;" ::: "memory");
    asm volatile("red.relaxed.gpu.global.add.u32 [%0], 1;" :: "l"(c) : "memory");
}
__device__ __forceinline__ void grid_wait(const unsigned int* c, unsigned int target) {
    unsigned int v; int it = 0;
    do {
        asm volatile("ld.relaxed.gpu.global.u32 %0, [%1];" : "=r"(v) : "l"(c) : "memory");
        if (++it > (1 << 22)) asm volatile("trap;");
    } while ((int)(v - target) < 0);
    asm volatile("ld.acquire.gpu.global.u32 %0, [%1];" : "=r"(v) : "l"(c) : "memory");
}

template <uint32_t HI>
__device__ __forceinline__ void wgmma_rs56(float (&d)[28], uint32_t a0, uint32_t a1, uint32_t a2, uint32_t a3, uint32_t db, int sd) {
    asm volatile("{ .reg .pred p; .reg .b64 db; setp.ne.b32 p, %33, 0; mov.b64 db, {%32, %34};\n"
        "wgmma.mma_async.sync.aligned.m64n56k16.f32.bf16.bf16 {"
        "%0, %1, %2, %3, %4, %5, %6, %7, %8, %9, %10, %11, %12, %13, %14, %15, "
        "%16, %17, %18, %19, %20, %21, %22, %23, %24, %25, %26, %27"
        "}, {%28, %29, %30, %31}, db, p, 1, 1, 1; }"
        : "+f"(d[0]), "+f"(d[1]), "+f"(d[2]), "+f"(d[3]), "+f"(d[4]), "+f"(d[5]), "+f"(d[6]), "+f"(d[7]),
          "+f"(d[8]), "+f"(d[9]), "+f"(d[10]), "+f"(d[11]), "+f"(d[12]), "+f"(d[13]), "+f"(d[14]), "+f"(d[15]),
          "+f"(d[16]), "+f"(d[17]), "+f"(d[18]), "+f"(d[19]), "+f"(d[20]), "+f"(d[21]), "+f"(d[22]), "+f"(d[23]),
          "+f"(d[24]), "+f"(d[25]), "+f"(d[26]), "+f"(d[27])
        : "r"(a0), "r"(a1), "r"(a2), "r"(a3), "r"(db), "r"(sd), "n"(HI));
}
template <uint32_t HI>
__device__ __forceinline__ void wgmma_rs64(float (&d)[32], uint32_t a0, uint32_t a1, uint32_t a2, uint32_t a3, uint32_t db, int sd) {
    asm volatile("{ .reg .pred p; .reg .b64 db; setp.ne.b32 p, %37, 0; mov.b64 db, {%36, %38};\n"
        "wgmma.mma_async.sync.aligned.m64n64k16.f32.bf16.bf16 {"
        "%0, %1, %2, %3, %4, %5, %6, %7, %8, %9, %10, %11, %12, %13, %14, %15, "
        "%16, %17, %18, %19, %20, %21, %22, %23, %24, %25, %26, %27, %28, %29, %30, %31"
        "}, {%32, %33, %34, %35}, db, p, 1, 1, 1; }"
        : "+f"(d[0]), "+f"(d[1]), "+f"(d[2]), "+f"(d[3]), "+f"(d[4]), "+f"(d[5]), "+f"(d[6]), "+f"(d[7]),
          "+f"(d[8]), "+f"(d[9]), "+f"(d[10]), "+f"(d[11]), "+f"(d[12]), "+f"(d[13]), "+f"(d[14]), "+f"(d[15]),
          "+f"(d[16]), "+f"(d[17]), "+f"(d[18]), "+f"(d[19]), "+f"(d[20]), "+f"(d[21]), "+f"(d[22]), "+f"(d[23]),
          "+f"(d[24]), "+f"(d[25]), "+f"(d[26]), "+f"(d[27]), "+f"(d[28]), "+f"(d[29]), "+f"(d[30]), "+f"(d[31])
        : "r"(a0), "r"(a1), "r"(a2), "r"(a3), "r"(db), "r"(sd), "n"(HI));
}
template <uint32_t HI>
__device__ __forceinline__ void wgmma_rs128(float (&d)[64], uint32_t a0, uint32_t a1, uint32_t a2, uint32_t a3, uint32_t db, int sd) {
    asm volatile("{ .reg .pred p; .reg .b64 db; setp.ne.b32 p, %69, 0; mov.b64 db, {%68, %70};\n"
        "wgmma.mma_async.sync.aligned.m64n128k16.f32.bf16.bf16 {"
        "%0, %1, %2, %3, %4, %5, %6, %7, %8, %9, %10, %11, %12, %13, %14, %15, "
        "%16, %17, %18, %19, %20, %21, %22, %23, %24, %25, %26, %27, %28, %29, %30, %31, "
        "%32, %33, %34, %35, %36, %37, %38, %39, %40, %41, %42, %43, %44, %45, %46, %47, "
        "%48, %49, %50, %51, %52, %53, %54, %55, %56, %57, %58, %59, %60, %61, %62, %63"
        "}, {%64, %65, %66, %67}, db, p, 1, 1, 1; }"
        : "+f"(d[0]), "+f"(d[1]), "+f"(d[2]), "+f"(d[3]), "+f"(d[4]), "+f"(d[5]), "+f"(d[6]), "+f"(d[7]),
          "+f"(d[8]), "+f"(d[9]), "+f"(d[10]), "+f"(d[11]), "+f"(d[12]), "+f"(d[13]), "+f"(d[14]), "+f"(d[15]),
          "+f"(d[16]), "+f"(d[17]), "+f"(d[18]), "+f"(d[19]), "+f"(d[20]), "+f"(d[21]), "+f"(d[22]), "+f"(d[23]),
          "+f"(d[24]), "+f"(d[25]), "+f"(d[26]), "+f"(d[27]), "+f"(d[28]), "+f"(d[29]), "+f"(d[30]), "+f"(d[31]),
          "+f"(d[32]), "+f"(d[33]), "+f"(d[34]), "+f"(d[35]), "+f"(d[36]), "+f"(d[37]), "+f"(d[38]), "+f"(d[39]),
          "+f"(d[40]), "+f"(d[41]), "+f"(d[42]), "+f"(d[43]), "+f"(d[44]), "+f"(d[45]), "+f"(d[46]), "+f"(d[47]),
          "+f"(d[48]), "+f"(d[49]), "+f"(d[50]), "+f"(d[51]), "+f"(d[52]), "+f"(d[53]), "+f"(d[54]), "+f"(d[55]),
          "+f"(d[56]), "+f"(d[57]), "+f"(d[58]), "+f"(d[59]), "+f"(d[60]), "+f"(d[61]), "+f"(d[62]), "+f"(d[63])
        : "r"(a0), "r"(a1), "r"(a2), "r"(a3), "r"(db), "r"(sd), "n"(HI));
}
template <uint32_t HI>
__device__ __forceinline__ void wgmma_rs184(float (&d)[92], uint32_t a0, uint32_t a1, uint32_t a2, uint32_t a3, uint32_t db, int sd) {
    asm volatile("{ .reg .pred p; .reg .b64 db; setp.ne.b32 p, %97, 0; mov.b64 db, {%96, %98};\n"
        "wgmma.mma_async.sync.aligned.m64n184k16.f32.bf16.bf16 {"
        "%0, %1, %2, %3, %4, %5, %6, %7, %8, %9, %10, %11, %12, %13, %14, %15, "
        "%16, %17, %18, %19, %20, %21, %22, %23, %24, %25, %26, %27, %28, %29, %30, %31, "
        "%32, %33, %34, %35, %36, %37, %38, %39, %40, %41, %42, %43, %44, %45, %46, %47, "
        "%48, %49, %50, %51, %52, %53, %54, %55, %56, %57, %58, %59, %60, %61, %62, %63, "
        "%64, %65, %66, %67, %68, %69, %70, %71, %72, %73, %74, %75, %76, %77, %78, %79, "
        "%80, %81, %82, %83, %84, %85, %86, %87, %88, %89, %90, %91"
        "}, {%92, %93, %94, %95}, db, p, 1, 1, 1; }"
        : "+f"(d[0]), "+f"(d[1]), "+f"(d[2]), "+f"(d[3]), "+f"(d[4]), "+f"(d[5]), "+f"(d[6]), "+f"(d[7]),
          "+f"(d[8]), "+f"(d[9]), "+f"(d[10]), "+f"(d[11]), "+f"(d[12]), "+f"(d[13]), "+f"(d[14]), "+f"(d[15]),
          "+f"(d[16]), "+f"(d[17]), "+f"(d[18]), "+f"(d[19]), "+f"(d[20]), "+f"(d[21]), "+f"(d[22]), "+f"(d[23]),
          "+f"(d[24]), "+f"(d[25]), "+f"(d[26]), "+f"(d[27]), "+f"(d[28]), "+f"(d[29]), "+f"(d[30]), "+f"(d[31]),
          "+f"(d[32]), "+f"(d[33]), "+f"(d[34]), "+f"(d[35]), "+f"(d[36]), "+f"(d[37]), "+f"(d[38]), "+f"(d[39]),
          "+f"(d[40]), "+f"(d[41]), "+f"(d[42]), "+f"(d[43]), "+f"(d[44]), "+f"(d[45]), "+f"(d[46]), "+f"(d[47]),
          "+f"(d[48]), "+f"(d[49]), "+f"(d[50]), "+f"(d[51]), "+f"(d[52]), "+f"(d[53]), "+f"(d[54]), "+f"(d[55]),
          "+f"(d[56]), "+f"(d[57]), "+f"(d[58]), "+f"(d[59]), "+f"(d[60]), "+f"(d[61]), "+f"(d[62]), "+f"(d[63]),
          "+f"(d[64]), "+f"(d[65]), "+f"(d[66]), "+f"(d[67]), "+f"(d[68]), "+f"(d[69]), "+f"(d[70]), "+f"(d[71]),
          "+f"(d[72]), "+f"(d[73]), "+f"(d[74]), "+f"(d[75]), "+f"(d[76]), "+f"(d[77]), "+f"(d[78]), "+f"(d[79]),
          "+f"(d[80]), "+f"(d[81]), "+f"(d[82]), "+f"(d[83]), "+f"(d[84]), "+f"(d[85]), "+f"(d[86]), "+f"(d[87]),
          "+f"(d[88]), "+f"(d[89]), "+f"(d[90]), "+f"(d[91])
        : "r"(a0), "r"(a1), "r"(a2), "r"(a3), "r"(db), "r"(sd), "n"(HI));
}
template <uint32_t HI>
__device__ __forceinline__ void wgmma_rs192(float (&d)[96], uint32_t a0, uint32_t a1, uint32_t a2, uint32_t a3, uint32_t db, int sd) {
    asm volatile("{ .reg .pred p; .reg .b64 db; setp.ne.b32 p, %101, 0; mov.b64 db, {%100, %102};\n"
        "wgmma.mma_async.sync.aligned.m64n192k16.f32.bf16.bf16 {"
        "%0, %1, %2, %3, %4, %5, %6, %7, %8, %9, %10, %11, %12, %13, %14, %15, "
        "%16, %17, %18, %19, %20, %21, %22, %23, %24, %25, %26, %27, %28, %29, %30, %31, "
        "%32, %33, %34, %35, %36, %37, %38, %39, %40, %41, %42, %43, %44, %45, %46, %47, "
        "%48, %49, %50, %51, %52, %53, %54, %55, %56, %57, %58, %59, %60, %61, %62, %63, "
        "%64, %65, %66, %67, %68, %69, %70, %71, %72, %73, %74, %75, %76, %77, %78, %79, "
        "%80, %81, %82, %83, %84, %85, %86, %87, %88, %89, %90, %91, %92, %93, %94, %95"
        "}, {%96, %97, %98, %99}, db, p, 1, 1, 1; }"
        : "+f"(d[0]), "+f"(d[1]), "+f"(d[2]), "+f"(d[3]), "+f"(d[4]), "+f"(d[5]), "+f"(d[6]), "+f"(d[7]),
          "+f"(d[8]), "+f"(d[9]), "+f"(d[10]), "+f"(d[11]), "+f"(d[12]), "+f"(d[13]), "+f"(d[14]), "+f"(d[15]),
          "+f"(d[16]), "+f"(d[17]), "+f"(d[18]), "+f"(d[19]), "+f"(d[20]), "+f"(d[21]), "+f"(d[22]), "+f"(d[23]),
          "+f"(d[24]), "+f"(d[25]), "+f"(d[26]), "+f"(d[27]), "+f"(d[28]), "+f"(d[29]), "+f"(d[30]), "+f"(d[31]),
          "+f"(d[32]), "+f"(d[33]), "+f"(d[34]), "+f"(d[35]), "+f"(d[36]), "+f"(d[37]), "+f"(d[38]), "+f"(d[39]),
          "+f"(d[40]), "+f"(d[41]), "+f"(d[42]), "+f"(d[43]), "+f"(d[44]), "+f"(d[45]), "+f"(d[46]), "+f"(d[47]),
          "+f"(d[48]), "+f"(d[49]), "+f"(d[50]), "+f"(d[51]), "+f"(d[52]), "+f"(d[53]), "+f"(d[54]), "+f"(d[55]),
          "+f"(d[56]), "+f"(d[57]), "+f"(d[58]), "+f"(d[59]), "+f"(d[60]), "+f"(d[61]), "+f"(d[62]), "+f"(d[63]),
          "+f"(d[64]), "+f"(d[65]), "+f"(d[66]), "+f"(d[67]), "+f"(d[68]), "+f"(d[69]), "+f"(d[70]), "+f"(d[71]),
          "+f"(d[72]), "+f"(d[73]), "+f"(d[74]), "+f"(d[75]), "+f"(d[76]), "+f"(d[77]), "+f"(d[78]), "+f"(d[79]),
          "+f"(d[80]), "+f"(d[81]), "+f"(d[82]), "+f"(d[83]), "+f"(d[84]), "+f"(d[85]), "+f"(d[86]), "+f"(d[87]),
          "+f"(d[88]), "+f"(d[89]), "+f"(d[90]), "+f"(d[91]), "+f"(d[92]), "+f"(d[93]), "+f"(d[94]), "+f"(d[95])
        : "r"(a0), "r"(a1), "r"(a2), "r"(a3), "r"(db), "r"(sd), "n"(HI));
}
template <uint32_t HI>
__device__ __forceinline__ void wgmma_ss64_tt(float (&d)[32], uint32_t da, uint32_t db, int sd) {
    asm volatile("{ .reg .pred p; .reg .b64 da, db; setp.ne.b32 p, %34, 0; mov.b64 da, {%32, %35}; mov.b64 db, {%33, %35};\n"
        "wgmma.mma_async.sync.aligned.m64n64k16.f32.bf16.bf16 {"
        "%0, %1, %2, %3, %4, %5, %6, %7, %8, %9, %10, %11, %12, %13, %14, %15, "
        "%16, %17, %18, %19, %20, %21, %22, %23, %24, %25, %26, %27, %28, %29, %30, %31"
        "}, da, db, p, 1, 1, 1, 1; }"
        : "+f"(d[0]), "+f"(d[1]), "+f"(d[2]), "+f"(d[3]), "+f"(d[4]), "+f"(d[5]), "+f"(d[6]), "+f"(d[7]),
          "+f"(d[8]), "+f"(d[9]), "+f"(d[10]), "+f"(d[11]), "+f"(d[12]), "+f"(d[13]), "+f"(d[14]), "+f"(d[15]),
          "+f"(d[16]), "+f"(d[17]), "+f"(d[18]), "+f"(d[19]), "+f"(d[20]), "+f"(d[21]), "+f"(d[22]), "+f"(d[23]),
          "+f"(d[24]), "+f"(d[25]), "+f"(d[26]), "+f"(d[27]), "+f"(d[28]), "+f"(d[29]), "+f"(d[30]), "+f"(d[31])
        : "r"(da), "r"(db), "r"(sd), "n"(HI));
}

__host__ __device__ constexpr uint32_t p4_pack(int n) { return (n / 3) * 36864 + (n % 3) * 14336; }
__host__ __device__ constexpr uint32_t p4_off(int n) {
    return n < 6 ? OFF_X + p4_pack(n) : n < 14 ? OFF_RING + p4_pack(n - 6) : n == 14 ? OFF_X + p4_pack(6)
                 : n == 17 ? OFF_STG + 8192 : n == 20 ? OFF_X + p4_pack(2) : OFF_X + p4_pack(n - 15);
}
__host__ __device__ constexpr uint32_t p4_bar(int n) {
    return n < 6 ? BAR_XFULL + 8 * n : n < 12 ? BAR_FULL + 8 * (n - 6) : n < 14 ? BAR_P4 + 8 * (n - 12)
                 : n == 14 ? BAR_XFULL + 48 : n == 17 ? BAR_P17 : n == 20 ? BAR_XFULL + 16 : BAR_XFULL + 8 * (n - 15);
}
__host__ __device__ constexpr uint32_t p4_par(int n) { return (n < 12 || n == 14) ? 1 : 0; }
constexpr uint32_t OFF_OUT = OFF_X + 5 * 16384;
static_assert(p4_off(7) == p4_off(6) + 14336 && p4_off(13) == p4_off(12) + 14336 && p4_off(16) == p4_off(15) + 14336, "Wd halves");
static_assert(p4_off(13) + 14336 <= OFF_STG + 8192 && p4_off(14) + 8192 == OFF_OUT, "pass-4 layout");

struct Ring {
    uint32_t slot, phase;
    __device__ __forceinline__ void advance() { if (++slot == NSLOT) { slot = 0; phase ^= 1; } }
};

struct Maps { CUtensorMap x, kv, q, g4, g3, u4, u3, d, o, out; };

__global__ void __cluster_dims__(2, 1, 1) __launch_bounds__(NTHREADS, 1)
fused_kernel(const __grid_constant__ Maps mp, const __nv_bfloat16* __restrict__ gate_w, __nv_bfloat16* __restrict__ out,
             uint32_t zero)
{
    extern __shared__ __align__(1024) unsigned char smem[];
    const uint32_t sb = (uint32_t)__cvta_generic_to_shared(smem);
    const int tid = threadIdx.x, warp = tid >> 5, lane = tid & 31;
    const int rank = blockIdx.x & 1, j = blockIdx.x >> 4;
    const int row0 = (blockIdx.x & 15) * 128;
    const int par = j & 1;
    const int g4i = (7 * j + 3 * par) >> 1;

    if (warp == 2) {
        if (elect_one()) {
            mbar_init(sb + BAR_W, 1);
            asm volatile("fence.mbarrier_init.release.cluster;" ::: "memory");
            mbar_expect_tx(sb + BAR_W, 896);
            asm volatile("cp.async.bulk.shared::cluster.global.mbarrier::complete_tx::bytes [%0], [%1], 896, [%2];"
                         :: "r"(sb + OFF_W), "l"(gate_w), "r"(sb + BAR_W) : "memory");
        }
        __syncwarp();
    } else if (warp == 11) {
        if (elect_one()) {
            #pragma unroll
            for (int s = 0; s < NSLOT; s++) mbar_init(sb + BAR_EMPTY + 8 * s, 4);
            mbar_init(sb + BAR_P4, 1);
            mbar_init(sb + BAR_P4 + 8, 1);
            mbar_init(sb + BAR_P17, 1);
            mbar_init(sb + BAR_REFILL, 4);
            mbar_init(sb + BAR_REFILL + 8, 4);
            asm volatile("fence.mbarrier_init.release.cluster;" ::: "memory");
        }
        __syncwarp();
    } else if (warp == 10) {
        if (elect_one()) {
            #pragma unroll
            for (int s = 1; s < 7; s++) mbar_init(sb + BAR_XFULL + 8 * s, 1);
            mbar_init(sb + BAR_KVDONE, 8);
            mbar_init(sb + BAR_AUX, 3);
            asm volatile("fence.mbarrier_init.release.cluster;" ::: "memory");
            if ((sb & 0xFFFFFF) != SB) asm volatile("trap;");
        }
        __syncwarp();
    } else if (warp == 8) {
        if (elect_one()) {
            #pragma unroll
            for (int s = 0; s < NSLOT; s++) mbar_init(sb + BAR_FULL + 8 * s, 1);
            asm volatile("fence.mbarrier_init.release.cluster;" ::: "memory");
            mbar_expect_tx(sb + BAR_FULL, TX1);
        }
        __syncwarp();
    } else if (warp == 9) {
        if (elect_one()) {
            prefetch_map(&mp.x);
            mbar_init(sb + BAR_XFULL, 1);
            mbar_expect_tx(sb + BAR_XFULL, 16384);
            tma2d(sb + OFF_X, &mp.x, 0, row0, sb + BAR_XFULL);
            asm volatile("fence.mbarrier_init.release.cluster;" ::: "memory");
        }
        __syncwarp();
    }
    asm volatile("barrier.cluster.arrive.relaxed.aligned;" ::: "memory");
    if (warp == 8) {
        if (elect_one()) { prefetch_map(&mp.kv); prefetch_map(&mp.g4); }
        __syncwarp();
    }
    asm volatile("barrier.cluster.wait.aligned;" ::: "memory");
    if (warp == 8) {
        if (elect_one()) {
            tma3d_mc(sb + OFF_RING + rank * 8192 + 4096, &mp.kv, 56 * j, 16 * rank, 1, sb + BAR_FULL);
            tma3d_mc(sb + OFF_RING + rank * 8192, &mp.g4, 0, 16 * rank, g4i, sb + BAR_FULL);
        }
        __syncwarp();
    }

    if (warp >= 8) {
        asm volatile("setmaxnreg.dec.sync.aligned.u32 40;");
        if (warp == 8) {
            if (elect_one()) {
                Ring r{1, 1};
                auto acquire = [&](uint32_t bytes) -> uint32_t {
                    mbar_wait(sb + BAR_EMPTY + 8 * r.slot, r.phase);
                    mbar_expect_tx(sb + BAR_FULL + 8 * r.slot, bytes);
                    return sb + OFF_RING + r.slot * SLOT_BYTES;
                };
                #pragma unroll 1
                for (int s = 1; s < 14; s++) {
                    const uint32_t dst = acquire(TX1) + rank * 8192;
                    tma3d_mc(dst + 4096, &mp.kv, 56 * j, 32 * s + 16 * rank, 1, sb + BAR_FULL + 8 * r.slot);
                    tma3d_mc(dst, &mp.g4, 0, 32 * s + 16 * rank, g4i, sb + BAR_FULL + 8 * r.slot);
                    r.advance();
                    if ((s & 1) && s < 12) {
                        const int n = (s >> 1) + 1;
                        mbar_expect_tx(sb + BAR_XFULL + 8 * n, 16384);
                        tma2d(sb + OFF_X + n * 16384, &mp.x, 64 * n, row0, sb + BAR_XFULL + 8 * n);
                    }
                    if (s == 5) {
                        prefetch_map(&mp.q); prefetch_map(&mp.u4); prefetch_map(&mp.g3); prefetch_map(&mp.u3);
                        prefetch_map(&mp.d); prefetch_map(&mp.o); prefetch_map(&mp.out);
                    }
                }
                #pragma unroll 1
                for (int s = 0; s < 14; s++) {
                    const uint32_t dst = acquire(TX2) + rank * 6144;
                    tma3d_mc(dst, &mp.q, 56 * j, 32 * s + 16 * rank, 0, sb + BAR_FULL + 8 * r.slot);
                    tma3d_mc(dst + 2048, &mp.u4, 0, 32 * s + 16 * rank, g4i, sb + BAR_FULL + 8 * r.slot);
                    r.advance();
                }
                const int cfirst = j == 7 ? 0 : j;
                auto load4 = [&](int n) {
                    int c = cfirst + n / 3;
                    if (c >= 7) c -= 7;
                    mbar_expect_tx(sb + p4_bar(n), n % 3 == 2 ? 8192 : 14336);
                    if (n % 3 == 2) tma2d_mc(sb + p4_off(n) + rank * 4096, &mp.o, 64 * c, 56 * j + 32 * rank, sb + p4_bar(n));
                    else tma2d_mc(sb + p4_off(n) + rank * 7168, &mp.d, 64 * c, 224 * j + 112 * (n % 3) + 56 * rank, sb + p4_bar(n));
                };
                #pragma unroll 1
                for (int s = 0; s < 14; s++) {
                    const uint32_t dst = acquire(TX3) + rank * 6144;
                    tma3d_mc(dst, &mp.g3, 0, 32 * s + 16 * rank, 7 * j + 4 - 4 * par, sb + BAR_FULL + 8 * r.slot);
                    tma3d_mc(dst + 3072, &mp.u3, 0, 32 * s + 16 * rank, 7 * j + 4 - 4 * par, sb + BAR_FULL + 8 * r.slot);
                    r.advance();
                    if (s == 7) load4(0);
                    if (s == 9) load4(1);
                    if (s == 11) load4(2);
                    if (s == 13) { load4(3); load4(4); }
                }
                mbar_wait(sb + BAR_EMPTY, 0);      load4(6);
                mbar_wait(sb + BAR_EMPTY + 8, 0);  load4(5); load4(7); load4(14);
                mbar_wait(sb + BAR_EMPTY + 16, 0); load4(8);
                mbar_wait(sb + BAR_EMPTY + 24, 0); load4(9); load4(10);
                mbar_wait(sb + BAR_EMPTY + 32, 0); load4(11);
                load4(17);
                mbar_wait(sb + BAR_EMPTY + 40, 0); load4(12);
                mbar_wait(sb + BAR_AUX, 0);        load4(13);
                mbar_wait(sb + BAR_REFILL, 0);     load4(15); load4(16); load4(20);
                mbar_wait(sb + BAR_REFILL + 8, 0); load4(18); load4(19);
            }
        } else {
            const int ht = tid - 288;
            unsigned int cnt0;
            asm volatile("ld.relaxed.gpu.global.u32 %0, [%1];" : "=r"(cnt0) : "l"(&g_counter[32]) : "memory");
            const unsigned int target = ((cnt0 >> 7) + 1) << 7;
            if (warp == 9) {
                reinterpret_cast<float4*>(&g_kvacc[0][0])[blockIdx.x * 32 + lane] = make_float4(0.f, 0.f, 0.f, 0.f);
                asm volatile("fence.proxy.async.global;" ::: "memory");
                __syncwarp();
                if (lane == 0) grid_arrive(&g_counter[0]);
                mbar_wait(sb + BAR_XFULL + 8 * 6, 0);
                uint4* o = reinterpret_cast<uint4*>(out) + blockIdx.x * 896 + lane;
                #pragma unroll 4
                for (int q = 0; q < 28; q++) o[q * 32] = make_uint4(0, 0, 0, 0);
                asm volatile("fence.proxy.async.global;" ::: "memory");
                __syncwarp();
                if (lane == 0) {
                    asm volatile("fence.acq_rel.gpu;" ::: "memory");
                    grid_wait(&g_counter[0], target);
                }
                __syncwarp();
            }
            mbar_wait(sb + BAR_KVDONE, 0);
            {
                #pragma unroll
                for (int i0 = 0; i0 < 5; i0 += 2) {
                    float4 pa[2], pb[2];
                    #pragma unroll
                    for (int i = 0; i < 2 && i0 + i < 5; i++) {
                        const int q = min(ht + 96 * (i0 + i), 447);
                        pa[i] = lds128f(sb + OFF_STG + q * 16); pb[i] = lds128f(sb + OFF_STG + 8192 + q * 16);
                    }
                    #pragma unroll
                    for (int i = 0; i < 2 && i0 + i < 5; i++) {
                        const int q = ht + 96 * (i0 + i);
                        if (q < 448) asm volatile("st.shared.v4.f32 [%0], {%1, %2, %3, %4};" :: "r"(sb + OFF_STG + q * 16),
                            "f"(pa[i].x + pb[i].x), "f"(pa[i].y + pb[i].y), "f"(pa[i].z + pb[i].z), "f"(pa[i].w + pb[i].w) : "memory");
                    }
                }
                fence_async_smem();
            }
            bar_sync<3, 96>();
            if (warp == 9) {
                if (elect_one()) {
                    bulk_reduce_f32(&g_kvacc[j][0], sb + OFF_STG, 7168);
                    asm volatile("cp.async.bulk.commit_group;" ::: "memory");
                    asm volatile("cp.async.bulk.wait_group 0;" ::: "memory");
                    asm volatile("red.relaxed.gpu.global.add.u32 [%0], 1;" :: "l"(&g_counter[32]) : "memory");
                }
            }
            __syncwarp();
            #pragma unroll
            for (int i = 0; i < 3; i++) {
                const int q = ht + 96 * i;
                const int d = q < 168 ? q / 3 : 56 + ((q - 168) >> 3);
                const int c = q < 168 ? (q - 3 * d + (d < 28 ? 4 : 0)) : (q & 7);
                if (q < 232) asm volatile("st.shared.v4.u32 [%0], {%1, %1, %1, %1};" :: "r"(sb + OFF_STG + 8192 + d * 128 + ((c ^ (d & 7)) << 4)), "r"(0) : "memory");
            }
            uint32_t plan[3];
            #pragma unroll
            for (int i = 0; i < 3; i++) {
                const int q = min(ht + 96 * i, 279), d = q / 5, m = q - 5 * d;
                const bool h0 = d < 28;
                const int c = m == 4 ? 7 : (h0 ? m : m + 3), pc = m < 4 ? m : (h0 ? 3 : 0);
                const int kind = m == 4 ? (h0 ? 3 : 4) : c == 3 ? (h0 ? 1 : 2) : 0;
                plan[i] = (d * 128 + ((c ^ (d & 7)) << 4)) | ((d * 4 + (pc ^ (d & 3))) << 13) | (kind << 23);
                asm volatile("" : "+r"(plan[i]));
            }
            if (lane == 0) grid_wait(&g_counter[32], target);
            __syncwarp();
            const float4* src = reinterpret_cast<const float4*>(&g_kvacc[j][0]);
            float4 va[3], vb[3];
            #pragma unroll
            for (int i = 0; i < 3; i++) {
                const float4* p = src + ((plan[i] >> 12) & 0x7fe);
                va[i] = __ldcg(p); vb[i] = __ldcg(p + 1);
            }
            #pragma unroll
            for (int i = 0; i < 3; i++) {
                const uint32_t kind = plan[i] >> 23;
                uint32_t w0 = pack_bf16(va[i].x, va[i].y), w1 = pack_bf16(va[i].z, va[i].w);
                uint32_t w2 = pack_bf16(vb[i].x, vb[i].y), w3 = pack_bf16(vb[i].z, vb[i].w);
                if (kind == 3) w0 = w2 & 0xffffu;
                if (kind == 4) w0 <<= 16;
                if (kind == 2) w0 = 0u;
                if (kind >= 2) w1 = 0u;
                if (kind != 0 && kind != 2) w2 = w3 = 0u;
                if (i < 2 || ht < 88)
                    asm volatile("st.shared.v4.u32 [%0], {%1, %2, %3, %4};"
                                 :: "r"(sb + OFF_STG + 8192 + (plan[i] & 0x1fff)), "r"(w0), "r"(w1), "r"(w2), "r"(w3) : "memory");
            }
            fence_async_smem();
            __syncwarp();
            if (lane == 0) mbar_arrive(sb + BAR_AUX);
        }
    } else {
        asm volatile("setmaxnreg.inc.sync.aligned.u32 232;");
        const int wg = warp >> 2, w4 = warp & 3;
        const int q4 = lane & 3, g8 = lane >> 2;
        const uint32_t lx = ((lane >> 4) ^ (lane & 7)) << 4;
        const uint32_t xa = sb + OFF_X + (warp * 16 + (lane & 15)) * 128;
        const uint32_t empty_dst = mapa(sb + BAR_EMPTY, w4 & 1);
        const bool signaller = lane == 0 && w4 < 2;
        constexpr uint32_t dsb = SB >> 4;
        Ring r{0, 0};
        uint32_t cur = 0, old = 0;
        bool ready = false;
        auto release = [&](uint32_t slot) { if (signaller) mbar_arrive_cluster(empty_dst + 8 * slot); };
        auto turn_wait = [&]() { if (wg == 0) bar_sync<6, 256>(); else bar_sync<7, 256>(); };
        auto turn_pass = [&]() { if (wg == 0) bar_arrive<7, 256>(); else bar_arrive<6, 256>(); };
        auto begin = [&]() -> uint32_t {
            if (!ready) mbar_wait(sb + BAR_FULL + 8 * r.slot, r.phase);
            wg_fence();
            return dsb + (OFF_RING >> 4) + r.slot * (SLOT_BYTES >> 4);
        };
        auto commit = [&]() { wg_commit(); old = cur; cur = r.slot; r.advance(); };
        auto retire = [&]() { wg_wait<1>(); release(old); };
        auto peek = [&]() { ready = mbar_try(sb + BAR_FULL + 8 * r.slot, r.phase); };
        uint32_t a0[8], a1[8];
        auto load_a0 = [&](int kc) { ldsm4(a0, xa + kc * 16384 + lx); ldsm4(a0 + 4, xa + kc * 16384 + (lx ^ 32)); };
        auto load_a1 = [&](int kc) { ldsm4(a1, xa + kc * 16384 + (lx ^ 64)); ldsm4(a1 + 4, xa + kc * 16384 + (lx ^ 96)); };

        uint32_t hp[56];
        float g0, g1, av[28], agk[92];
        {
            float d0 = 0.f, d1 = 0.f, d2 = 0.f, d3 = 0.f;
            uint32_t w0[4], w1[4];
            auto issue1 = [&](uint32_t (&a)[8], int sd) {
                const uint32_t b = begin();
                wgmma_rs184<HI128>(agk, a[0], a[1], a[2], a[3], b + LO128X2, sd);
                wgmma_rs56<HI128>(av, a[0], a[1], a[2], a[3], b + LO128 + 384, sd);
                wgmma_rs184<HI128>(agk, a[4], a[5], a[6], a[7], b + LO128X2 + 512, 1);
                wgmma_rs56<HI128>(av, a[4], a[5], a[6], a[7], b + LO128 + 896, 1);
                commit();
            };
            auto issue1s = [&](uint32_t (&a)[8]) {
                const uint32_t b = begin();
                wgmma_rs184<HI128>(agk, a[0], a[1], a[2], a[3], b + LO128X2, 1);
                wgmma_rs184<HI128>(agk, a[4], a[5], a[6], a[7], b + LO128X2 + 512, 1);
                wg_commit();
                wgmma_rs56<HI128>(av, a[0], a[1], a[2], a[3], b + LO128 + 384, 1);
                wgmma_rs56<HI128>(av, a[4], a[5], a[6], a[7], b + LO128 + 896, 1);
                commit();
            };
            auto load_w = [&](uint32_t (&w)[4], int s) {
                #pragma unroll
                for (int e = 0; e < 4; e++) w[e] = lds32(sb + OFF_W + s * 64 + q4 * 4 + e * 16);
            };
            auto dot = [&](uint32_t (&a)[8], uint32_t (&w)[4]) {
                #pragma unroll
                for (int e = 0; e < 4; e++) {
                    const uint32_t p0 = mul_bf16x2(a[2 * e], w[e]), p1 = mul_bf16x2(a[2 * e + 1], w[e]);
                    d0 += bf_lo(p0); d2 += bf_hi(p0); d1 += bf_lo(p1); d3 += bf_hi(p1);
                }
                asm volatile("" : "+f"(d0), "+f"(d1), "+f"(d2), "+f"(d3));
            };
            mbar_wait(sb + BAR_XFULL, 0);
            load_a0(0);
            mbar_wait(sb + BAR_W, 0);
            load_w(w0, 0);
            auto odd_stage = [&](int it, bool first, bool last) {
                wg_wait<1>();
                if (!first) release(old);
                load_a1(it);
                load_w(w1, 2 * it + 1);
                peek();
                dot(a0, w0);
                if (last && wg == 1) bar_sync<4, 256>();
                issue1s(a1);
                if (last && wg == 0) bar_arrive<4, 256>();
            };
            issue1(a0, 0);
            #pragma unroll
            for (int it = 0; it < 6; it++) {
                const bool xok = mbar_try(sb + BAR_XFULL + 8 * (it + 1), 0);
                odd_stage(it, it == 0, false);
                wg_wait<2>(); release(old);
                if (!xok) mbar_wait(sb + BAR_XFULL + 8 * (it + 1), 0);
                load_a0(it + 1);
                load_w(w0, 2 * it + 2);
                peek();
                dot(a1, w1);
                issue1(a0, 1);
            }
            odd_stage(6, false, true);
            wg_wait<2>(); release(old);
            load_a0(0);
            peek();
            dot(a1, w1);
            wg_wait<1>();
            reg_fence(agk);
            #pragma unroll
            for (int i = 0; i < 32; i++) hp[i] = pack_relu_bf16(agk[2 * i], agk[2 * i + 1]);
            reg_fence_part<0, 32>(hp);
            g0 = d0 + d2; g1 = d1 + d3;
        }

        float aq[28], au[64];
        {
            auto issue2 = [&](uint32_t (&a)[8], int sd) {
                const uint32_t b = begin();
                wgmma_rs56<HI128>(aq, a[0], a[1], a[2], a[3], b + LO128, sd);
                wgmma_rs128<HI128>(au, a[0], a[1], a[2], a[3], b + LO128X2 + 128, sd);
                wgmma_rs56<HI128>(aq, a[4], a[5], a[6], a[7], b + LO128 + 384, 1);
                wgmma_rs128<HI128>(au, a[4], a[5], a[6], a[7], b + LO128X2 + 512, 1);
            };
            const uint32_t st_base = wg == 0 ? OFF_STG : OFF_RING + 12288, st_step = wg == 0 ? 2048 : SLOT_BYTES, st_v = wg == 0 ? 8192 : 2048;
            const uint32_t sk = sb + st_base + w4 * st_step + (lane & 15) * 128;
            float tok = kLog2e;
            uint32_t pk[16];
            pk[14] = 0u; pk[15] = 0u;
            auto stage_k = [&](int lo, int hi) {
                #pragma unroll
                for (int i = 0; i < 14; i++) if (i >= lo && i < hi) pk[i] = pack_bf16(phi(agk[64 + 2 * i], tok), phi(agk[65 + 2 * i], tok));
                #pragma unroll
                for (int t = 0; t < 4; t++) {
                    const int need = t < 3 ? 4 * t + 4 : 14;
                    if (need > lo && need <= hi) stsm4(sk + (lx ^ (t * 32)), pk[4 * t], pk[4 * t + 1], pk[4 * t + 2], pk[4 * t + 3]);
                }
                #pragma unroll
                for (int i = 0; i < 14; i++) if (i >= lo && i < hi) asm volatile("" : "+r"(pk[i]));
            };
            issue2(a0, 0); commit();
            tok = after_issue(kLog2e, zero);
            retire();
            reg_fence(av);
            if (wg == 0) bar_arrive<8, 256>();
            load_a1(0); peek();
            uint32_t pv[14];
            #pragma unroll
            for (int i = 0; i < 14; i++) pv[i] = pack_bf16(av[2 * i], av[2 * i + 1]);
            if (wg == 1) bar_sync<8, 256>();
            {
                const uint32_t ones = q4 == 0 ? 0x3f803f80u : 0u;
                #pragma unroll
                for (int t = 0; t < 3; t++) stsm4(sk + st_v + (lx ^ (t * 32)), pv[4 * t], pv[4 * t + 1], pv[4 * t + 2], pv[4 * t + 3]);
                stsm4(sk + st_v + (lx ^ 96), pv[12], pv[13], ones, ones);
            }
            stage_k(0, 2);
            issue2(a1, 1); commit();
            tok = after_issue(kLog2e, zero);
            retire(); load_a0(1); peek();
            stage_k(2, 5);
            issue2(a0, 1); commit();
            tok = after_issue(kLog2e, zero);
            retire(); load_a1(1); peek();
            stage_k(5, 8);
            issue2(a1, 1); commit();
            tok = after_issue(kLog2e, zero);
            retire(); load_a0(2); peek();
            stage_k(8, 11);
            issue2(a0, 1); commit();
            tok = after_issue(kLog2e, zero);
            retire(); load_a1(2); peek();
            stage_k(11, 14);
            issue2(a1, 1); commit();
            retire(); load_a0(3); peek();
            fence_async_smem();
            if (wg == 0) bar_sync<1, 128>(); else bar_sync<2, 128>();
            float kv[32];
            issue2(a0, 1);
            {
                const uint32_t dk = dsb + LO128 + (st_base >> 4), ds = st_step >> 4, dv = st_v >> 4;
                #pragma unroll
                for (int ks = 0; ks < 4; ks++) wgmma_ss64_tt<HI128>(kv, dk + ks * ds, dk + ks * ds + dv, ks);
            }
            commit();
            tok = after_issue(-kLog2e, zero);
            retire(); load_a1(3); peek();
            {
                g0 += __shfl_xor_sync(0xffffffffu, g0, 1); g1 += __shfl_xor_sync(0xffffffffu, g1, 1);
                g0 += __shfl_xor_sync(0xffffffffu, g0, 2); g1 += __shfl_xor_sync(0xffffffffu, g1, 2);
                const uint32_t lg = pack_bf16(g0, g1);
                float e0, e1;
                asm("ex2.approx.ftz.f32 %0, %1;" : "=f"(e0) : "f"(bf_lo(lg) * tok));
                asm("ex2.approx.ftz.f32 %0, %1;" : "=f"(e1) : "f"(bf_hi(lg) * tok));
                const uint32_t gg = pack_bf16(rcp(1.f + e0), rcp(1.f + e1));
                g0 = bf_lo(gg); g1 = bf_hi(gg);
                asm volatile("" : "+f"(g0), "+f"(g1));
            }
            issue2(a1, 1); commit();
            retire(); load_a0(4); peek();
            reg_fence(kv);
            if (wg == 0) { bar_arrive<5, 256>(); bar_sync<1, 128>(); } else bar_sync<5, 256>();
            auto stage_kv = [&](int hh) {
                const int d = w4 * 16 + g8 + 8 * hh;
                const bool h0 = d < 28;
                const uint32_t rowa = sb + OFF_STG + wg * 8192 + d * 128 + q4 * 8;
                #pragma unroll
                for (int t = 0; t < 4; t++) {
                    float v0 = h0 ? kv[4 * t + 2 * hh] : kv[4 * t + 12 + 2 * hh];
                    float v1 = h0 ? kv[4 * t + 2 * hh + 1] : kv[4 * t + 13 + 2 * hh];
                    if (t == 0 && !h0 && q4 == 0) v0 = kv[28 + 2 * hh];
                    if (d < 56 && !(t == 3 && h0 && q4 == 2))
                        asm volatile("st.shared.v2.f32 [%0], {%1, %2};" :: "r"(rowa + ((t ^ (g8 & 3)) << 5)), "f"(v0), "f"(v1) : "memory");
                }
                if (h0 && q4 == 0)
                    asm volatile("st.shared.v2.f32 [%0], {%1, %1};" :: "r"(rowa + ((3 ^ (g8 & 3)) << 5) + 16), "f"(kv[28 + 2 * hh]) : "memory");
            };
            stage_kv(0);
            issue2(a0, 1); commit();
            retire(); load_a1(4); peek();
            stage_kv(1);
            __syncwarp();
            if (lane == 0) mbar_arrive(sb + BAR_KVDONE);
            issue2(a1, 1); commit();
            retire(); load_a0(5); peek();
            auto prescale = [&](int lo, int hi) {
                const float t0 = after_issue(1.f - g0, zero), t1 = after_issue(1.f - g1, zero);
                const uint32_t s0 = pack_bf16(t0, t0), s1 = pack_bf16(t1, t1);
                #pragma unroll
                for (int i = 0; i < 32; i++) if (i >= lo && i < hi) { hp[i] = mul_bf16x2(hp[i], (i & 1) ? s1 : s0); asm volatile("" : "+r"(hp[i])); }
            };
            prescale(0, 16);
            issue2(a0, 1); commit();
            retire(); load_a1(5); peek();
            prescale(16, 32);
            issue2(a1, 1); commit();
            retire(); load_a0(6); peek();
            if (wg == 1) bar_sync<4, 256>();
            issue2(a0, 1); commit();
            retire(); load_a1(6); peek();
            const uint32_t b = begin();
            wgmma_rs128<HI128>(au, a1[0], a1[1], a1[2], a1[3], b + LO128X2 + 128, 1);
            wgmma_rs128<HI128>(au, a1[4], a1[5], a1[6], a1[7], b + LO128X2 + 512, 1);
            wg_commit();
            wgmma_rs56<HI128>(aq, a1[0], a1[1], a1[2], a1[3], b + LO128, 1);
            wgmma_rs56<HI128>(aq, a1[4], a1[5], a1[6], a1[7], b + LO128 + 384, 1);
            commit();
            if (wg == 0) bar_arrive<4, 256>();
            wg_wait<2>(); release(old);
            load_a0(0); peek();
            wg_wait<1>();
            reg_fence(au);
        }
        #pragma unroll
        for (int i = 0; i < 32; i++) hp[i] = mul_bf16x2(hp[i], pack_bf16(au[2 * i], au[2 * i + 1]));
        reg_fence_part<0, 32>(hp);

        float ag[96];
        uint32_t op[16];
        {
            auto issue3 = [&](uint32_t (&a)[8], int sd) {
                const uint32_t b = begin();
                wgmma_rs192<HI64>(ag, a[0], a[1], a[2], a[3], b + LO64, sd);
                wgmma_rs192<HI64>(ag, a[4], a[5], a[6], a[7], b + LO64 + 384, 1);
            };
            uint32_t pq[16];
            float nd[32];
            uint32_t a2[8];
            auto load3 = [&](int st) {
                uint32_t (&a)[8] = st % 3 == 0 ? a0 : st % 3 == 1 ? a1 : a2;
                const uint32_t p = xa + (st >> 1) * 16384, x0 = lx ^ ((st & 1) * 64);
                ldsm4(a, p + x0); ldsm4(a + 4, p + (x0 ^ 32));
            };
            pq[14] = 0u; pq[15] = 0u;
            bool aux = false;
            #pragma unroll
            for (int st = 0; st < 14; st++) {
                uint32_t (&a)[8] = st % 3 == 0 ? a0 : st % 3 == 1 ? a1 : a2;
                if (st == 0) load3(2);
                if (st == 11 && wg == 1) bar_sync<4, 256>();
                if (st == 12) {
                    if (!aux) mbar_wait(sb + BAR_AUX, 0);
                }
                issue3(a, st);
                if (st == 12) {
                    const uint32_t dk = dsb + LO128 + ((OFF_STG + 8192) >> 4);
                    #pragma unroll
                    for (int ks = 0; ks < 4; ks++) wgmma_rs64<HI128>(nd, pq[4 * ks], pq[4 * ks + 1], pq[4 * ks + 2], pq[4 * ks + 3], dk + ks * 128, ks);
                }
                commit();
                if (st == 13) { if (wg == 0) bar_arrive<4, 256>(); break; }
                const float tok = (st >= 1 && st < 8) ? after_issue(kLog2e, zero) : 0.f;
                if (st == 11) aux = mbar_try(sb + BAR_AUX, 0);
                peek();
                retire();
                if (st == 0) { reg_fence(aq); load3(1); }
                else if (st + 2 < 14) load3(st + 2);
                if (st >= 1 && st < 8) {
                    const int i = 2 * st - 2;
                    pq[i] = pack_bf16(phi(aq[2 * i], tok), phi(aq[2 * i + 1], tok));
                    pq[i + 1] = pack_bf16(phi(aq[2 * i + 2], tok), phi(aq[2 * i + 3], tok));
                    asm volatile("" : "+r"(pq[i]), "+r"(pq[i + 1]));
                }
            }
            ready = mbar_try(sb + p4_bar(0), p4_par(0));
            retire();
            reg_fence(nd);
            const int src = lane & ~3;
            const float s00 = g0 * rcp(__shfl_sync(0xffffffffu, nd[28], src) + 1e-6f);
            const float s01 = g0 * rcp(__shfl_sync(0xffffffffu, nd[29], src) + 1e-6f);
            const float s10 = g1 * rcp(__shfl_sync(0xffffffffu, nd[30], src) + 1e-6f);
            const float s11 = g1 * rcp(__shfl_sync(0xffffffffu, nd[31], src) + 1e-6f);
            #pragma unroll
            for (int t = 0; t < 7; t++) {
                const bool h1 = t > 3 || (t == 3 && q4 >= 2);
                const float sa = h1 ? s01 : s00, sc = h1 ? s11 : s10;
                op[2 * t] = pack_bf16(nd[4 * t] * sa, nd[4 * t + 1] * sa);
                op[2 * t + 1] = pack_bf16(nd[4 * t + 2] * sc, nd[4 * t + 3] * sc);
            }
            op[14] = 0u; op[15] = 0u;
            reg_fence(op);
        }

        float oa[32], ob[32];
        int c = j == 7 ? 0 : j;
        const int wsh = __shfl_sync(0xffffffffu, warp * 16, 0);
        const uint32_t sh0 = par * 768, sh1 = par * 1024;
        bool ready2 = false;
        auto issue_d = [&](float (&o)[32], int c0, int half) {
            const int n = 3 * c0;
            if (half == 0) {
                if (!ready) mbar_wait(sb + p4_bar(n), p4_par(n));
                if (!ready2) mbar_wait(sb + p4_bar(n + 1), p4_par(n + 1));
                ready = mbar_try(sb + p4_bar(n + 2), p4_par(n + 2));
            }
            wg_fence();
            const uint32_t b = dsb + LO128 + (p4_off(n) >> 4);
            #pragma unroll
            for (int ks = 7 * half; ks < 7 * half + 7; ks++)
                wgmma_rs64<HI128>(o, hp[4 * ks], hp[4 * ks + 1], hp[4 * ks + 2], hp[4 * ks + 3],
                                  b + ks * 128 + (ks < 8 ? sh0 : 0u - sh1), ks);
        };
        auto issue_o = [&](float (&o)[32], int c0) {
            const int n = 3 * c0 + 2;
            if (!ready) mbar_wait(sb + p4_bar(n), p4_par(n));
            if (c0 < 6) {
                ready = mbar_try(sb + p4_bar(n + 1), p4_par(n + 1));
                ready2 = mbar_try(sb + p4_bar(n + 2), p4_par(n + 2));
            }
            wg_fence();
            const uint32_t b = dsb + LO128 + (p4_off(n) >> 4);
            #pragma unroll
            for (int ks = 0; ks < 4; ks++) wgmma_rs64<HI128>(o, op[4 * ks], op[4 * ks + 1], op[4 * ks + 2], op[4 * ks + 3], b + ks * 128, 1);
            wg_commit();
        };
        auto ship = [&](float (&o)[32], int c0) {
            reg_fence(o);
            const uint32_t so = xa + OFF_OUT + (c0 & 1) * 16384;
            #pragma unroll
            for (int t = 0; t < 4; t++)
                stsm4(so + (lx ^ (t * 32)), pack_bf16(o[8 * t], o[8 * t + 1]), pack_bf16(o[8 * t + 2], o[8 * t + 3]),
                      pack_bf16(o[8 * t + 4], o[8 * t + 5]), pack_bf16(o[8 * t + 6], o[8 * t + 7]));
            fence_async_smem();
            __syncwarp();
            if (elect_one()) {
                tma_reduce2d(&mp.out, sb + OFF_OUT + (c0 & 1) * 16384 + wsh * 128, 64 * c, row0 + wsh);
                asm volatile("cp.async.bulk.commit_group;" ::: "memory");
            }
            if (++c == 7) c = 0;
        };
        auto finish_h = [&]() {
            reg_fence(ag);
            release(cur);
            const uint32_t s0 = pack_bf16(1.f - g0, 1.f - g0), s1 = pack_bf16(1.f - g1, 1.f - g1);
            #pragma unroll
            for (int i = 0; i < 24; i++)
                hp[32 + i] = mul_bf16x2(mul_bf16x2(pack_relu_bf16(ag[2 * i], ag[2 * i + 1]), (i & 1) ? s1 : s0),
                                        pack_bf16(ag[48 + 2 * i], ag[49 + 2 * i]));
            reg_fence_part<32, 56>(hp);
        };
        ready2 = mbar_try(sb + p4_bar(1), p4_par(1));
        wg_wait<0>();
        finish_h();
        #pragma unroll
        for (int c0 = 0; c0 < 7; c0++) {
            float (&o)[32] = (c0 & 1) ? ob : oa;
            if (c0 > 0 || wg == 1) turn_wait();
            issue_d(o, c0, 0);
            issue_d(o, c0, 1);
            issue_o(o, c0);
            if (!(c0 == 6 && wg == 1)) turn_pass();
            if (c0 >= 2) {
                if (elect_one()) asm volatile("cp.async.bulk.wait_group.read 1;" ::: "memory");
                __syncwarp();
            }
            wg_wait<0>();
            if (c0 < 2 && signaller) mbar_arrive_cluster(empty_dst + (BAR_REFILL - BAR_EMPTY) + 8 * c0);
            ship(o, c0);
        }
        if (elect_one()) asm volatile("cp.async.bulk.wait_group.read 0;" ::: "memory");
    }
}

typedef CUresult (*EncodeFn)(CUtensorMap*, CUtensorMapDataType, cuuint32_t, void*, const cuuint64_t*, const cuuint64_t*,
                             const cuuint32_t*, const cuuint32_t*, CUtensorMapInterleave, CUtensorMapSwizzle,
                             CUtensorMapL2promotion, CUtensorMapFloatOOBfill);

void make_map(EncodeFn enc, CUtensorMap* m, const void* base, int rank, const cuuint64_t* dims, const cuuint64_t* strides,
              cuuint32_t b0, cuuint32_t b1, cuuint32_t b2, CUtensorMapSwizzle sw) {
    const cuuint32_t es[3] = {1, 1, 1}, box[3] = {b0, b1, b2};
    enc(m, CU_TENSOR_MAP_DATA_TYPE_BFLOAT16, rank, const_cast<void*>(base), dims, strides, box, es,
        CU_TENSOR_MAP_INTERLEAVE_NONE, sw, CU_TENSOR_MAP_L2_PROMOTION_L2_128B, CU_TENSOR_MAP_FLOAT_OOB_FILL_NONE);
}

}

extern "C" void kernel_launch(void* const* d_in, const int* in_sizes, int n_in, void* d_out, int out_size) {
    (void)in_sizes; (void)n_in; (void)out_size;
    static EncodeFn enc = nullptr;
    if (!enc) {
        void* fn = nullptr;
        cudaDriverEntryPointQueryResult st;
        cudaGetDriverEntryPoint("cuTensorMapEncodeTiled", &fn, cudaEnableDefault, &st);
        enc = (EncodeFn)fn;
        cudaFuncSetAttribute(fused_kernel, cudaFuncAttributeMaxDynamicSharedMemorySize, SMEM_BYTES);
    }
    Maps mp;
    const cuuint64_t dimx[2] = {kD, kS}, dimd[2] = {kD, kF}, dimo[2] = {kD, kD}, strd[1] = {kD * 2};
    make_map(enc, &mp.x, d_in[0], 2, dimx, strd, 64, 128, 1, CU_TENSOR_MAP_SWIZZLE_128B);
    make_map(enc, &mp.out, d_out, 2, dimx, strd, 64, 16, 1, CU_TENSOR_MAP_SWIZZLE_128B);
    make_map(enc, &mp.d, d_in[6], 2, dimd, strd, 64, 56, 1, CU_TENSOR_MAP_SWIZZLE_128B);
    make_map(enc, &mp.o, d_in[2], 2, dimo, strd, 64, 32, 1, CU_TENSOR_MAP_SWIZZLE_128B);
    const cuuint64_t dimq[3] = {kD, kD, 3}, strq[2] = {3 * kD * 2, kD * 2};
    make_map(enc, &mp.kv, d_in[1], 3, dimq, strq, 56, 16, 2, CU_TENSOR_MAP_SWIZZLE_128B);
    make_map(enc, &mp.q, d_in[1], 3, dimq, strq, 56, 16, 1, CU_TENSOR_MAP_SWIZZLE_128B);
    const cuuint64_t dimf[3] = {32, kD, kF / 32}, strf[2] = {kF * 2, 64};
    const cuuint64_t dimw[3] = {64, kD, kF / 64}, strw[2] = {kF * 2, 128};
    make_map(enc, &mp.g4, d_in[4], 3, dimw, strw, 64, 16, 2, CU_TENSOR_MAP_SWIZZLE_128B);
    make_map(enc, &mp.u4, d_in[5], 3, dimw, strw, 64, 16, 2, CU_TENSOR_MAP_SWIZZLE_128B);
    make_map(enc, &mp.g3, d_in[4], 3, dimf, strf, 32, 16, 3, CU_TENSOR_MAP_SWIZZLE_64B);
    make_map(enc, &mp.u3, d_in[5], 3, dimf, strf, 32, 16, 3, CU_TENSOR_MAP_SWIZZLE_64B);
    fused_kernel<<<NCTA, NTHREADS, SMEM_BYTES>>>(mp, (const __nv_bfloat16*)d_in[7], (__nv_bfloat16*)d_out, 0u);
}
```
